```python
import torch

def _softmax(x, axis=-1):
    return torch.softmax(x, dim=axis)
def _gelu(x):
    return torch.nn.functional.gelu(x, approximate="tanh")
def _silu(x):
    return torch.nn.functional.silu(x)
def _sigmoid(x):
    return torch.sigmoid(x)
def _layernorm(x, axis=-1, eps=1e-5):
    m = x.mean(dim=axis, keepdim=True)
    v = x.var(dim=axis, keepdim=True, unbiased=False)
    return (x - m) / torch.sqrt(v + eps)
def _scatter_add(tgt, idx, src, axis=0):
    return tgt.clone().index_add_(axis, idx, src)
def _segment_sum(src, seg, n):
    out = torch.zeros((n,) + src.shape[1:], dtype=src.dtype)
    return out.index_add_(0, seg, src)
def _pad(x, pw):
    flat = tuple(v for pair in reversed(pw) for v in pair)
    return torch.nn.functional.pad(x, flat)

kernel_name = 'sequential_preLN__gqa_block_cached__geglu_ffn__decode'

def setup_inputs():

    _w = (lambda a: (lambda t: t.to(torch.bfloat16) if t.is_floating_point() else t)(torch.as_tensor(a)))
    def _A_setup():
        B, Sq, D = 4, 1, 512
        Hq, Hkv, Sk, Dh = 32, 8, 8192, 128
        assert Hq % Hkv == 0, (Hq, Hkv)
        return {
            "x": _w((lambda *s: torch.randn(*s, dtype=torch.bfloat16) * 0.05)(B, Sq, D)),
            "k_cache": _w((lambda *s: torch.randn(*s, dtype=torch.bfloat16) * 3.2)(B, Hkv, Sk, Dh)),
            "v_cache": _w((lambda *s: torch.randn(*s, dtype=torch.bfloat16) * 0.4)(B, Hkv, Sk, Dh)),
            "wq": _w((lambda *s: torch.randn(*s, dtype=torch.bfloat16) * 3.2)(D, Hq * Dh) * (D ** -0.5)),
            "wo": _w((lambda *s: torch.randn(*s, dtype=torch.bfloat16) * 0.4)(Hq * Dh, D) * ((Hq * Dh) ** -0.5)),
        }
    _A_in = _A_setup()

    def _B_setup():
        B, S, D, F = 4, 1, 512, 1792
        return {
            "x": _w((lambda *s: torch.randn(*s, dtype=torch.bfloat16) * 0.05)(B, S, D)),
            "w_gate": _w((lambda *s: torch.randn(*s, dtype=torch.bfloat16) * 0.05)(D, F)),
            "w_up": _w((lambda *s: torch.randn(*s, dtype=torch.bfloat16) * 0.05)(D, F)),
            "w_down": _w((lambda *s: torch.randn(*s, dtype=torch.bfloat16) * 0.05)(F, D)),
        }
    _B_in = _B_setup()

    return {
        "A_x": _A_in["x"],
        "A_k_cache": _A_in["k_cache"],
        "A_v_cache": _A_in["v_cache"],
        "A_wq": _A_in["wq"],
        "A_wo": _A_in["wo"],
        "B_x": _B_in["x"],
        "B_w_gate": _B_in["w_gate"],
        "B_w_up": _B_in["w_up"],
        "B_w_down": _B_in["w_down"],
    }

def reference(A_x, A_k_cache, A_v_cache, A_wq, A_wo, B_x, B_w_gate, B_w_up, B_w_down):
    def _A_ref(x, k_cache, v_cache, wq, wo):
        B, Sq, D = x.shape
        Hq, Dh = 32, 128
        Hkv = k_cache.shape[1]
        rep = Hq // Hkv
        q = (lambda x, *d: x.permute(*d))((x @ wq).reshape(B, Sq, Hq, Dh), 0, 2, 1, 3)
        k = (lambda x, n, axis: torch.repeat_interleave(x, n, dim=axis))(k_cache, rep, axis=1)
        v = (lambda x, n, axis: torch.repeat_interleave(x, n, dim=axis))(v_cache, rep, axis=1)
        scores = torch.einsum("bhqd,bhkd->bhqk", q, k) * (Dh ** -0.5)
        p = _softmax(scores, axis=-1)
        o = torch.einsum("bhqk,bhkd->bhqd", p, v)
        return (lambda x, *d: x.permute(*d))(o, 0, 2, 1, 3).reshape(B, Sq, Hq * Dh) @ wo

    def _B_ref(x, w_gate, w_up, w_down):
        return (_gelu(x @ w_gate) * (x @ w_up)) @ w_down

    x = A_x
    h = x + _A_ref(_layernorm(x, axis=-1), A_k_cache, A_v_cache, A_wq, A_wo)
    h2 = h + _B_ref(_layernorm(h, axis=-1), B_w_gate, B_w_up, B_w_down)
    return h2
```

```cpp
#include <cuda_runtime.h>
#include <cuda_bf16.h>
#include <cuda.h>
#include <stdint.h>

namespace {

constexpr int NCTA      = 128;
constexpr int NTHREADS  = 288;
constexpr int SLOT      = 32768;
constexpr int NSLOT     = 6;
constexpr int NTILE     = 16;
constexpr int NFFN      = 112;
#define DEPTH 2
constexpr int RESET_TILE = 9;
constexpr uint32_t SENT = 0xFFFFFFFFu;

constexpr int OFF_XN   = NSLOT * SLOT;
constexpr int XN_PITCH = 1040;
constexpr int OFF_QS   = OFF_XN + 4 * XN_PITCH;
constexpr int QS_PITCH = 272;
constexpr int OFF_P    = OFF_QS + 4 * QS_PITCH;
constexpr int OFF_RED  = OFF_P + 4 * QS_PITCH;
constexpr int OFF_MX   = OFF_RED + 4096;
constexpr int OFF_L    = OFF_MX + 64;
constexpr int OFF_ACT  = OFF_L + 128;
constexpr int OFF_RED2 = OFF_ACT + 128;
constexpr int OFF_BAR  = OFF_RED2 + 512;
constexpr int OFF_MISC = OFF_BAR + 128;
constexpr int SMEM_USED = OFF_MISC + 64;
constexpr int SMEM_BYTES = SMEM_USED + 1024;

__device__ uint2    g_q[4 * 2048];
__device__ float    g_partO[32 * 4 * 4 * 128];
__device__ float2   g_ml[32 * 4 * 4];
__device__ float    g_ypart[4 * 32 * 32 * 16];
__device__ uint16_t g_h[4 * 512];
__device__ float    g_dpart[4 * 32 * NFFN * 16];
__device__ unsigned g_cnt0, g_cnt1;
#define TS(i)
#define TSP(i)

__device__ __forceinline__ uint32_t smem_u32(const void* p) { return (uint32_t)__cvta_generic_to_shared(p); }
__device__ __forceinline__ void mbar_init(uint32_t bar, uint32_t cnt) {
    asm volatile("mbarrier.init.shared::cta.b64 [%0], %1;" ::"r"(bar), "r"(cnt) : "memory");
}
__device__ __forceinline__ void mbar_expect_tx(uint32_t bar, uint32_t bytes) {
    asm volatile("mbarrier.arrive.expect_tx.shared::cta.b64 _, [%0], %1;" ::"r"(bar), "r"(bytes) : "memory");
}
__device__ __forceinline__ void mbar_arrive(uint32_t bar) {
    asm volatile("mbarrier.arrive.shared::cta.b64 _, [%0];" ::"r"(bar) : "memory");
}
__device__ __forceinline__ bool mbar_try(uint32_t bar, uint32_t parity) {
    uint32_t ok;
    asm volatile("{\n.reg .pred p;\nmbarrier.try_wait.parity.shared::cta.b64 p, [%1], %2;\nselp.u32 %0, 1, 0, p;\n}"
                 : "=r"(ok) : "r"(bar), "r"(parity) : "memory");
    return ok != 0;
}
constexpr long long TIMEOUT_CYCLES = 4000000000LL;
__device__ __forceinline__ void mbar_wait(uint32_t bar, uint32_t parity) {
    if (mbar_try(bar, parity)) return;
    long long t0 = clock64();
    while (!mbar_try(bar, parity)) {
        if (clock64() - t0 > TIMEOUT_CYCLES) __trap();
    }
}
__device__ __forceinline__ void tma2d(uint32_t dst, const CUtensorMap* m, int c0, int c1, uint32_t bar) {
    asm volatile("cp.async.bulk.tensor.2d.shared::cluster.global.mbarrier::complete_tx::bytes [%0], [%1, {%3, %4}], [%2];"
                 ::"r"(dst), "l"(m), "r"(bar), "r"(c0), "r"(c1) : "memory");
}
__device__ __forceinline__ void tma3d(uint32_t dst, const CUtensorMap* m, int c0, int c1, int c2, uint32_t bar) {
    asm volatile("cp.async.bulk.tensor.3d.shared::cluster.global.mbarrier::complete_tx::bytes [%0], [%1, {%3, %4, %5}], [%2];"
                 ::"r"(dst), "l"(m), "r"(bar), "r"(c0), "r"(c1), "r"(c2) : "memory");
}
__device__ __forceinline__ void tma3d_hint(uint32_t dst, const CUtensorMap* m, int c0, int c1, int c2, uint32_t bar, uint64_t pol) {
    asm volatile("cp.async.bulk.tensor.3d.shared::cluster.global.mbarrier::complete_tx::bytes.L2::cache_hint [%0], [%1, {%3, %4, %5}], [%2], %6;"
                 ::"r"(dst), "l"(m), "r"(bar), "r"(c0), "r"(c1), "r"(c2), "l"(pol) : "memory");
}
__device__ __forceinline__ void ldsm4(uint32_t (&r)[4], uint32_t addr) {
    asm volatile("ldmatrix.sync.aligned.m8n8.x4.shared.b16 {%0,%1,%2,%3}, [%4];"
                 : "=r"(r[0]), "=r"(r[1]), "=r"(r[2]), "=r"(r[3]) : "r"(addr) : "memory");
}
__device__ __forceinline__ void ldsm4t(uint32_t (&r)[4], uint32_t addr) {
    asm volatile("ldmatrix.sync.aligned.m8n8.x4.trans.shared.b16 {%0,%1,%2,%3}, [%4];"
                 : "=r"(r[0]), "=r"(r[1]), "=r"(r[2]), "=r"(r[3]) : "r"(addr) : "memory");
}
__device__ __forceinline__ void mma16816(float (&c)[4], const uint32_t (&a)[4], uint32_t b0, uint32_t b1) {
    asm volatile("mma.sync.aligned.m16n8k16.row.col.f32.bf16.bf16.f32 {%0,%1,%2,%3}, {%4,%5,%6,%7}, {%8,%9}, {%0,%1,%2,%3};"
                 : "+f"(c[0]), "+f"(c[1]), "+f"(c[2]), "+f"(c[3])
                 : "r"(a[0]), "r"(a[1]), "r"(a[2]), "r"(a[3]), "r"(b0), "r"(b1));
}
__device__ __forceinline__ void cbar() { asm volatile("bar.sync 1, 256;" ::: "memory"); }
__device__ __forceinline__ uint4 ld_poll4(const void* p) {
    uint4 v;
    asm volatile("ld.relaxed.gpu.global.v4.u32 {%0,%1,%2,%3}, [%4];" : "=r"(v.x), "=r"(v.y), "=r"(v.z), "=r"(v.w) : "l"(p) : "memory");
    return v;
}
__device__ __forceinline__ uint2 ld_poll2(const void* p) {
    uint2 v;
    asm volatile("ld.relaxed.gpu.global.v2.u32 {%0,%1}, [%2];" : "=r"(v.x), "=r"(v.y) : "l"(p) : "memory");
    return v;
}
__device__ __forceinline__ void st_rel32(void* p, uint32_t v) { asm volatile("st.relaxed.gpu.global.u32 [%0], %1;" ::"l"(p), "r"(v) : "memory"); }
__device__ __forceinline__ void st_rel16(void* p, uint16_t v) { asm volatile("st.relaxed.gpu.global.u16 [%0], %1;" ::"l"(p), "h"(v) : "memory"); }
__device__ __forceinline__ void st_rel64(void* p, uint32_t a, uint32_t b) { asm volatile("st.relaxed.gpu.global.v2.u32 [%0], {%1,%2};" ::"l"(p), "r"(a), "r"(b) : "memory"); }
__device__ __forceinline__ void st_rel128(void* p, uint32_t v) { asm volatile("st.relaxed.gpu.global.v4.u32 [%0], {%1,%1,%1,%1};" ::"l"(p), "r"(v) : "memory"); }
__device__ __forceinline__ bool valid4(const uint4& v) { return v.x != SENT && v.y != SENT && v.z != SENT && v.w != SENT; }
__device__ __forceinline__ bool valid8h(const uint4& v) {
    return (__vcmpeq2(v.x, SENT) | __vcmpeq2(v.y, SENT) | __vcmpeq2(v.z, SENT) | __vcmpeq2(v.w, SENT)) == 0;
}
struct Spin {
    long long t0; bool started = false;
    __device__ __forceinline__ void tick() {
        if (!started) { t0 = clock64(); started = true; }
        else if (clock64() - t0 > TIMEOUT_CYCLES) __trap();
    }
};
__device__ __forceinline__ float bf16r(float x) { return __bfloat162float(__float2bfloat16_rn(x)); }
__device__ __forceinline__ uint32_t pack_bf16(float lo, float hi) {
    uint32_t r; asm("cvt.rn.bf16x2.f32 %0, %1, %2;" : "=r"(r) : "f"(hi), "f"(lo)); return r;
}
__device__ __forceinline__ float bf_lo(uint32_t v) { return __uint_as_float(v << 16); }
__device__ __forceinline__ float bf_hi(uint32_t v) { return __uint_as_float(v & 0xFFFF0000u); }
__device__ __forceinline__ uint32_t hmax2(uint32_t a, uint32_t b) {
    uint32_t r; asm("max.bf16x2 %0, %1, %2;" : "=r"(r) : "r"(a), "r"(b)); return r;
}
__device__ __forceinline__ float ex2(float x) { float r; asm("ex2.approx.ftz.f32 %0, %1;" : "=f"(r) : "f"(x)); return r; }

__device__ __forceinline__ void ln_row_store(const uint4& a, const uint4& b, unsigned char* row, int lane) {
    float v[16];
    v[0] = bf_lo(a.x); v[1] = bf_hi(a.x); v[2] = bf_lo(a.y); v[3] = bf_hi(a.y);
    v[4] = bf_lo(a.z); v[5] = bf_hi(a.z); v[6] = bf_lo(a.w); v[7] = bf_hi(a.w);
    v[8] = bf_lo(b.x); v[9] = bf_hi(b.x); v[10] = bf_lo(b.y); v[11] = bf_hi(b.y);
    v[12] = bf_lo(b.z); v[13] = bf_hi(b.z); v[14] = bf_lo(b.w); v[15] = bf_hi(b.w);
    const float shift = __shfl_sync(0xffffffffu, v[0], 0);
    float s = 0.f, ss = 0.f;
#pragma unroll
    for (int i = 0; i < 16; i++) { float d = v[i] - shift; s += d; ss = fmaf(d, d, ss); }
#pragma unroll
    for (int o = 16; o > 0; o >>= 1) { s += __shfl_xor_sync(0xffffffffu, s, o); ss += __shfl_xor_sync(0xffffffffu, ss, o); }
    const float md = s * (1.0f / 512.0f);
    const float var = fmaxf(ss * (1.0f / 512.0f) - md * md, 0.f);
    const float m = bf16r(shift + md);
    const float sd = bf16r(sqrtf(bf16r(bf16r(var) + 1e-5f)));
    const float rs = 1.0f / sd;
    uint32_t o[8];
#pragma unroll
    for (int i = 0; i < 8; i++) o[i] = pack_bf16(bf16r(v[2 * i] - m) * rs, bf16r(v[2 * i + 1] - m) * rs);
    *reinterpret_cast<uint4*>(row + lane * 16) = make_uint4(o[0], o[1], o[2], o[3]);
    *reinterpret_cast<uint4*>(row + 512 + lane * 16) = make_uint4(o[4], o[5], o[6], o[7]);
}

__global__ void __launch_bounds__(NTHREADS, 1)
fused_decode_kernel(const __grid_constant__ CUtensorMap tmK, const __grid_constant__ CUtensorMap tmV,
                    const __grid_constant__ CUtensorMap tmWq, const __grid_constant__ CUtensorMap tmWo,
                    const __grid_constant__ CUtensorMap tmWg, const __grid_constant__ CUtensorMap tmWu,
                    const __grid_constant__ CUtensorMap tmWd,
                    const __nv_bfloat16* __restrict__ x, __nv_bfloat16* __restrict__ out)
{
    extern __shared__ unsigned char smem_raw[];
    unsigned char* smem = reinterpret_cast<unsigned char*>((reinterpret_cast<uintptr_t>(smem_raw) + 1023) & ~(uintptr_t)1023);
    const uint32_t sbase = smem_u32(smem);
    const uint32_t bar_full = sbase + OFF_BAR, bar_empty = sbase + OFF_BAR + 48;
    const int tid = threadIdx.x, warp = tid >> 5, lane = tid & 31;
    const int cta = blockIdx.x;

    TS(0);
    if (tid == 0) {
        for (int i = 0; i < NSLOT; i++) { mbar_init(bar_full + 8 * i, 1); mbar_init(bar_empty + 8 * i, 8); }
        asm volatile("fence.mbarrier_init.release.cluster;" ::: "memory");
    }
    __syncthreads();

    if (warp == 8) {
        if (lane == 0) {
            uint64_t pol;
            asm volatile("createpolicy.fractional.L2::evict_first.b64 %0, 1.0;" : "=l"(pol));
            const int key0 = cta * (NTILE * 128);
            const int nseq = (cta < NFFN) ? 36 : 34;
            for (int i = 0; i < nseq; i++) {
                const int slot = i % NSLOT;
                if (i >= NSLOT) mbar_wait(bar_empty + 8 * slot, ((i / NSLOT) - 1) & 1);
                if (i >= DEPTH) mbar_wait(bar_full + 8 * ((i - DEPTH) % NSLOT), ((i - DEPTH) / NSLOT) & 1);
                const uint32_t dst = sbase + slot * SLOT, fb = bar_full + 8 * slot;
                if (i == 0) {
                    mbar_expect_tx(fb, 32768);
                    tma2d(dst, &tmWq, cta * 32, 0, fb);
                    tma2d(dst + 16384, &tmWq, cta * 32, 256, fb);
                } else if (i <= 32) {
                    mbar_expect_tx(fb, 32768);
                    const int t = (i - 1) >> 1;
                    tma3d_hint(dst, ((i - 1) & 1) ? &tmV : &tmK, 0, key0 + t * 128, 0, fb, pol);
                } else if (i == 33) {
                    mbar_expect_tx(fb, 32768);
                    tma3d(dst, &tmWo, 0, (cta >> 2) * 128, (cta & 3) * 2, fb);
                } else if (i == 34) {
                    mbar_expect_tx(fb, 32768);
                    tma2d(dst, &tmWg, cta * 16, 0, fb);
                    tma2d(dst + 8192, &tmWg, cta * 16, 256, fb);
                    tma2d(dst + 16384, &tmWu, cta * 16, 0, fb);
                    tma2d(dst + 24576, &tmWu, cta * 16, 256, fb);
                } else {
                    mbar_expect_tx(fb, 16384);
                    tma3d(dst, &tmWd, 0, cta * 16, 0, fb);
                }
            }
            TSP(20);
        }
        return;
    }

    const int r8 = lane >> 2, q4 = lane & 3;
    const int hp = q4 & 1, kh = q4 >> 1;
    const int pair = cta >> 2, split = cta & 3;
    const int bq = pair >> 3, gq = pair & 7;

    if (tid == 0) {
        unsigned old = atomicAdd(&g_cnt0, 1u);
        *reinterpret_cast<volatile unsigned*>(smem + OFF_MISC) = old >> 7;
    }
    float xres = 0.f;
    if (warp == 0) xres = __bfloat162float(x[(cta >> 5) * 512 + (cta & 31) * 16 + (lane >> 1)]);

    if (warp < 4) {
        const uint4* xr = reinterpret_cast<const uint4*>(x + warp * 512);
        uint4 a = __ldg(xr + lane), b = __ldg(xr + 32 + lane);
        ln_row_store(a, b, smem + OFF_XN + warp * XN_PITCH, lane);
    }
    cbar();
    const unsigned epoch = *reinterpret_cast<volatile unsigned*>(smem + OFF_MISC);
    const uint32_t tag = epoch + 1;

    {
        uint32_t bfr[4][2];
        {
            uint32_t t4[4];
#pragma unroll
            for (int u = 0; u < 2; u++) {
                ldsm4(t4, sbase + OFF_XN + (lane & 3) * XN_PITCH + (8 * warp + 4 * u + (lane >> 3)) * 16);
                bfr[2 * u][0] = t4[0]; bfr[2 * u][1] = t4[1]; bfr[2 * u + 1][0] = t4[2]; bfr[2 * u + 1][1] = t4[3];
            }
        }
        mbar_wait(bar_full + 0, 0);
        TS(1);
        float acc[2][4] = {};
#pragma unroll
        for (int ks = 0; ks < 4; ks++) {
            const int k = 64 * warp + 16 * ks + (lane & 7) + (lane >> 4) * 8;
#pragma unroll
            for (int mt = 0; mt < 2; mt++) {
                uint32_t a[4];
                const int chunk = 2 * mt + ((lane >> 3) & 1);
                ldsm4t(a, sbase + k * 64 + ((chunk ^ ((k >> 1) & 3)) << 4));
                mma16816(acc[mt], a, bfr[ks][0], bfr[ks][1]);
            }
        }
        __syncwarp();
        if (lane == 0) mbar_arrive(bar_empty + 0);
        float* red = reinterpret_cast<float*>(smem + OFF_RED);
#pragma unroll
        for (int mt = 0; mt < 2; mt++) {
            float2 v = kh ? make_float2(acc[mt][2], acc[mt][3]) : make_float2(acc[mt][0], acc[mt][1]);
            *reinterpret_cast<float2*>(red + ((warp * 2 + mt) * 16 + r8 + 8 * kh) * 4 + 2 * hp) = v;
        }
        cbar();
        if (tid < 64) {
            const int b = tid >> 4, c2 = tid & 15;
            float s0 = 0.f, s1 = 0.f;
            const int c0 = 2 * c2, c1 = 2 * c2 + 1;
#pragma unroll
            for (int w = 0; w < 8; w++) {
                s0 += red[((w * 2 + (c0 >> 4)) * 16 + (c0 & 15)) * 4 + b];
                s1 += red[((w * 2 + (c1 >> 4)) * 16 + (c1 & 15)) * 4 + b];
            }
            st_rel64(&g_q[b * 2048 + cta * 16 + c2], pack_bf16(s0, s1), tag);
        }
        {
            const uint2* src = &g_q[bq * 2048 + gq * 256 + tid];
            uint2 v = ld_poll2(src);
            Spin sp;
            while (v.y != tag) { sp.tick(); v = ld_poll2(src); }
            *reinterpret_cast<uint32_t*>(smem + OFF_QS + (tid >> 6) * QS_PITCH + (tid & 63) * 4) = v.x;
            __syncwarp();
        }
        cbar();
    }
    TS(2);
    uint32_t qf[8][2];
    {
        uint32_t t4[4];
#pragma unroll
        for (int u = 0; u < 4; u++) {
            ldsm4(t4, sbase + OFF_QS + (lane & 3) * QS_PITCH + (4 * u + (lane >> 3)) * 16);
            qf[2 * u][0] = t4[0]; qf[2 * u][1] = t4[1]; qf[2 * u + 1][0] = t4[2]; qf[2 * u + 1][1] = t4[3];
        }
    }

    const uint32_t koff = (16 * warp + (lane & 7) + ((lane >> 3) & 1) * 8) * 128;
    const uint32_t kx = lane & 7, kc = lane >> 4;
    const uint32_t voff = (warp >> 2) * 16384 + ((lane & 7) + (lane >> 4) * 8) * 128 +
                          ((((2 * warp + ((lane >> 3) & 1)) & 7) ^ (lane & 7)) << 4);
    const uint32_t poff = sbase + OFF_P + (lane & 3) * QS_PITCH + (lane >> 3) * 16;
    uint32_t M2 = 0xFF80FF80u;
    float l0 = 0.f, l1 = 0.f;
    float oacc[2][4] = {};
    constexpr float SCALE = 0.08838834764831845f;
    constexpr float LOG2E = 1.4426950408889634f;
    uint32_t* mxbuf = reinterpret_cast<uint32_t*>(smem + OFF_MX);

    int slot = 1; uint32_t ph = 0;
    for (int t = 0; t < NTILE; t++) {
        mbar_wait(bar_full + 8 * slot, ph);
        float sa[4] = {}, sb[4] = {};
        {
            const uint32_t kb = sbase + slot * SLOT + koff;
#pragma unroll
            for (int ks = 0; ks < 8; ks++) {
                uint32_t a[4];
                ldsm4(a, kb + (ks >> 2) * 16384 + (((2 * (ks & 3) + kc) ^ kx) << 4));
                if (ks & 1) mma16816(sb, a, qf[ks][0], qf[ks][1]); else mma16816(sa, a, qf[ks][0], qf[ks][1]);
            }
        }
        __syncwarp();
        if (lane == 0) mbar_arrive(bar_empty + 8 * slot);
        if (++slot == NSLOT) { slot = 0; ph ^= 1; }

        const float r0 = kh ? sa[2] + sb[2] : sa[0] + sb[0];
        const float r1 = kh ? sa[3] + sb[3] : sa[1] + sb[1];
        uint32_t sp = pack_bf16(r0, r1);
        sp = pack_bf16(bf_lo(sp) * SCALE, bf_hi(sp) * SCALE);
        uint32_t mx = sp;
#pragma unroll
        for (int o = 2; o <= 16; o <<= 1) mx = hmax2(mx, __shfl_xor_sync(0xffffffffu, mx, o));
        if (lane < 2) mxbuf[lane * 8 + warp] = mx;
        if (t == RESET_TILE) {
            if (tid < 128) st_rel128(&g_partO[((pair * 4 + (tid >> 5)) * 4 + split) * 128 + (tid & 31) * 4], SENT);
            else {
                const int u = tid - 128;
                const int seg = u >> 2, b = seg >> 3, w = seg & 7;
                st_rel128(&g_ypart[((b * 32 + (cta & 3) * 8 + w) * 32 + (cta >> 2)) * 16 + (u & 3) * 4], SENT);
            }
            if (tid < 4) st_rel64(&g_ml[(pair * 4 + tid) * 4 + split], SENT, SENT);
            if (tid >= 32 && tid < 34) st_rel128(&g_h[(cta >> 5) * 512 + (cta & 31) * 16 + (tid - 32) * 8], SENT);
            if (cta < NFFN) {
#pragma unroll
                for (int u = 0; u < 2; u++) {
                    const int e = tid + 256 * u, seg = e >> 2;
                    st_rel128(&g_dpart[(seg * NFFN + cta) * 16 + (e & 3) * 4], SENT);
                }
            }
        }
        if (t == NTILE - 1 && tid == 0) {
            Spin spn; unsigned v;
            do { asm volatile("ld.acquire.gpu.global.u32 %0, [%1];" : "=r"(v) : "l"(&g_cnt1) : "memory"); spn.tick(); } while ((int)(v - (epoch + 1) * NCTA) < 0);
        }
        __syncwarp();
        cbar();
        if (t == RESET_TILE && tid == 0) { __threadfence(); atomicAdd(&g_cnt1, 1u); }
        {
            const uint4 m0 = *reinterpret_cast<const uint4*>(mxbuf + hp * 8), m1 = *reinterpret_cast<const uint4*>(mxbuf + hp * 8 + 4);
            uint32_t mt = hmax2(hmax2(hmax2(m0.x, m0.y), hmax2(m0.z, m0.w)), hmax2(hmax2(m1.x, m1.y), hmax2(m1.z, m1.w)));
            const uint32_t Mn = hmax2(M2, mt);
            const float a0 = ex2((bf_lo(M2) - bf_lo(Mn)) * LOG2E), a1 = ex2((bf_hi(M2) - bf_hi(Mn)) * LOG2E);
            const float p0 = ex2((bf_lo(sp) - bf_lo(Mn)) * LOG2E), p1 = ex2((bf_hi(sp) - bf_hi(Mn)) * LOG2E);
            M2 = Mn;
            l0 = fmaf(l0, a0, p0); l1 = fmaf(l1, a1, p1);
            const uint32_t pp = pack_bf16(p0, p1);
            unsigned char* pd = smem + OFF_P + (2 * hp) * QS_PITCH + (16 * warp + r8 + 8 * kh) * 2;
            *reinterpret_cast<uint16_t*>(pd) = (uint16_t)(pp & 0xFFFF);
            *reinterpret_cast<uint16_t*>(pd + QS_PITCH) = (uint16_t)(pp >> 16);
#pragma unroll
            for (int c = 0; c < 2; c++) { oacc[c][0] *= a0; oacc[c][1] *= a1; oacc[c][2] *= a0; oacc[c][3] *= a1; }
        }
        if (t == NTILE - 1) {
            float s0 = l0, s1 = l1;
#pragma unroll
            for (int o = 2; o <= 16; o <<= 1) { s0 += __shfl_xor_sync(0xffffffffu, s0, o); s1 += __shfl_xor_sync(0xffffffffu, s1, o); }
            if (lane < 2) *reinterpret_cast<float2*>(smem + OFF_L + warp * 16 + lane * 8) = make_float2(s0, s1);
        }
        cbar();
        if (t == NTILE - 1 && warp == 0) {
            const uint32_t other = __shfl_sync(0xffffffffu, M2, lane >> 1);
            if (lane < 4) {
                float l = 0.f;
#pragma unroll
                for (int w = 0; w < 8; w++) l += *reinterpret_cast<const float*>(smem + OFF_L + w * 16 + lane * 4);
                const float m = (lane & 1) ? bf_hi(other) : bf_lo(other);
                st_rel64(&g_ml[(pair * 4 + lane) * 4 + split], __float_as_uint(m), __float_as_uint(l));
            }
        }
        uint32_t pb[8][2];
        {
            uint32_t t4[4];
#pragma unroll
            for (int u = 0; u < 4; u++) {
                ldsm4(t4, poff + u * 64);
                pb[2 * u][0] = t4[0]; pb[2 * u][1] = t4[1]; pb[2 * u + 1][0] = t4[2]; pb[2 * u + 1][1] = t4[3];
            }
        }
        mbar_wait(bar_full + 8 * slot, ph);
        {
            const uint32_t vb = sbase + slot * SLOT + voff;
#pragma unroll
            for (int ks = 0; ks < 8; ks++) {
                uint32_t a[4];
                ldsm4t(a, vb + ks * 2048);
                mma16816(oacc[ks & 1], a, pb[ks][0], pb[ks][1]);
            }
        }
        __syncwarp();
        if (lane == 0) mbar_arrive(bar_empty + 8 * slot);
        if (++slot == NSLOT) { slot = 0; ph ^= 1; }
    }
    TS(3);
    {
        const float v0 = kh ? oacc[0][2] + oacc[1][2] : oacc[0][0] + oacc[1][0];
        const float v1 = kh ? oacc[0][3] + oacc[1][3] : oacc[0][1] + oacc[1][1];
        float* dst = &g_partO[((pair * 4 + 2 * hp) * 4 + split) * 128 + 16 * warp + r8 + 8 * kh];
        st_rel32(dst, __float_as_uint(v0));
        st_rel32(dst + 512, __float_as_uint(v1));
    }

    {
        uint32_t af[8][4];
        mbar_wait(bar_full + 8 * slot, ph);
        {
            const uint32_t wb = sbase + slot * SLOT + voff;
#pragma unroll
            for (int ks = 0; ks < 8; ks++) ldsm4t(af[ks], wb + ks * 2048);
        }
        if (++slot == NSLOT) { slot = 0; ph ^= 1; }
        TS(4);
        if (warp < 4) {
            const int head = cta >> 2;
            const int ph_idx = (warp * 8 + (head >> 2)) * 4 + (head & 3);
            const float* po = &g_partO[ph_idx * 512 + lane * 4];
            const float2* pm = &g_ml[ph_idx * 4];
            uint4 o0, o1, o2, o3, ma, mb;
            Spin sp;
            while (true) {
                o0 = ld_poll4(po); o1 = ld_poll4(po + 128); o2 = ld_poll4(po + 256); o3 = ld_poll4(po + 384);
                ma = ld_poll4(pm); mb = ld_poll4(pm + 2);
                if (valid4(o0) && valid4(o1) && valid4(o2) && valid4(o3) && valid4(ma) && valid4(mb)) break;
                sp.tick();
            }
            const float m0 = __uint_as_float(ma.x), m1 = __uint_as_float(ma.z), m2 = __uint_as_float(mb.x), m3 = __uint_as_float(mb.z);
            const float M = fmaxf(fmaxf(m0, m1), fmaxf(m2, m3));
            float w0 = ex2((m0 - M) * LOG2E), w1 = ex2((m1 - M) * LOG2E), w2 = ex2((m2 - M) * LOG2E), w3 = ex2((m3 - M) * LOG2E);
            const float L = w0 * __uint_as_float(ma.y) + w1 * __uint_as_float(ma.w) + w2 * __uint_as_float(mb.y) + w3 * __uint_as_float(mb.w);
            const float inv = 1.0f / L;
            w0 *= inv; w1 *= inv; w2 *= inv; w3 *= inv;
            const float e0 = w0 * __uint_as_float(o0.x) + w1 * __uint_as_float(o1.x) + w2 * __uint_as_float(o2.x) + w3 * __uint_as_float(o3.x);
            const float e1 = w0 * __uint_as_float(o0.y) + w1 * __uint_as_float(o1.y) + w2 * __uint_as_float(o2.y) + w3 * __uint_as_float(o3.y);
            const float e2 = w0 * __uint_as_float(o0.z) + w1 * __uint_as_float(o1.z) + w2 * __uint_as_float(o2.z) + w3 * __uint_as_float(o3.z);
            const float e3 = w0 * __uint_as_float(o0.w) + w1 * __uint_as_float(o1.w) + w2 * __uint_as_float(o2.w) + w3 * __uint_as_float(o3.w);
            *reinterpret_cast<uint2*>(smem + OFF_QS + warp * QS_PITCH + lane * 8) = make_uint2(pack_bf16(e0, e1), pack_bf16(e2, e3));
            __syncwarp();
        }
        cbar();
        TS(5);
        float acc[2][4] = {};
        {
            uint32_t t4[4];
#pragma unroll
            for (int u = 0; u < 4; u++) {
                ldsm4(t4, sbase + OFF_QS + (lane & 3) * QS_PITCH + (4 * u + (lane >> 3)) * 16);
                mma16816(acc[0], af[2 * u], t4[0], t4[1]);
                mma16816(acc[1], af[2 * u + 1], t4[2], t4[3]);
            }
        }
        const float v0 = kh ? acc[0][2] + acc[1][2] : acc[0][0] + acc[1][0];
        const float v1 = kh ? acc[0][3] + acc[1][3] : acc[0][1] + acc[1][1];
        float* dst = &g_ypart[(((2 * hp) * 32 + (cta & 3) * 8 + warp) * 32 + (cta >> 2)) * 16 + r8 + 8 * kh];
        st_rel32(dst, __float_as_uint(v0));
        st_rel32(dst + 32 * 32 * 16, __float_as_uint(v1));
    }
    TS(6);

    uint32_t gf[8][4];
    uint32_t df[4][4];
    float hres = 0.f;

    if (warp == 0) {
        const float* src = &g_ypart[(cta * 32 + lane) * 16];
        uint4 y0, y1, y2, y3;
        Spin sp;
        while (true) {
            y0 = ld_poll4(src); y1 = ld_poll4(src + 4); y2 = ld_poll4(src + 8); y3 = ld_poll4(src + 12);
            if (valid4(y0) && valid4(y1) && valid4(y2) && valid4(y3)) break;
            sp.tick();
        }
        float v[16] = {__uint_as_float(y0.x), __uint_as_float(y0.y), __uint_as_float(y0.z), __uint_as_float(y0.w),
                       __uint_as_float(y1.x), __uint_as_float(y1.y), __uint_as_float(y1.z), __uint_as_float(y1.w),
                       __uint_as_float(y2.x), __uint_as_float(y2.y), __uint_as_float(y2.z), __uint_as_float(y2.w),
                       __uint_as_float(y3.x), __uint_as_float(y3.y), __uint_as_float(y3.z), __uint_as_float(y3.w)};
#pragma unroll
        for (int n = 8; n >= 1; n >>= 1) {
            const bool up = lane & (2 * n);
#pragma unroll
            for (int i = 0; i < n; i++) {
                const float send = up ? v[i] : v[i + n];
                const float keep = up ? v[i + n] : v[i];
                v[i] = keep + __shfl_xor_sync(0xffffffffu, send, 2 * n);
            }
        }
        v[0] += __shfl_xor_sync(0xffffffffu, v[0], 1);
        hres = bf16r(xres + bf16r(v[0]));
        if (!(lane & 1)) st_rel16(&g_h[(cta >> 5) * 512 + (cta & 31) * 16 + (lane >> 1)], (uint16_t)(__float_as_uint(hres) >> 16));
        TS(7);
    }

    if (cta < NFFN) {
        mbar_wait(bar_full + 8 * slot, ph);
        {
            const uint32_t wb = sbase + slot * SLOT;
#pragma unroll
            for (int ks = 0; ks < 4; ks++) {
                const int k = 64 * warp + 16 * ks + (lane & 7) + (lane >> 4) * 8;
                const uint32_t a = wb + k * 32 + ((((lane >> 3) & 1) ^ ((k >> 2) & 1)) << 4);
                ldsm4t(gf[2 * ks], a);
                ldsm4t(gf[2 * ks + 1], a + 16384);
            }
        }
        if (++slot == NSLOT) { slot = 0; ph ^= 1; }
        mbar_wait(bar_full + 8 * slot, ph);
        {
            const uint32_t wb = sbase + slot * SLOT + warp * 2048 + ((lane & 7) + (lane >> 4) * 8) * 128;
#pragma unroll
            for (int i = 0; i < 4; i++) ldsm4t(df[i], wb + (((2 * i + ((lane >> 3) & 1)) ^ (lane & 7)) << 4));
        }
        if (warp >= 4) {
            const uint4* hr = reinterpret_cast<const uint4*>(g_h + (warp - 4) * 512);
            uint4 a, b;
            Spin sp;
            while (true) {
                a = ld_poll4(hr + lane); b = ld_poll4(hr + 32 + lane);
                if (valid8h(a) && valid8h(b)) break;
                sp.tick();
            }
            __syncwarp();
            ln_row_store(a, b, smem + OFF_XN + (warp - 4) * XN_PITCH, lane);
        }
        cbar();
        TS(8);
        float acc[2][4] = {};
        {
            uint32_t t4[4];
#pragma unroll
            for (int u = 0; u < 2; u++) {
                ldsm4(t4, sbase + OFF_XN + (lane & 3) * XN_PITCH + (8 * warp + 4 * u + (lane >> 3)) * 16);
                mma16816(acc[0], gf[4 * u + 0], t4[0], t4[1]);
                mma16816(acc[1], gf[4 * u + 1], t4[0], t4[1]);
                mma16816(acc[0], gf[4 * u + 2], t4[2], t4[3]);
                mma16816(acc[1], gf[4 * u + 3], t4[2], t4[3]);
            }
        }
        float* red = reinterpret_cast<float*>(smem + OFF_RED);
#pragma unroll
        for (int mt = 0; mt < 2; mt++) {
            float2 v = kh ? make_float2(acc[mt][2], acc[mt][3]) : make_float2(acc[mt][0], acc[mt][1]);
            *reinterpret_cast<float2*>(red + ((warp * 2 + mt) * 16 + r8 + 8 * kh) * 4 + 2 * hp) = v;
        }
        cbar();
        if (tid < 64) {
            const int c = tid >> 2, b = tid & 3;
            float g = 0.f, u = 0.f;
#pragma unroll
            for (int w = 0; w < 8; w++) { g += red[((w * 2) * 16 + c) * 4 + b]; u += red[((w * 2 + 1) * 16 + c) * 4 + b]; }
            g = bf16r(g); u = bf16r(u);
            const float inner = 0.7978845608028654f * (g + 0.044715f * g * g * g);
            const float th = 1.0f - 2.0f / (__expf(2.0f * inner) + 1.0f);
            const float ge = bf16r(0.5f * g * (1.0f + th));
            *reinterpret_cast<__nv_bfloat16*>(smem + OFF_ACT + b * 32 + c * 2) = __float2bfloat16_rn(ge * u);
        }
        cbar();
        {
            const uint32_t b0 = *reinterpret_cast<const uint32_t*>(smem + OFF_ACT + (r8 & 3) * 32 + q4 * 4);
            const uint32_t b1 = *reinterpret_cast<const uint32_t*>(smem + OFF_ACT + (r8 & 3) * 32 + 16 + q4 * 4);
#pragma unroll
            for (int i = 0; i < 4; i++) {
                float c[4] = {};
                mma16816(c, df[i], b0, b1);
                const float v0 = kh ? c[2] : c[0], v1 = kh ? c[3] : c[1];
                float* dst = &g_dpart[(((2 * hp) * 32 + 4 * warp + i) * NFFN + cta) * 16 + r8 + 8 * kh];
                st_rel32(dst, __float_as_uint(v0));
                st_rel32(dst + 32 * NFFN * 16, __float_as_uint(v1));
            }
        }
        TS(9);
    }

    {
        const int quad = tid & 3, jj = tid >> 2;
        const float* src = &g_dpart[(cta * NFFN + jj) * 16 + quad * 4];
        const bool two = jj + 64 < NFFN;
        uint4 a, b = make_uint4(0, 0, 0, 0);
        Spin sp;
        while (true) {
            a = ld_poll4(src);
            if (two) b = ld_poll4(src + 64 * 16);
            if (valid4(a) && valid4(b)) break;
            sp.tick();
        }
        float v[4] = {__uint_as_float(a.x) + __uint_as_float(b.x), __uint_as_float(a.y) + __uint_as_float(b.y),
                      __uint_as_float(a.z) + __uint_as_float(b.z), __uint_as_float(a.w) + __uint_as_float(b.w)};
        __syncwarp();
        {
            const bool up = lane & 16;
            const float s0 = up ? v[0] : v[2], s1 = up ? v[1] : v[3];
            const float k0 = up ? v[2] : v[0], k1 = up ? v[3] : v[1];
            v[0] = k0 + __shfl_xor_sync(0xffffffffu, s0, 16);
            v[1] = k1 + __shfl_xor_sync(0xffffffffu, s1, 16);
            const bool up2 = lane & 8;
            const float s = up2 ? v[0] : v[1], k = up2 ? v[1] : v[0];
            v[0] = k + __shfl_xor_sync(0xffffffffu, s, 8);
            v[0] += __shfl_xor_sync(0xffffffffu, v[0], 4);
            if (!(lane & 4)) reinterpret_cast<float*>(smem + OFF_RED2)[warp * 16 + 4 * quad + ((lane & 16) ? 2 : 0) + ((lane & 8) ? 1 : 0)] = v[0];
        }
        cbar();
        if (warp == 0) {
            const float* r2 = reinterpret_cast<const float*>(smem + OFF_RED2) + (lane & 1) * 64 + (lane >> 1);
            float s = r2[0] + r2[16] + r2[32] + r2[48];
            s += __shfl_xor_sync(0xffffffffu, s, 1);
            if (!(lane & 1)) out[(cta >> 5) * 512 + (cta & 31) * 16 + (lane >> 1)] = __float2bfloat16_rn(hres + bf16r(s));
        }
    }
    TS(10);
}

typedef CUresult (*EncodeFn)(CUtensorMap*, CUtensorMapDataType, cuuint32_t, void*, const cuuint64_t*, const cuuint64_t*,
                             const cuuint32_t*, const cuuint32_t*, CUtensorMapInterleave, CUtensorMapSwizzle,
                             CUtensorMapL2promotion, CUtensorMapFloatOOBfill);

void encode(EncodeFn fn, CUtensorMap* m, const void* base, int rank, const cuuint64_t* dims, const cuuint64_t* strides,
            const cuuint32_t* box, CUtensorMapSwizzle sw, CUtensorMapL2promotion promo) {
    cuuint32_t es[3] = {1, 1, 1};
    fn(m, CU_TENSOR_MAP_DATA_TYPE_BFLOAT16, (cuuint32_t)rank, const_cast<void*>(base), dims, strides, box, es,
       CU_TENSOR_MAP_INTERLEAVE_NONE, sw, promo, CU_TENSOR_MAP_FLOAT_OOB_FILL_NONE);
}

}

extern "C" void kernel_launch(void* const* d_in, const int* in_sizes, int n_in, void* d_out, int out_size) {
    (void)in_sizes; (void)n_in; (void)out_size;
    static EncodeFn enc = nullptr;
    if (!enc) {
        void* fn = nullptr;
        cudaDriverEntryPointQueryResult qr;
        cudaGetDriverEntryPoint("cuTensorMapEncodeTiled", &fn, cudaEnableDefault, &qr);
        enc = (EncodeFn)fn;
        cudaFuncSetAttribute(fused_decode_kernel, cudaFuncAttributeMaxDynamicSharedMemorySize, SMEM_BYTES);
    }
    const void* x = d_in[0];
    CUtensorMap tmK, tmV, tmWq, tmWo, tmWg, tmWu, tmWd;
    {
        cuuint64_t dims[3] = {64, 262144, 2}; cuuint64_t str[2] = {256, 128}; cuuint32_t box[3] = {64, 128, 2};
        encode(enc, &tmK, d_in[1], 3, dims, str, box, CU_TENSOR_MAP_SWIZZLE_128B, CU_TENSOR_MAP_L2_PROMOTION_L2_256B);
        encode(enc, &tmV, d_in[2], 3, dims, str, box, CU_TENSOR_MAP_SWIZZLE_128B, CU_TENSOR_MAP_L2_PROMOTION_L2_256B);
    }
    {
        cuuint64_t dims[2] = {4096, 512}; cuuint64_t str[1] = {8192}; cuuint32_t box[2] = {32, 256};
        encode(enc, &tmWq, d_in[3], 2, dims, str, box, CU_TENSOR_MAP_SWIZZLE_64B, CU_TENSOR_MAP_L2_PROMOTION_L2_128B);
    }
    {
        cuuint64_t dims[3] = {64, 4096, 8}; cuuint64_t str[2] = {1024, 128}; cuuint32_t box[3] = {64, 128, 2};
        encode(enc, &tmWo, d_in[4], 3, dims, str, box, CU_TENSOR_MAP_SWIZZLE_128B, CU_TENSOR_MAP_L2_PROMOTION_L2_256B);
    }
    {
        cuuint64_t dims[2] = {1792, 512}; cuuint64_t str[1] = {3584}; cuuint32_t box[2] = {16, 256};
        encode(enc, &tmWg, d_in[6], 2, dims, str, box, CU_TENSOR_MAP_SWIZZLE_32B, CU_TENSOR_MAP_L2_PROMOTION_L2_128B);
        encode(enc, &tmWu, d_in[7], 2, dims, str, box, CU_TENSOR_MAP_SWIZZLE_32B, CU_TENSOR_MAP_L2_PROMOTION_L2_128B);
    }
    {
        cuuint64_t dims[3] = {64, 1792, 8}; cuuint64_t str[2] = {1024, 128}; cuuint32_t box[3] = {64, 16, 8};
        encode(enc, &tmWd, d_in[8], 3, dims, str, box, CU_TENSOR_MAP_SWIZZLE_128B, CU_TENSOR_MAP_L2_PROMOTION_L2_256B);
    }
    fused_decode_kernel<<<NCTA, NTHREADS, SMEM_BYTES, cudaStreamPerThread>>>(
        tmK, tmV, tmWq, tmWo, tmWg, tmWu, tmWd, (const __nv_bfloat16*)x, (__nv_bfloat16*)d_out);
}
```

```cpp
#include <cuda_runtime.h>
#include <cuda_bf16.h>
#include <cuda.h>
#include <stdint.h>

namespace {

constexpr int NCTA      = 128;
constexpr int NTHREADS  = 320;
constexpr int SLOT      = 32768;
constexpr int NSLOT     = 6;
constexpr int NTILE     = 16;
constexpr int NFFN      = 112;
#define DEPTH_LO 2
#define DEPTH_HI 3
#define LEAD_THR8 4
#define GATE_MARGIN 128
#define WARM_TILE 2
#define RESET_TILE 9
constexpr uint32_t SENT = 0xFFFFFFFFu;

constexpr int OFF_MISC = NSLOT * SLOT;
constexpr int M_XN     = 0;
constexpr int XN_PITCH = 1040;
constexpr int M_QS     = M_XN + 4 * XN_PITCH;
constexpr int QS_PITCH = 272;
constexpr int M_P      = M_QS + 4 * QS_PITCH;
constexpr int M_RED    = M_P + 4 * QS_PITCH;
constexpr int M_MX     = M_RED + 4096;
constexpr int M_L      = M_MX + 64;
constexpr int M_ACT    = M_L + 128;
constexpr int M_RED2   = M_ACT + 128;
constexpr int MISC_BYTES = M_RED2 + 512;
constexpr int OFF_BAR  = OFF_MISC + 2 * MISC_BYTES;
constexpr int OFF_VAR  = OFF_BAR + 128;
constexpr int SMEM_USED = OFF_VAR + 64;
constexpr int SMEM_BYTES = SMEM_USED + 1024;
static_assert(MISC_BYTES % 16 == 0, "alignment");

__device__ uint2    g_q[4 * 2048];
__device__ float    g_partO[32 * 4 * 4 * 128];
__device__ float2   g_ml[32 * 4 * 4];
__device__ float    g_ypart[4 * 32 * 32 * 16];
__device__ uint16_t g_h[4 * 512];
__device__ float    g_dpart[4 * 32 * NFFN * 16];
__device__ unsigned g_cnt0, g_cnt1, g_prog;
#define TS(i)
#define TSX(i, cond)
#define TSG(i)

__device__ __forceinline__ uint32_t smem_u32(const void* p) { return (uint32_t)__cvta_generic_to_shared(p); }
__device__ __forceinline__ void mbar_init(uint32_t bar, uint32_t cnt) {
    asm volatile("mbarrier.init.shared::cta.b64 [%0], %1;" ::"r"(bar), "r"(cnt) : "memory");
}
__device__ __forceinline__ void mbar_expect_tx(uint32_t bar, uint32_t bytes) {
    asm volatile("mbarrier.arrive.expect_tx.shared::cta.b64 _, [%0], %1;" ::"r"(bar), "r"(bytes) : "memory");
}
__device__ __forceinline__ void mbar_arrive(uint32_t bar) {
    asm volatile("mbarrier.arrive.shared::cta.b64 _, [%0];" ::"r"(bar) : "memory");
}
__device__ __forceinline__ bool mbar_try(uint32_t bar, uint32_t parity) {
    uint32_t ok;
    asm volatile("{\n.reg .pred p;\nmbarrier.try_wait.parity.shared::cta.b64 p, [%1], %2;\nselp.u32 %0, 1, 0, p;\n}"
                 : "=r"(ok) : "r"(bar), "r"(parity) : "memory");
    return ok != 0;
}
constexpr uint32_t SPIN_LIMIT = 1u << 22;
__device__ __forceinline__ void mbar_wait(uint32_t bar, uint32_t parity) {
    uint32_t it = 0;
    while (!mbar_try(bar, parity)) { if (++it > SPIN_LIMIT) __trap(); }
}
__device__ __forceinline__ void tma3d(uint32_t dst, const CUtensorMap* m, int c0, int c1, int c2, uint32_t bar, uint64_t pol) {
    asm volatile("cp.async.bulk.tensor.3d.shared::cluster.global.mbarrier::complete_tx::bytes.L2::cache_hint [%0], [%1, {%3, %4, %5}], [%2], %6;"
                 ::"r"(dst), "l"(m), "r"(bar), "r"(c0), "r"(c1), "r"(c2), "l"(pol) : "memory");
}
__device__ __forceinline__ void ldsm4(uint32_t (&r)[4], uint32_t addr) {
    asm volatile("ldmatrix.sync.aligned.m8n8.x4.shared.b16 {%0,%1,%2,%3}, [%4];"
                 : "=r"(r[0]), "=r"(r[1]), "=r"(r[2]), "=r"(r[3]) : "r"(addr) : "memory");
}
__device__ __forceinline__ void ldsm4t(uint32_t (&r)[4], uint32_t addr) {
    asm volatile("ldmatrix.sync.aligned.m8n8.x4.trans.shared.b16 {%0,%1,%2,%3}, [%4];"
                 : "=r"(r[0]), "=r"(r[1]), "=r"(r[2]), "=r"(r[3]) : "r"(addr) : "memory");
}
__device__ __forceinline__ void mma16816(float (&c)[4], const uint32_t (&a)[4], uint32_t b0, uint32_t b1) {
    asm volatile("mma.sync.aligned.m16n8k16.row.col.f32.bf16.bf16.f32 {%0,%1,%2,%3}, {%4,%5,%6,%7}, {%8,%9}, {%0,%1,%2,%3};"
                 : "+f"(c[0]), "+f"(c[1]), "+f"(c[2]), "+f"(c[3])
                 : "r"(a[0]), "r"(a[1]), "r"(a[2]), "r"(a[3]), "r"(b0), "r"(b1));
}
__device__ __forceinline__ void cbar() { asm volatile("bar.sync 1, 256;" ::: "memory"); }
__device__ __forceinline__ void cbar_p(uint32_t live) {
    asm volatile("{\n.reg .pred q;\nsetp.ne.u32 q, %0, 0;\n@q bar.sync 1, 256;\n}" ::"r"(live) : "memory");
}
__device__ __forceinline__ void st32_p(void* p, uint32_t v, uint32_t live) {
    asm volatile("{\n.reg .pred q;\nsetp.ne.u32 q, %2, 0;\n@q st.relaxed.gpu.global.u32 [%0], %1;\n}" ::"l"(p), "r"(v), "r"(live) : "memory");
}
__device__ __forceinline__ void st64_p(void* p, uint32_t a, uint32_t b, uint32_t live) {
    asm volatile("{\n.reg .pred q;\nsetp.ne.u32 q, %3, 0;\n@q st.relaxed.gpu.global.v2.u32 [%0], {%1,%2};\n}" ::"l"(p), "r"(a), "r"(b), "r"(live) : "memory");
}
__device__ __forceinline__ void st16_p(void* p, uint16_t v, uint32_t live) {
    asm volatile("{\n.reg .pred q;\nsetp.ne.u32 q, %2, 0;\n@q st.relaxed.gpu.global.u16 [%0], %1;\n}" ::"l"(p), "h"(v), "r"(live) : "memory");
}
__device__ __forceinline__ uint4 ld_poll4(const void* p) {
    uint4 v;
    asm volatile("ld.relaxed.gpu.global.v4.u32 {%0,%1,%2,%3}, [%4];" : "=r"(v.x), "=r"(v.y), "=r"(v.z), "=r"(v.w) : "l"(p) : "memory");
    return v;
}
__device__ __forceinline__ uint2 ld_poll2(const void* p) {
    uint2 v;
    asm volatile("ld.relaxed.gpu.global.v2.u32 {%0,%1}, [%2];" : "=r"(v.x), "=r"(v.y) : "l"(p) : "memory");
    return v;
}
__device__ __forceinline__ void st_rel32(void* p, uint32_t v) { asm volatile("st.relaxed.gpu.global.u32 [%0], %1;" ::"l"(p), "r"(v) : "memory"); }
__device__ __forceinline__ void st_rel16(void* p, uint16_t v) { asm volatile("st.relaxed.gpu.global.u16 [%0], %1;" ::"l"(p), "h"(v) : "memory"); }
__device__ __forceinline__ void st_rel64(void* p, uint32_t a, uint32_t b) { asm volatile("st.relaxed.gpu.global.v2.u32 [%0], {%1,%2};" ::"l"(p), "r"(a), "r"(b) : "memory"); }
__device__ __forceinline__ void st_rel128(void* p, uint32_t v) { asm volatile("st.relaxed.gpu.global.v4.u32 [%0], {%1,%1,%1,%1};" ::"l"(p), "r"(v) : "memory"); }
__device__ __forceinline__ bool valid4(const uint4& v) { return v.x != SENT && v.y != SENT && v.z != SENT && v.w != SENT; }
__device__ __forceinline__ bool valid8h(const uint4& v) {
    return (__vcmpeq2(v.x, SENT) | __vcmpeq2(v.y, SENT) | __vcmpeq2(v.z, SENT) | __vcmpeq2(v.w, SENT)) == 0;
}
struct Spin {
    uint32_t it = 0;
    __device__ __forceinline__ void tick() { if (++it > SPIN_LIMIT) __trap(); }
};
__device__ __forceinline__ float bf16r(float x) { return __bfloat162float(__float2bfloat16_rn(x)); }
__device__ __forceinline__ uint32_t pack_bf16(float lo, float hi) {
    uint32_t r; asm("cvt.rn.bf16x2.f32 %0, %1, %2;" : "=r"(r) : "f"(hi), "f"(lo)); return r;
}
__device__ __forceinline__ float bf_lo(uint32_t v) { return __uint_as_float(v << 16); }
__device__ __forceinline__ float bf_hi(uint32_t v) { return __uint_as_float(v & 0xFFFF0000u); }
__device__ __forceinline__ uint32_t hmax2(uint32_t a, uint32_t b) {
    uint32_t r; asm("max.bf16x2 %0, %1, %2;" : "=r"(r) : "r"(a), "r"(b)); return r;
}
__device__ __forceinline__ float ex2(float x) { float r; asm("ex2.approx.ftz.f32 %0, %1;" : "=f"(r) : "f"(x)); return r; }

__device__ __forceinline__ void ln_row_store(const uint4& a, const uint4& b, unsigned char* row, int lane) {
    float v[16];
    v[0] = bf_lo(a.x); v[1] = bf_hi(a.x); v[2] = bf_lo(a.y); v[3] = bf_hi(a.y);
    v[4] = bf_lo(a.z); v[5] = bf_hi(a.z); v[6] = bf_lo(a.w); v[7] = bf_hi(a.w);
    v[8] = bf_lo(b.x); v[9] = bf_hi(b.x); v[10] = bf_lo(b.y); v[11] = bf_hi(b.y);
    v[12] = bf_lo(b.z); v[13] = bf_hi(b.z); v[14] = bf_lo(b.w); v[15] = bf_hi(b.w);
    const float shift = __shfl_sync(0xffffffffu, v[0], 0);
    float s = 0.f, ss = 0.f;
#pragma unroll
    for (int i = 0; i < 16; i++) { float d = v[i] - shift; s += d; ss = fmaf(d, d, ss); }
#pragma unroll
    for (int o = 16; o > 0; o >>= 1) { s += __shfl_xor_sync(0xffffffffu, s, o); ss += __shfl_xor_sync(0xffffffffu, ss, o); }
    const float md = s * (1.0f / 512.0f);
    const float var = fmaxf(ss * (1.0f / 512.0f) - md * md, 0.f);
    const float m = bf16r(shift + md);
    const float sd = bf16r(sqrtf(bf16r(bf16r(var) + 1e-5f)));
    const float rs = 1.0f / sd;
    uint32_t o[8];
#pragma unroll
    for (int i = 0; i < 8; i++) o[i] = pack_bf16(bf16r(v[2 * i] - m) * rs, bf16r(v[2 * i + 1] - m) * rs);
    *reinterpret_cast<uint4*>(row + lane * 16) = make_uint4(o[0], o[1], o[2], o[3]);
    *reinterpret_cast<uint4*>(row + 512 + lane * 16) = make_uint4(o[4], o[5], o[6], o[7]);
}

struct Maps { CUtensorMap m[7]; };

__global__ void __launch_bounds__(NTHREADS, 1)
fused_decode_kernel(const __grid_constant__ Maps maps,
                    const __nv_bfloat16* __restrict__ x, __nv_bfloat16* __restrict__ out)
{
    extern __shared__ __align__(1024) unsigned char smem_raw[];
    unsigned char* smem = smem_raw + ((1024u - (smem_u32(smem_raw) & 1023u)) & 1023u);
    const uint32_t sbase = smem_u32(smem);
    const uint32_t bar_full = sbase + OFF_BAR, bar_empty = sbase + OFF_BAR + 48, bar_ready = sbase + OFF_BAR + 96;
    volatile unsigned* vars = reinterpret_cast<volatile unsigned*>(smem + OFF_VAR);
    const int tid = threadIdx.x, warp = tid >> 5, lane = tid & 31;
    const int cta = blockIdx.x;

    if (tid == 0) TSG(0);
    if (tid == 256) {
        for (int i = 0; i < NSLOT; i++) { mbar_init(bar_full + 8 * i, 1); mbar_init(bar_empty + 8 * i, 8); }
        mbar_init(bar_ready, 1);
        vars[1] = 0;
        asm volatile("fence.mbarrier_init.release.cluster;" ::: "memory");
    }
    __syncthreads();

    if (warp == 8) {
        if (lane == 0) {
            uint64_t pol_first, pol_norm;
            asm volatile("createpolicy.fractional.L2::evict_first.b64 %0, 1.0;" : "=l"(pol_first));
            asm volatile("createpolicy.fractional.L2::evict_normal.b64 %0, 1.0;" : "=l"(pol_norm));
            const int key0 = cta * (NTILE * 128);
            const int nseq = (cta < NFFN) ? 36 : 34;
            int arrived = 0;
            unsigned gbase = 0, grel = 0;
            for (int i = 0; i < nseq; i++) {
                const int slot = i % NSLOT;
                if (i >= NSLOT) mbar_wait(bar_empty + 8 * slot, ((i / NSLOT) - 1) & 1);
                int d = NSLOT;
                if (i <= 32) {
                    const int lead8 = ((i - 1) * NCTA - (int)grel) / (NCTA / 8);
                    d = (i > 2 && lead8 > LEAD_THR8) ? DEPTH_LO : DEPTH_HI;
                }
                while (arrived < i - d + 1) { mbar_wait(bar_full + 8 * (arrived % NSLOT), (arrived / NSLOT) & 1); arrived++; }
                if (i == 33) {
                    Spin sp; unsigned v;
                    while (true) {
                        asm volatile("ld.relaxed.gpu.global.u32 %0, [%1];" : "=r"(v) : "l"(&g_prog) : "memory");
                        if ((int)(v - gbase) >= NCTA * 32 - GATE_MARGIN) break;
                        sp.tick(); __nanosleep(64);
                    }
                }
                const uint32_t dst = sbase + slot * SLOT, fb = bar_full + 8 * slot;
                int mi, c0, c1, c2 = 0, nbox = 1, dstep = 0, bytes = 32768;
                if (i == 0)       { mi = 2; c0 = cta * 32; c1 = 0; nbox = 2; dstep = 16384; }
                else if (i <= 32) { mi = (i - 1) & 1; c0 = 0; c1 = key0 + ((i - 1) >> 1) * 128; }
                else if (i == 33) { mi = 3; c0 = 0; c1 = (cta >> 2) * 128; c2 = (cta & 3) * 2; }
                else if (i == 34) { mi = 4; c0 = cta * 16; c1 = 0; nbox = 4; dstep = 8192; }
                else              { mi = 6; c0 = 0; c1 = cta * 16; bytes = 16384; }
                const uint64_t pol = (i >= 1 && i <= 32) ? pol_first : pol_norm;
                mbar_expect_tx(fb, bytes);
                for (int j = 0; j < nbox; j++)
                    tma3d(dst + j * dstep, &maps.m[mi + (j >> 1)], c0, c1 + (j & 1) * 256, c2, fb, pol);
                if (i >= 1 && i <= 32) {
                    const unsigned g = atomicAdd(&g_prog, 1u);
                    if (i == 1) gbase = g & ~(unsigned)(NCTA * 32 - 1);
                    grel = g - gbase;
                }
            }
            TSX(20, true);
        }
        return;
    }

    const uint32_t live = (warp != 9);
    const int w = live ? warp : 0;
    const int ltid = live ? tid : lane;
    unsigned char* sm = smem + OFF_MISC + (live ? 0 : MISC_BYTES);
    const uint32_t smb = smem_u32(sm);
    const int r8 = lane >> 2, q4 = lane & 3;
    const int hp = q4 & 1, kh = q4 >> 1;
    const int pair = cta >> 2, split = cta & 3;
    constexpr float LOG2E = 1.4426950408889634f;

    const uint32_t voff = (w >> 2) * 16384 + ((lane & 7) + (lane >> 4) * 8) * 128 +
                          ((((2 * w + ((lane >> 3) & 1)) & 7) ^ (lane & 7)) << 4);
    const uint32_t poff = smb + M_P + (lane & 3) * QS_PITCH + (lane >> 3) * 16;
    uint32_t M2 = 0xFF80FF80u;
    float l0 = 0.f, l1 = 0.f;
    float oacc[2][4] = {};
    float xres = 0.f;
    int slot = 1; uint32_t ph = 0;

    if (live) {
        const int bq = pair >> 3, gq = pair & 7;
        if (tid == 0) vars[0] = atomicAdd(&g_cnt0, 1u) >> 7;
        if (warp == 7) st_rel128(&g_q[(lane >> 3) * 2048 + cta * 16 + (lane & 7) * 2], 0u);
        if (warp == 0) xres = __bfloat162float(x[(cta >> 5) * 512 + (cta & 31) * 16 + (lane >> 1)]);

        if (warp < 4) {
            const uint4* xr = reinterpret_cast<const uint4*>(x + warp * 512);
            uint4 a = __ldg(xr + lane), b = __ldg(xr + 32 + lane);
            ln_row_store(a, b, sm + M_XN + warp * XN_PITCH, lane);
        }
        cbar();
        const uint32_t tag = vars[0] + 1;

        {
            uint32_t bfr[4][2];
            {
                uint32_t t4[4];
#pragma unroll
                for (int u = 0; u < 2; u++) {
                    ldsm4(t4, smb + M_XN + (lane & 3) * XN_PITCH + (8 * warp + 4 * u + (lane >> 3)) * 16);
                    bfr[2 * u][0] = t4[0]; bfr[2 * u][1] = t4[1]; bfr[2 * u + 1][0] = t4[2]; bfr[2 * u + 1][1] = t4[3];
                }
            }
            mbar_wait(bar_full + 0, 0);
            TS(2);
            float acc[2][4] = {};
#pragma unroll
            for (int ks = 0; ks < 4; ks++) {
                const int k = 64 * warp + 16 * ks + (lane & 7) + (lane >> 4) * 8;
#pragma unroll
                for (int mt = 0; mt < 2; mt++) {
                    uint32_t a[4];
                    const int chunk = 2 * mt + ((lane >> 3) & 1);
                    ldsm4t(a, sbase + k * 64 + ((chunk ^ ((k >> 1) & 3)) << 4));
                    mma16816(acc[mt], a, bfr[ks][0], bfr[ks][1]);
                }
            }
            __syncwarp();
            if (lane == 0) mbar_arrive(bar_empty + 0);
            float* red = reinterpret_cast<float*>(sm + M_RED);
#pragma unroll
            for (int mt = 0; mt < 2; mt++) {
                float2 v = kh ? make_float2(acc[mt][2], acc[mt][3]) : make_float2(acc[mt][0], acc[mt][1]);
                *reinterpret_cast<float2*>(red + ((warp * 2 + mt) * 16 + r8 + 8 * kh) * 4 + 2 * hp) = v;
            }
            cbar();
            if (tid < 64) {
                const int b = tid >> 4, c2 = tid & 15;
                float s0 = 0.f, s1 = 0.f;
                const int c0 = 2 * c2, c1 = 2 * c2 + 1;
#pragma unroll
                for (int ww = 0; ww < 8; ww++) {
                    s0 += red[((ww * 2 + (c0 >> 4)) * 16 + (c0 & 15)) * 4 + b];
                    s1 += red[((ww * 2 + (c1 >> 4)) * 16 + (c1 & 15)) * 4 + b];
                }
                st_rel64(&g_q[b * 2048 + cta * 16 + c2], pack_bf16(s0, s1), tag);
            }
            {
                const uint2* src = &g_q[bq * 2048 + gq * 256 + tid];
                uint2 v = ld_poll2(src);
                Spin sp;
                while (v.y != tag) { sp.tick(); v = ld_poll2(src); }
                *reinterpret_cast<uint32_t*>(sm + M_QS + (tid >> 6) * QS_PITCH + (tid & 63) * 4) = v.x;
                __syncwarp();
            }
            cbar();
        }
        TS(3);
        uint32_t qf[8][2];
        {
            uint32_t t4[4];
#pragma unroll
            for (int u = 0; u < 4; u++) {
                ldsm4(t4, smb + M_QS + (lane & 3) * QS_PITCH + (4 * u + (lane >> 3)) * 16);
                qf[2 * u][0] = t4[0]; qf[2 * u][1] = t4[1]; qf[2 * u + 1][0] = t4[2]; qf[2 * u + 1][1] = t4[3];
            }
        }

        const uint32_t koff = (16 * warp + (lane & 7) + ((lane >> 3) & 1) * 8) * 128;
        const uint32_t kx = lane & 7, kc = lane >> 4;
        constexpr float SCALE = 0.08838834764831845f;
        uint32_t* mxbuf = reinterpret_cast<uint32_t*>(sm + M_MX);

        for (int t = 0;; t++) {
            mbar_wait(bar_full + 8 * slot, ph);
            float sa[4] = {}, sb[4] = {};
            {
                const uint32_t kb = sbase + slot * SLOT + koff;
#pragma unroll
                for (int ks = 0; ks < 8; ks++) {
                    uint32_t a[4];
                    ldsm4(a, kb + (ks >> 2) * 16384 + (((2 * (ks & 3) + kc) ^ kx) << 4));
                    if (ks & 1) mma16816(sb, a, qf[ks][0], qf[ks][1]); else mma16816(sa, a, qf[ks][0], qf[ks][1]);
                }
            }
            __syncwarp();
            if (lane == 0) mbar_arrive(bar_empty + 8 * slot);
            if (++slot == NSLOT) { slot = 0; ph ^= 1; }

            const float r0 = kh ? sa[2] + sb[2] : sa[0] + sb[0];
            const float r1 = kh ? sa[3] + sb[3] : sa[1] + sb[1];
            uint32_t sp = pack_bf16(r0, r1);
            sp = pack_bf16(bf_lo(sp) * SCALE, bf_hi(sp) * SCALE);
            uint32_t mx = sp;
#pragma unroll
            for (int o = 2; o <= 16; o <<= 1) mx = hmax2(mx, __shfl_xor_sync(0xffffffffu, mx, o));
            if (lane < 2) mxbuf[lane * 8 + warp] = mx;
            if (tid == 0) vars[1] = t + 1;
            cbar();
            {
                const uint4 m0 = *reinterpret_cast<const uint4*>(mxbuf + hp * 8), m1 = *reinterpret_cast<const uint4*>(mxbuf + hp * 8 + 4);
                uint32_t mt = hmax2(hmax2(hmax2(m0.x, m0.y), hmax2(m0.z, m0.w)), hmax2(hmax2(m1.x, m1.y), hmax2(m1.z, m1.w)));
                const uint32_t Mn = hmax2(M2, mt);
                const float a0 = ex2((bf_lo(M2) - bf_lo(Mn)) * LOG2E), a1 = ex2((bf_hi(M2) - bf_hi(Mn)) * LOG2E);
                const float p0 = ex2((bf_lo(sp) - bf_lo(Mn)) * LOG2E), p1 = ex2((bf_hi(sp) - bf_hi(Mn)) * LOG2E);
                M2 = Mn;
                l0 = fmaf(l0, a0, p0); l1 = fmaf(l1, a1, p1);
                const uint32_t pp = pack_bf16(p0, p1);
                unsigned char* pd = sm + M_P + (2 * hp) * QS_PITCH + (16 * warp + r8 + 8 * kh) * 2;
                *reinterpret_cast<uint16_t*>(pd) = (uint16_t)(pp & 0xFFFF);
                *reinterpret_cast<uint16_t*>(pd + QS_PITCH) = (uint16_t)(pp >> 16);
#pragma unroll
                for (int c = 0; c < 2; c++) { oacc[c][0] *= a0; oacc[c][1] *= a1; oacc[c][2] *= a0; oacc[c][3] *= a1; }
            }
            if (t == NTILE - 1) break;
            cbar();
            uint32_t pb[8][2];
            {
                uint32_t t4[4];
#pragma unroll
                for (int u = 0; u < 4; u++) {
                    ldsm4(t4, poff + u * 64);
                    pb[2 * u][0] = t4[0]; pb[2 * u][1] = t4[1]; pb[2 * u + 1][0] = t4[2]; pb[2 * u + 1][1] = t4[3];
                }
            }
            mbar_wait(bar_full + 8 * slot, ph);
            {
                const uint32_t vb = sbase + slot * SLOT + voff;
#pragma unroll
                for (int ks = 0; ks < 8; ks++) {
                    uint32_t a[4];
                    ldsm4t(a, vb + ks * 2048);
                    mma16816(oacc[ks & 1], a, pb[ks][0], pb[ks][1]);
                }
            }
            __syncwarp();
            if (lane == 0) mbar_arrive(bar_empty + 8 * slot);
            if (++slot == NSLOT) { slot = 0; ph ^= 1; }
        }
    } else {
        Spin sp;
        while (vars[1] < WARM_TILE) { sp.tick(); __nanosleep(256); }
    }

    {
        float s0 = l0, s1 = l1;
#pragma unroll
        for (int o = 2; o <= 16; o <<= 1) { s0 += __shfl_xor_sync(0xffffffffu, s0, o); s1 += __shfl_xor_sync(0xffffffffu, s1, o); }
        if (lane < 2) *reinterpret_cast<float2*>(sm + M_L + w * 16 + lane * 8) = make_float2(s0, s1);
        if (live) mbar_wait(bar_ready, 0);
        cbar_p(live);
        if (w == 0) {
            const uint32_t other = __shfl_sync(0xffffffffu, M2, lane >> 1);
            float l = 0.f;
#pragma unroll
            for (int ww = 0; ww < 8; ww++) l += *reinterpret_cast<const float*>(sm + M_L + ww * 16 + (lane & 3) * 4);
            const float m = (lane & 1) ? bf_hi(other) : bf_lo(other);
            st64_p(&g_ml[(pair * 4 + (lane & 3)) * 4 + split], __float_as_uint(m), __float_as_uint(l), live && lane < 4);
        }
        uint32_t pb[8][2];
        {
            uint32_t t4[4];
#pragma unroll
            for (int u = 0; u < 4; u++) {
                ldsm4(t4, poff + u * 64);
                pb[2 * u][0] = t4[0]; pb[2 * u][1] = t4[1]; pb[2 * u + 1][0] = t4[2]; pb[2 * u + 1][1] = t4[3];
            }
        }
        if (live) mbar_wait(bar_full + 8 * slot, ph);
        {
            const uint32_t vb = sbase + slot * SLOT + voff;
#pragma unroll
            for (int ks = 0; ks < 8; ks++) {
                uint32_t a[4];
                ldsm4t(a, vb + ks * 2048);
                mma16816(oacc[ks & 1], a, pb[ks][0], pb[ks][1]);
            }
        }
        if (++slot == NSLOT) { slot = 0; ph ^= 1; }
        TS(4);
        const float v0 = kh ? oacc[0][2] + oacc[1][2] : oacc[0][0] + oacc[1][0];
        const float v1 = kh ? oacc[0][3] + oacc[1][3] : oacc[0][1] + oacc[1][1];
        float* dst = &g_partO[((pair * 4 + 2 * hp) * 4 + split) * 128 + 16 * w + r8 + 8 * kh];
        st32_p(dst, __float_as_uint(v0), live);
        st32_p(dst + 512, __float_as_uint(v1), live);
    }

    {
        uint32_t af[8][4];
        if (live) mbar_wait(bar_full + 8 * slot, ph);
        {
            const uint32_t wb = sbase + slot * SLOT + voff;
#pragma unroll
            for (int ks = 0; ks < 8; ks++) ldsm4t(af[ks], wb + ks * 2048);
        }
        if (++slot == NSLOT) { slot = 0; ph ^= 1; }
        TS(5);
        if (w < 4) {
            const int head = cta >> 2;
            const int ph_idx = (w * 8 + (head >> 2)) * 4 + (head & 3);
            const float* po = live ? &g_partO[ph_idx * 512 + lane * 4] : reinterpret_cast<const float*>(x) + lane * 4;
            const float* pm = live ? reinterpret_cast<const float*>(&g_ml[ph_idx * 4]) : reinterpret_cast<const float*>(x);
            uint4 o0, o1, o2, o3, ma, mb;
            Spin sp;
            while (true) {
                o0 = ld_poll4(po); o1 = ld_poll4(po + 128); o2 = ld_poll4(po + 256); o3 = ld_poll4(po + 384);
                ma = ld_poll4(pm); mb = ld_poll4(pm + 4);
                if ((valid4(o0) && valid4(o1) && valid4(o2) && valid4(o3) && valid4(ma) && valid4(mb)) || !live) break;
                sp.tick();
            }
            TS(6);
            const float m0 = __uint_as_float(ma.x), m1 = __uint_as_float(ma.z), m2 = __uint_as_float(mb.x), m3 = __uint_as_float(mb.z);
            const float M = fmaxf(fmaxf(m0, m1), fmaxf(m2, m3));
            float w0 = ex2((m0 - M) * LOG2E), w1 = ex2((m1 - M) * LOG2E), w2 = ex2((m2 - M) * LOG2E), w3 = ex2((m3 - M) * LOG2E);
            const float L = w0 * __uint_as_float(ma.y) + w1 * __uint_as_float(ma.w) + w2 * __uint_as_float(mb.y) + w3 * __uint_as_float(mb.w);
            const float inv = 1.0f / L;
            w0 *= inv; w1 *= inv; w2 *= inv; w3 *= inv;
            const float e0 = w0 * __uint_as_float(o0.x) + w1 * __uint_as_float(o1.x) + w2 * __uint_as_float(o2.x) + w3 * __uint_as_float(o3.x);
            const float e1 = w0 * __uint_as_float(o0.y) + w1 * __uint_as_float(o1.y) + w2 * __uint_as_float(o2.y) + w3 * __uint_as_float(o3.y);
            const float e2 = w0 * __uint_as_float(o0.z) + w1 * __uint_as_float(o1.z) + w2 * __uint_as_float(o2.z) + w3 * __uint_as_float(o3.z);
            const float e3 = w0 * __uint_as_float(o0.w) + w1 * __uint_as_float(o1.w) + w2 * __uint_as_float(o2.w) + w3 * __uint_as_float(o3.w);
            *reinterpret_cast<uint2*>(sm + M_QS + w * QS_PITCH + lane * 8) = make_uint2(pack_bf16(e0, e1), pack_bf16(e2, e3));
            __syncwarp();
        }
        cbar_p(live);
        TS(7);
        float acc[2][4] = {};
        {
            uint32_t t4[4];
#pragma unroll
            for (int u = 0; u < 4; u++) {
                ldsm4(t4, smb + M_QS + (lane & 3) * QS_PITCH + (4 * u + (lane >> 3)) * 16);
                mma16816(acc[0], af[2 * u], t4[0], t4[1]);
                mma16816(acc[1], af[2 * u + 1], t4[2], t4[3]);
            }
        }
        const float v0 = kh ? acc[0][2] + acc[1][2] : acc[0][0] + acc[1][0];
        const float v1 = kh ? acc[0][3] + acc[1][3] : acc[0][1] + acc[1][1];
        float* dst = &g_ypart[(((2 * hp) * 32 + (cta & 3) * 8 + w) * 32 + (cta >> 2)) * 16 + r8 + 8 * kh];
        st32_p(dst, __float_as_uint(v0), live);
        st32_p(dst + 32 * 32 * 16, __float_as_uint(v1), live);
        TS(8);
    }

    uint32_t gf[8][4];
    uint32_t df[4][4];
    float hres = 0.f;

    if (w == 0) {
        const float* src = live ? &g_ypart[(cta * 32 + lane) * 16] : reinterpret_cast<const float*>(x) + lane * 16;
        uint4 y0, y1, y2, y3;
        Spin sp;
        while (true) {
            y0 = ld_poll4(src); y1 = ld_poll4(src + 4); y2 = ld_poll4(src + 8); y3 = ld_poll4(src + 12);
            if ((valid4(y0) && valid4(y1) && valid4(y2) && valid4(y3)) || !live) break;
            sp.tick();
        }
        TS(9);
        float v0, v1, v2, v3, v4, v5, v6, v7;
        {
            const bool up = lane & 16;
#define RSTEP(dst, lo, hi, m) { const float _l = __uint_as_float(lo), _h = __uint_as_float(hi); dst = (up ? _h : _l) + __shfl_xor_sync(0xffffffffu, up ? _l : _h, m); }
            RSTEP(v0, y0.x, y2.x, 16) RSTEP(v1, y0.y, y2.y, 16) RSTEP(v2, y0.z, y2.z, 16) RSTEP(v3, y0.w, y2.w, 16)
            RSTEP(v4, y1.x, y3.x, 16) RSTEP(v5, y1.y, y3.y, 16) RSTEP(v6, y1.z, y3.z, 16) RSTEP(v7, y1.w, y3.w, 16)
#undef RSTEP
        }
#define RSTEP(dst, a, b, m) { const bool _u = lane & m; dst = (_u ? b : a) + __shfl_xor_sync(0xffffffffu, _u ? a : b, m); }
        RSTEP(v0, v0, v4, 8) RSTEP(v1, v1, v5, 8) RSTEP(v2, v2, v6, 8) RSTEP(v3, v3, v7, 8)
        RSTEP(v0, v0, v2, 4) RSTEP(v1, v1, v3, 4)
        RSTEP(v0, v0, v1, 2)
#undef RSTEP
        v0 += __shfl_xor_sync(0xffffffffu, v0, 1);
        hres = bf16r(xres + bf16r(v0));
        st16_p(&g_h[(cta >> 5) * 512 + (cta & 31) * 16 + (lane >> 1)], (uint16_t)(__float_as_uint(hres) >> 16), live && !(lane & 1));
        TS(10);
    }

    if (cta < NFFN) {
        if (live) mbar_wait(bar_full + 8 * slot, ph);
        {
            const uint32_t wb = sbase + slot * SLOT;
#pragma unroll
            for (int ks = 0; ks < 4; ks++) {
                const int k = 64 * w + 16 * ks + (lane & 7) + (lane >> 4) * 8;
                const uint32_t a = wb + k * 32 + ((((lane >> 3) & 1) ^ ((k >> 2) & 1)) << 4);
                ldsm4t(gf[2 * ks], a);
                ldsm4t(gf[2 * ks + 1], a + 16384);
            }
        }
        if (++slot == NSLOT) { slot = 0; ph ^= 1; }
        TS(11);
        if (live) mbar_wait(bar_full + 8 * slot, ph);
        {
            const uint32_t wb = sbase + slot * SLOT + w * 2048 + ((lane & 7) + (lane >> 4) * 8) * 128;
#pragma unroll
            for (int i = 0; i < 4; i++) ldsm4t(df[i], wb + (((2 * i + ((lane >> 3) & 1)) ^ (lane & 7)) << 4));
        }
        TS(12);
        if (w >= 4 || !live) {
            const uint4* hr = live ? reinterpret_cast<const uint4*>(g_h + (w - 4) * 512) : reinterpret_cast<const uint4*>(x);
            uint4 a, b;
            Spin sp;
            while (true) {
                a = ld_poll4(hr + lane); b = ld_poll4(hr + 32 + lane);
                if ((valid8h(a) && valid8h(b)) || !live) break;
                sp.tick();
            }
            TSX(13, tid == 128);
            __syncwarp();
            ln_row_store(a, b, sm + M_XN + (w & 3) * XN_PITCH, lane);
            TSX(14, tid == 128);
        }
        cbar_p(live);
        float acc[2][4] = {};
        {
            uint32_t t4[4];
#pragma unroll
            for (int u = 0; u < 2; u++) {
                ldsm4(t4, smb + M_XN + (lane & 3) * XN_PITCH + (8 * w + 4 * u + (lane >> 3)) * 16);
                mma16816(acc[0], gf[4 * u + 0], t4[0], t4[1]);
                mma16816(acc[1], gf[4 * u + 1], t4[0], t4[1]);
                mma16816(acc[0], gf[4 * u + 2], t4[2], t4[3]);
                mma16816(acc[1], gf[4 * u + 3], t4[2], t4[3]);
            }
        }
        float* red = reinterpret_cast<float*>(sm + M_RED);
#pragma unroll
        for (int mt = 0; mt < 2; mt++) {
            float2 v = kh ? make_float2(acc[mt][2], acc[mt][3]) : make_float2(acc[mt][0], acc[mt][1]);
            *reinterpret_cast<float2*>(red + ((w * 2 + mt) * 16 + r8 + 8 * kh) * 4 + 2 * hp) = v;
        }
        cbar_p(live);
        TS(16);
        if (ltid < 64) {
            const int c = ltid >> 2, b = ltid & 3;
            float g = 0.f, u = 0.f;
#pragma unroll
            for (int ww = 0; ww < 8; ww++) { g += red[((ww * 2) * 16 + c) * 4 + b]; u += red[((ww * 2 + 1) * 16 + c) * 4 + b]; }
            g = bf16r(g); u = bf16r(u);
            const float inner = 0.7978845608028654f * (g + 0.044715f * g * g * g);
            const float th = 1.0f - __fdividef(2.0f, __expf(2.0f * inner) + 1.0f);
            const float ge = bf16r(0.5f * g * (1.0f + th));
            *reinterpret_cast<__nv_bfloat16*>(sm + M_ACT + b * 32 + c * 2) = __float2bfloat16_rn(ge * u);
        }
        cbar_p(live);
        TS(17);
        {
            const uint32_t b0 = *reinterpret_cast<const uint32_t*>(sm + M_ACT + (r8 & 3) * 32 + q4 * 4);
            const uint32_t b1 = *reinterpret_cast<const uint32_t*>(sm + M_ACT + (r8 & 3) * 32 + 16 + q4 * 4);
#pragma unroll
            for (int i = 0; i < 4; i++) {
                float c[4] = {};
                mma16816(c, df[i], b0, b1);
                const float v0 = kh ? c[2] : c[0], v1 = kh ? c[3] : c[1];
                float* dst = &g_dpart[(((2 * hp) * 32 + 4 * w + i) * NFFN + cta) * 16 + r8 + 8 * kh];
                st32_p(dst, __float_as_uint(v0), live);
                st32_p(dst + 32 * NFFN * 16, __float_as_uint(v1), live);
            }
        }
        TS(18);
    }

    {
        const int quad = ltid & 3, jj = ltid >> 2;
        const float* src = (live ? &g_dpart[cta * NFFN * 16] : reinterpret_cast<const float*>(x)) + jj * 16 + quad * 4;
        const bool two = live && (jj + 64 < NFFN);
        uint4 a, b = make_uint4(0, 0, 0, 0);
        Spin sp;
        while (true) {
            a = ld_poll4(src);
            if (two) b = ld_poll4(src + 64 * 16);
            if ((valid4(a) && valid4(b)) || !live) break;
            sp.tick();
        }
        TS(19);
        float v[4] = {__uint_as_float(a.x) + __uint_as_float(b.x), __uint_as_float(a.y) + __uint_as_float(b.y),
                      __uint_as_float(a.z) + __uint_as_float(b.z), __uint_as_float(a.w) + __uint_as_float(b.w)};
        __syncwarp();
        {
            const bool up = lane & 16;
            const float s0 = up ? v[0] : v[2], s1 = up ? v[1] : v[3];
            const float k0 = up ? v[2] : v[0], k1 = up ? v[3] : v[1];
            v[0] = k0 + __shfl_xor_sync(0xffffffffu, s0, 16);
            v[1] = k1 + __shfl_xor_sync(0xffffffffu, s1, 16);
            const bool up2 = lane & 8;
            const float s = up2 ? v[0] : v[1], k = up2 ? v[1] : v[0];
            v[0] = k + __shfl_xor_sync(0xffffffffu, s, 8);
            v[0] += __shfl_xor_sync(0xffffffffu, v[0], 4);
            if (!(lane & 4)) reinterpret_cast<float*>(sm + M_RED2)[w * 16 + 4 * quad + ((lane & 16) ? 2 : 0) + ((lane & 8) ? 1 : 0)] = v[0];
        }
        cbar_p(live);
        TS(21);
        if (w == 0) {
            const float* r2 = reinterpret_cast<const float*>(sm + M_RED2) + (lane & 1) * 64 + (lane >> 1);
            float s = r2[0] + r2[16] + r2[32] + r2[48];
            s += __shfl_xor_sync(0xffffffffu, s, 1);
            st16_p(out + (cta >> 5) * 512 + (cta & 31) * 16 + (lane >> 1),
                   __bfloat16_as_ushort(__float2bfloat16_rn(hres + bf16r(s))), live && !(lane & 1));
        }
    }
    TS(22);
    if (tid == 0) TSG(62);

    if (!live) {
        TSX(23, lane == 0);
        Spin sp;
        while (vars[1] < RESET_TILE) { sp.tick(); __nanosleep(256); }
        const unsigned epoch = vars[0];
#pragma unroll 1
        for (int u = lane; u < 128; u += 32) {
            st_rel128(&g_partO[((pair * 4 + (u >> 5)) * 4 + split) * 128 + (u & 31) * 4], SENT);
            const int seg = u >> 2;
            st_rel128(&g_ypart[(((seg >> 3) * 32 + (cta & 3) * 8 + (seg & 7)) * 32 + (cta >> 2)) * 16 + (u & 3) * 4], SENT);
        }
        if (lane < 4) st_rel64(&g_ml[(pair * 4 + lane) * 4 + split], SENT, SENT);
        if (lane < 2) st_rel128(&g_h[(cta >> 5) * 512 + (cta & 31) * 16 + lane * 8], SENT);
        if (cta < NFFN) {
#pragma unroll 1
            for (int e = lane; e < 512; e += 32) st_rel128(&g_dpart[((e >> 2) * NFFN + cta) * 16 + (e & 3) * 4], SENT);
        }
        __threadfence();
        __syncwarp();
        if (lane == 0) {
            atomicAdd(&g_cnt1, 1u);
            unsigned v; Spin sp2;
            while (true) {
                asm volatile("ld.acquire.gpu.global.u32 %0, [%1];" : "=r"(v) : "l"(&g_cnt1) : "memory");
                if ((int)(v - (epoch + 1) * NCTA) >= 0) break;
                sp2.tick(); __nanosleep(128);
            }
            mbar_arrive(bar_ready);
        }
        TSX(24, lane == 0);
    }
}

typedef CUresult (*EncodeFn)(CUtensorMap*, CUtensorMapDataType, cuuint32_t, void*, const cuuint64_t*, const cuuint64_t*,
                             const cuuint32_t*, const cuuint32_t*, CUtensorMapInterleave, CUtensorMapSwizzle,
                             CUtensorMapL2promotion, CUtensorMapFloatOOBfill);

void encode(EncodeFn fn, CUtensorMap* m, const void* base, int rank, const cuuint64_t* dims, const cuuint64_t* strides,
            const cuuint32_t* box, CUtensorMapSwizzle sw, CUtensorMapL2promotion promo) {
    cuuint32_t es[3] = {1, 1, 1};
    fn(m, CU_TENSOR_MAP_DATA_TYPE_BFLOAT16, (cuuint32_t)rank, const_cast<void*>(base), dims, strides, box, es,
       CU_TENSOR_MAP_INTERLEAVE_NONE, sw, promo, CU_TENSOR_MAP_FLOAT_OOB_FILL_NONE);
}

}

extern "C" void kernel_launch(void* const* d_in, const int* in_sizes, int n_in, void* d_out, int out_size) {
    (void)in_sizes; (void)n_in; (void)out_size;
    static EncodeFn enc = nullptr;
    if (!enc) {
        void* fn = nullptr;
        cudaDriverEntryPointQueryResult qr;
        cudaGetDriverEntryPoint("cuTensorMapEncodeTiled", &fn, cudaEnableDefault, &qr);
        enc = (EncodeFn)fn;
        cudaFuncSetAttribute(fused_decode_kernel, cudaFuncAttributeMaxDynamicSharedMemorySize, SMEM_BYTES);
    }
    const void* x = d_in[0];
    Maps maps;
    {
        cuuint64_t dims[3] = {64, 262144, 2}; cuuint64_t str[2] = {256, 128}; cuuint32_t box[3] = {64, 128, 2};
        encode(enc, &maps.m[0], d_in[1], 3, dims, str, box, CU_TENSOR_MAP_SWIZZLE_128B, CU_TENSOR_MAP_L2_PROMOTION_L2_256B);
        encode(enc, &maps.m[1], d_in[2], 3, dims, str, box, CU_TENSOR_MAP_SWIZZLE_128B, CU_TENSOR_MAP_L2_PROMOTION_L2_256B);
    }
    {
        cuuint64_t dims[3] = {4096, 512, 1}; cuuint64_t str[2] = {8192, 8192 * 512}; cuuint32_t box[3] = {32, 256, 1};
        encode(enc, &maps.m[2], d_in[3], 3, dims, str, box, CU_TENSOR_MAP_SWIZZLE_64B, CU_TENSOR_MAP_L2_PROMOTION_L2_128B);
    }
    {
        cuuint64_t dims[3] = {64, 4096, 8}; cuuint64_t str[2] = {1024, 128}; cuuint32_t box[3] = {64, 128, 2};
        encode(enc, &maps.m[3], d_in[4], 3, dims, str, box, CU_TENSOR_MAP_SWIZZLE_128B, CU_TENSOR_MAP_L2_PROMOTION_L2_256B);
    }
    {
        cuuint64_t dims[3] = {1792, 512, 1}; cuuint64_t str[2] = {3584, 3584 * 512}; cuuint32_t box[3] = {16, 256, 1};
        encode(enc, &maps.m[4], d_in[6], 3, dims, str, box, CU_TENSOR_MAP_SWIZZLE_32B, CU_TENSOR_MAP_L2_PROMOTION_L2_128B);
        encode(enc, &maps.m[5], d_in[7], 3, dims, str, box, CU_TENSOR_MAP_SWIZZLE_32B, CU_TENSOR_MAP_L2_PROMOTION_L2_128B);
    }
    {
        cuuint64_t dims[3] = {64, 1792, 8}; cuuint64_t str[2] = {1024, 128}; cuuint32_t box[3] = {64, 16, 8};
        encode(enc, &maps.m[6], d_in[8], 3, dims, str, box, CU_TENSOR_MAP_SWIZZLE_128B, CU_TENSOR_MAP_L2_PROMOTION_L2_256B);
    }
    fused_decode_kernel<<<NCTA, NTHREADS, SMEM_BYTES, cudaStreamPerThread>>>(maps, (const __nv_bfloat16*)x, (__nv_bfloat16*)d_out);
}
```

```cpp
#include <cuda_runtime.h>
#include <cuda_bf16.h>
#include <cuda.h>
#include <stdint.h>

namespace {

constexpr int NCTA      = 128;
constexpr int NTHREADS  = 320;
constexpr int SLOT      = 32768;
constexpr int NSLOT     = 6;
constexpr int NTILE     = 16;
constexpr int NFFN      = 112;
#define DEPTH_LO 2
#define DEPTH_HI 3
#define LEAD_THR8 4
#define WD_LATE 1
constexpr int SEQ_WO  = 31;
constexpr int SEQ_WGU = 32;
constexpr int SEQ_WD  = WD_LATE ? 35 : 33;
constexpr int SEQ_K15 = WD_LATE ? 33 : 34;
constexpr int NSEQ    = WD_LATE ? 35 : 36;
#define WARM_TILE 10
#define RESET_TILE 8
constexpr uint32_t SENT = 0xFFFFFFFFu;

constexpr int OFF_MISC = NSLOT * SLOT;
constexpr int M_XN     = 0;
constexpr int XN_PITCH = 1040;
constexpr int M_QS     = M_XN + 4 * XN_PITCH;
constexpr int QS_PITCH = 272;
constexpr int M_P      = M_QS + 4 * QS_PITCH;
constexpr int M_RED    = M_P + 4 * QS_PITCH;
constexpr int M_MX     = M_RED + 4096;
constexpr int M_L      = M_MX + 64;
constexpr int M_ACT    = M_L + 128;
constexpr int M_RED2   = M_ACT + 128;
constexpr int MISC_BYTES = M_RED2 + 512;
constexpr int OFF_BAR  = OFF_MISC + 2 * MISC_BYTES;
constexpr int OFF_VAR  = OFF_BAR + 160;
constexpr int SMEM_USED = OFF_VAR + 64;
constexpr int SMEM_BYTES = SMEM_USED + 1024;
static_assert(MISC_BYTES % 16 == 0, "alignment");

__device__ uint2    g_q[4 * 2048];
__device__ float    g_partO[32 * 4 * 4 * 128];
__device__ float2   g_ml[32 * 4 * 4];
__device__ float    g_ypart[4 * 32 * 32 * 16];
__device__ uint16_t g_h[4 * 512];
__device__ float    g_dpart[4 * 32 * NFFN * 16];
__device__ unsigned g_cnt0, g_cnt1, g_prog;
#define TS(i)
#define TSX(i, cond)
#define TSG(i)
#define TSD(i, cond, dep)

__device__ __forceinline__ uint32_t smem_u32(const void* p) { return (uint32_t)__cvta_generic_to_shared(p); }
__device__ __forceinline__ void mbar_init(uint32_t bar, uint32_t cnt) {
    asm volatile("mbarrier.init.shared::cta.b64 [%0], %1;" ::"r"(bar), "r"(cnt) : "memory");
}
__device__ __forceinline__ void mbar_expect_tx(uint32_t bar, uint32_t bytes) {
    asm volatile("mbarrier.arrive.expect_tx.shared::cta.b64 _, [%0], %1;" ::"r"(bar), "r"(bytes) : "memory");
}
__device__ __forceinline__ void mbar_arrive(uint32_t bar) {
    asm volatile("mbarrier.arrive.shared::cta.b64 _, [%0];" ::"r"(bar) : "memory");
}
__device__ __forceinline__ bool mbar_try(uint32_t bar, uint32_t parity) {
    uint32_t ok;
    asm volatile("{\n.reg .pred p;\nmbarrier.try_wait.parity.shared::cta.b64 p, [%1], %2;\nselp.u32 %0, 1, 0, p;\n}"
                 : "=r"(ok) : "r"(bar), "r"(parity) : "memory");
    return ok != 0;
}
constexpr uint32_t SPIN_LIMIT = 1u << 22;
__device__ __forceinline__ void mbar_wait(uint32_t bar, uint32_t parity) {
    uint32_t it = 0;
    while (!mbar_try(bar, parity)) { if (++it > SPIN_LIMIT) __trap(); }
}
__device__ __forceinline__ void tma3d(uint32_t dst, const CUtensorMap* m, int c0, int c1, int c2, uint32_t bar, uint64_t pol) {
    asm volatile("cp.async.bulk.tensor.3d.shared::cluster.global.mbarrier::complete_tx::bytes.L2::cache_hint [%0], [%1, {%3, %4, %5}], [%2], %6;"
                 ::"r"(dst), "l"(m), "r"(bar), "r"(c0), "r"(c1), "r"(c2), "l"(pol) : "memory");
}
__device__ __forceinline__ void tma3d_prefetch(const CUtensorMap* m, int c0, int c1, int c2) {
    asm volatile("cp.async.bulk.prefetch.tensor.3d.L2.global.tile [%0, {%1, %2, %3}];" ::"l"(m), "r"(c0), "r"(c1), "r"(c2) : "memory");
}
__device__ __forceinline__ void ldsm4(uint32_t (&r)[4], uint32_t addr) {
    asm volatile("ldmatrix.sync.aligned.m8n8.x4.shared.b16 {%0,%1,%2,%3}, [%4];"
                 : "=r"(r[0]), "=r"(r[1]), "=r"(r[2]), "=r"(r[3]) : "r"(addr) : "memory");
}
__device__ __forceinline__ void ldsm4t(uint32_t (&r)[4], uint32_t addr) {
    asm volatile("ldmatrix.sync.aligned.m8n8.x4.trans.shared.b16 {%0,%1,%2,%3}, [%4];"
                 : "=r"(r[0]), "=r"(r[1]), "=r"(r[2]), "=r"(r[3]) : "r"(addr) : "memory");
}
__device__ __forceinline__ void mma16816(float (&c)[4], const uint32_t (&a)[4], uint32_t b0, uint32_t b1) {
    asm volatile("mma.sync.aligned.m16n8k16.row.col.f32.bf16.bf16.f32 {%0,%1,%2,%3}, {%4,%5,%6,%7}, {%8,%9}, {%0,%1,%2,%3};"
                 : "+f"(c[0]), "+f"(c[1]), "+f"(c[2]), "+f"(c[3])
                 : "r"(a[0]), "r"(a[1]), "r"(a[2]), "r"(a[3]), "r"(b0), "r"(b1));
}
__device__ __forceinline__ void cbar() { asm volatile("bar.sync 1, 256;" ::: "memory"); }
__device__ __forceinline__ void cbar_p(uint32_t live) {
    asm volatile("{\n.reg .pred q;\nsetp.ne.u32 q, %0, 0;\n@q bar.sync 1, 256;\n}" ::"r"(live) : "memory");
}
__device__ __forceinline__ void st32_p(void* p, uint32_t v, uint32_t live) {
    asm volatile("{\n.reg .pred q;\nsetp.ne.u32 q, %2, 0;\n@q st.relaxed.gpu.global.u32 [%0], %1;\n}" ::"l"(p), "r"(v), "r"(live) : "memory");
}
__device__ __forceinline__ void st64_p(void* p, uint32_t a, uint32_t b, uint32_t live) {
    asm volatile("{\n.reg .pred q;\nsetp.ne.u32 q, %3, 0;\n@q st.relaxed.gpu.global.v2.u32 [%0], {%1,%2};\n}" ::"l"(p), "r"(a), "r"(b), "r"(live) : "memory");
}
__device__ __forceinline__ void st16_p(void* p, uint16_t v, uint32_t live) {
    asm volatile("{\n.reg .pred q;\nsetp.ne.u32 q, %2, 0;\n@q st.relaxed.gpu.global.u16 [%0], %1;\n}" ::"l"(p), "h"(v), "r"(live) : "memory");
}
__device__ __forceinline__ uint4 ld_poll4(const void* p) {
    uint4 v;
    asm volatile("ld.relaxed.gpu.global.v4.u32 {%0,%1,%2,%3}, [%4];" : "=r"(v.x), "=r"(v.y), "=r"(v.z), "=r"(v.w) : "l"(p) : "memory");
    return v;
}
__device__ __forceinline__ uint2 ld_poll2(const void* p) {
    uint2 v;
    asm volatile("ld.relaxed.gpu.global.v2.u32 {%0,%1}, [%2];" : "=r"(v.x), "=r"(v.y) : "l"(p) : "memory");
    return v;
}
__device__ __forceinline__ void st_rel32(void* p, uint32_t v) { asm volatile("st.relaxed.gpu.global.u32 [%0], %1;" ::"l"(p), "r"(v) : "memory"); }
__device__ __forceinline__ void st_rel16(void* p, uint16_t v) { asm volatile("st.relaxed.gpu.global.u16 [%0], %1;" ::"l"(p), "h"(v) : "memory"); }
__device__ __forceinline__ void st_rel64(void* p, uint32_t a, uint32_t b) { asm volatile("st.relaxed.gpu.global.v2.u32 [%0], {%1,%2};" ::"l"(p), "r"(a), "r"(b) : "memory"); }
__device__ __forceinline__ void st_rel128(void* p, uint32_t v) { asm volatile("st.relaxed.gpu.global.v4.u32 [%0], {%1,%1,%1,%1};" ::"l"(p), "r"(v) : "memory"); }
__device__ __forceinline__ bool valid4(const uint4& v) { return (v.x != SENT) & (v.y != SENT) & (v.z != SENT) & (v.w != SENT); }
__device__ __forceinline__ bool valid8h(const uint4& v) {
    return (__vcmpeq2(v.x, SENT) | __vcmpeq2(v.y, SENT) | __vcmpeq2(v.z, SENT) | __vcmpeq2(v.w, SENT)) == 0;
}
struct Spin {
    uint32_t it = 0;
    __device__ __forceinline__ void tick() { if (++it > SPIN_LIMIT) __trap(); }
};
__device__ __forceinline__ uint32_t pack_bf16(float lo, float hi) {
    uint32_t r; asm("cvt.rn.bf16x2.f32 %0, %1, %2;" : "=r"(r) : "f"(hi), "f"(lo)); return r;
}
__device__ __forceinline__ float bf16r(float x) { return __uint_as_float(pack_bf16(0.f, x) & 0xFFFF0000u); }
__device__ __forceinline__ float bf_lo(uint32_t v) { return __uint_as_float(v << 16); }
__device__ __forceinline__ float bf_hi(uint32_t v) { return __uint_as_float(v & 0xFFFF0000u); }
__device__ __forceinline__ uint32_t hmax2(uint32_t a, uint32_t b) {
    uint32_t r; asm("max.bf16x2 %0, %1, %2;" : "=r"(r) : "r"(a), "r"(b)); return r;
}
__device__ __forceinline__ float ex2(float x) { float r; asm("ex2.approx.ftz.f32 %0, %1;" : "=f"(r) : "f"(x)); return r; }

__device__ __forceinline__ void ln_row_store(const uint4& a, const uint4& b, unsigned char* row, int lane) {
    float v[16];
    v[0] = bf_lo(a.x); v[1] = bf_hi(a.x); v[2] = bf_lo(a.y); v[3] = bf_hi(a.y);
    v[4] = bf_lo(a.z); v[5] = bf_hi(a.z); v[6] = bf_lo(a.w); v[7] = bf_hi(a.w);
    v[8] = bf_lo(b.x); v[9] = bf_hi(b.x); v[10] = bf_lo(b.y); v[11] = bf_hi(b.y);
    v[12] = bf_lo(b.z); v[13] = bf_hi(b.z); v[14] = bf_lo(b.w); v[15] = bf_hi(b.w);
    const float shift = __shfl_sync(0xffffffffu, v[0], 0);
    float s = 0.f, ss = 0.f;
#pragma unroll
    for (int i = 0; i < 16; i++) { float d = v[i] - shift; s += d; ss = fmaf(d, d, ss); }
#pragma unroll
    for (int o = 16; o > 0; o >>= 1) { s += __shfl_xor_sync(0xffffffffu, s, o); ss += __shfl_xor_sync(0xffffffffu, ss, o); }
    const float md = s * (1.0f / 512.0f);
    const float var = fmaxf(ss * (1.0f / 512.0f) - md * md, 0.f);
    const float m = bf16r(shift + md);
    const float sd = bf16r(sqrtf(bf16r(bf16r(var) + 1e-5f)));
    const float rs = 1.0f / sd;
    uint32_t o[8];
#pragma unroll
    for (int i = 0; i < 8; i++) o[i] = pack_bf16(bf16r(v[2 * i] - m) * rs, bf16r(v[2 * i + 1] - m) * rs);
    *reinterpret_cast<uint4*>(row + lane * 16) = make_uint4(o[0], o[1], o[2], o[3]);
    *reinterpret_cast<uint4*>(row + 512 + lane * 16) = make_uint4(o[4], o[5], o[6], o[7]);
}

struct Maps { CUtensorMap m[7]; };

__global__ void __launch_bounds__(NTHREADS, 1)
fused_decode_kernel(const __grid_constant__ Maps maps,
                    const __nv_bfloat16* __restrict__ x, __nv_bfloat16* __restrict__ out)
{
    extern __shared__ __align__(1024) unsigned char smem_raw[];
    unsigned char* smem = smem_raw + ((1024u - (smem_u32(smem_raw) & 1023u)) & 1023u);
    const uint32_t sbase = smem_u32(smem);
    const uint32_t bar_full = sbase + OFF_BAR, bar_empty = sbase + OFF_BAR + 48, bar_ready = sbase + OFF_BAR + 96, bar_w = sbase + OFF_BAR + 104;
    volatile unsigned* vars = reinterpret_cast<volatile unsigned*>(smem + OFF_VAR);
    const int tid = threadIdx.x, warp = tid >> 5, lane = tid & 31;
    const int cta = blockIdx.x;

    if (tid == 0) TSG(0);
    if (tid == 256) {
        for (int i = 0; i < NSLOT; i++) { mbar_init(bar_full + 8 * i, 1); mbar_init(bar_empty + 8 * i, 8); }
        mbar_init(bar_ready, 1);
        for (int i = 0; i < 6; i++) mbar_init(bar_w + 8 * i, 1);
        vars[1] = 0; vars[2] = 0;
        asm volatile("fence.mbarrier_init.release.cluster;" ::: "memory");
    }
    __syncthreads();

    if (warp == 8) {
        if (lane == 0) {
            uint64_t pol_first, pol_norm;
            asm volatile("createpolicy.fractional.L2::evict_first.b64 %0, 1.0;" : "=l"(pol_first));
            asm volatile("createpolicy.fractional.L2::evict_normal.b64 %0, 1.0;" : "=l"(pol_norm));
            const int key0 = cta * (NTILE * 128);
            int arrived = 0;
            unsigned gbase = 0, grel = 0;
            int nkv = 0;
            const bool ffn = cta < NFFN;
            for (int i = 0; i < NSEQ; i++) {
                const int slot = i % NSLOT;
                const bool is_w = (i == 0) || (i >= SEQ_WO && i < SEQ_K15);
                if (i >= NSLOT) mbar_wait(bar_empty + 8 * slot, ((i / NSLOT) - 1) & 1);
                const int lead8 = (nkv * NCTA - (int)grel) / (NCTA / 8);
                const int d = (i > 2 && lead8 > LEAD_THR8) ? DEPTH_LO : DEPTH_HI;
                while (arrived < i - d + 1) { mbar_wait(bar_full + 8 * (arrived % NSLOT), (arrived / NSLOT) & 1); arrived++; }
                const uint32_t dst = sbase + slot * SLOT, fb = bar_full + 8 * slot;
                int mi, c0 = 0, c1 = 0, c2 = 0, nbox = 1, dstep = 0, bytes = 32768;
                if (i == 0)            { mi = 2; c0 = cta * 32; nbox = 2; dstep = 16384; }
                else if (i == SEQ_WO)  { mi = 3; c1 = (cta >> 2) * 128; c2 = (cta & 3) * 2; }
                else if (i == SEQ_WGU) { mi = 4; c0 = cta * 16; nbox = 4; dstep = 8192; }
                else if (!WD_LATE && i == SEQ_WD) { mi = 6; c1 = cta * 16; bytes = 16384; nbox = 2; dstep = 8192; }
                else                   { mi = nkv & 1; c1 = key0 + (nkv >> 1) * 128; }
                if (!ffn && (i == SEQ_WGU || (!WD_LATE && i == SEQ_WD))) { mbar_arrive(fb); continue; }
                mbar_expect_tx(fb, bytes);
                if (mi == 6) { tma3d(dst, &maps.m[6], 0, c1, 0, fb, pol_norm); tma3d(dst + 8192, &maps.m[6], 0, c1, 4, fb, pol_norm); }
                else for (int j = 0; j < nbox; j++) tma3d(dst + j * dstep, &maps.m[mi + (j >> 1)], c0, c1 + (j & 1) * 256, c2, fb, is_w ? pol_norm : pol_first);
                if (!is_w) {
                    const unsigned g = atomicAdd(&g_prog, 1u);
                    if (nkv == 0) gbase = g & ~(unsigned)(NCTA * 32 - 1);
                    grel = g - gbase;
                    nkv++;
                }
            }
            if (WD_LATE && ffn) {
                constexpr int slot = SEQ_WD % NSLOT;
                mbar_wait(bar_empty + 8 * slot, ((SEQ_WD / NSLOT) - 1) & 1);
                mbar_wait(bar_full + 8 * ((SEQ_K15 + 1) % NSLOT), ((SEQ_K15 + 1) / NSLOT) & 1);
                mbar_expect_tx(bar_w, 8192);
                tma3d(sbase + slot * SLOT, &maps.m[6], 0, cta * 16, 0, bar_w, pol_norm);
                mbar_wait(bar_w, 0);
                mbar_expect_tx(bar_w + 8, 8192);
                tma3d(sbase + slot * SLOT + 8192, &maps.m[6], 0, cta * 16, 4, bar_w + 8, pol_norm);
            }
            TSX(20, true);
        }
        return;
    }

    const uint32_t live = (warp != 9);
    const int w = live ? warp : 0;
    const int ltid = live ? tid : lane;
    unsigned char* sm = smem + OFF_MISC + (live ? 0 : MISC_BYTES);
    const uint32_t smb = smem_u32(sm);
    const int r8 = lane >> 2, q4 = lane & 3;
    const int hp = q4 & 1, kh = q4 >> 1;
    const int pair = cta >> 2, split = cta & 3;
    constexpr float LOG2E = 1.4426950408889634f;

    const uint32_t voff = (w >> 2) * 16384 + ((lane & 7) + (lane >> 4) * 8) * 128 +
                          ((((2 * w + ((lane >> 3) & 1)) & 7) ^ (lane & 7)) << 4);
    const uint32_t poff = smb + M_P + (lane & 3) * QS_PITCH + (lane >> 3) * 16;
    uint32_t M2 = 0xFF80FF80u;
    float l0 = 0.f, l1 = 0.f;
    float oacc[2][4] = {};
    float xres = 0.f;
    int slot = 1; uint32_t ph = 0;

    if (live) {
        const int bq = pair >> 3, gq = pair & 7;
        if (tid == 0) vars[0] = atomicAdd(&g_cnt0, 1u) >> 7;
        if (warp == 7) st_rel128(&g_q[(lane >> 3) * 2048 + cta * 16 + (lane & 7) * 2], 0u);
        if (warp == 0) xres = __bfloat162float(x[(cta >> 5) * 512 + (cta & 31) * 16 + (lane >> 1)]);

        if (warp < 4) {
            const uint4* xr = reinterpret_cast<const uint4*>(x + warp * 512);
            uint4 a = __ldg(xr + lane), b = __ldg(xr + 32 + lane);
            ln_row_store(a, b, sm + M_XN + warp * XN_PITCH, lane);
        }
        cbar();
        const uint32_t tag = vars[0] + 1;

        {
            uint32_t bfr[4][2];
            {
                uint32_t t4[4];
#pragma unroll
                for (int u = 0; u < 2; u++) {
                    ldsm4(t4, smb + M_XN + (lane & 3) * XN_PITCH + (8 * warp + 4 * u + (lane >> 3)) * 16);
                    bfr[2 * u][0] = t4[0]; bfr[2 * u][1] = t4[1]; bfr[2 * u + 1][0] = t4[2]; bfr[2 * u + 1][1] = t4[3];
                }
            }
            mbar_wait(bar_full + 0, 0);
            TS(2);
            float acc[2][4] = {};
#pragma unroll
            for (int ks = 0; ks < 4; ks++) {
                const int k = 64 * warp + 16 * ks + (lane & 7) + (lane >> 4) * 8;
#pragma unroll
                for (int mt = 0; mt < 2; mt++) {
                    uint32_t a[4];
                    const int chunk = 2 * mt + ((lane >> 3) & 1);
                    ldsm4t(a, sbase + k * 64 + ((chunk ^ ((k >> 1) & 3)) << 4));
                    mma16816(acc[mt], a, bfr[ks][0], bfr[ks][1]);
                }
            }
            __syncwarp();
            if (lane == 0) mbar_arrive(bar_empty + 0);
            float* red = reinterpret_cast<float*>(sm + M_RED);
#pragma unroll
            for (int mt = 0; mt < 2; mt++) {
                float2 v = kh ? make_float2(acc[mt][2], acc[mt][3]) : make_float2(acc[mt][0], acc[mt][1]);
                *reinterpret_cast<float2*>(red + ((warp * 2 + mt) * 16 + r8 + 8 * kh) * 4 + 2 * hp) = v;
            }
            cbar();
            if (tid < 64) {
                const int b = tid >> 4, c2 = tid & 15;
                float s0 = 0.f, s1 = 0.f;
                const int c0 = 2 * c2, c1 = 2 * c2 + 1;
#pragma unroll
                for (int ww = 0; ww < 8; ww++) {
                    s0 += red[((ww * 2 + (c0 >> 4)) * 16 + (c0 & 15)) * 4 + b];
                    s1 += red[((ww * 2 + (c1 >> 4)) * 16 + (c1 & 15)) * 4 + b];
                }
                st_rel64(&g_q[b * 2048 + cta * 16 + c2], pack_bf16(s0, s1), tag);
            }
            {
                const uint2* src = &g_q[bq * 2048 + gq * 256 + tid];
                uint2 v;
                Spin sp;
                while (true) { v = ld_poll2(src); if (__all_sync(0xffffffffu, v.y == tag)) break; sp.tick(); }
                *reinterpret_cast<uint32_t*>(sm + M_QS + (tid >> 6) * QS_PITCH + (tid & 63) * 4) = v.x;
                __syncwarp();
            }
            cbar();
        }
        TS(3);
        uint32_t qf[8][2];
        {
            uint32_t t4[4];
#pragma unroll
            for (int u = 0; u < 4; u++) {
                ldsm4(t4, smb + M_QS + (lane & 3) * QS_PITCH + (4 * u + (lane >> 3)) * 16);
                qf[2 * u][0] = t4[0]; qf[2 * u][1] = t4[1]; qf[2 * u + 1][0] = t4[2]; qf[2 * u + 1][1] = t4[3];
            }
        }

        const uint32_t koff = (16 * warp + (lane & 7) + ((lane >> 3) & 1) * 8) * 128;
        const uint32_t kx = lane & 7, kc = lane >> 4;
        constexpr float SCALE = 0.08838834764831845f;
        uint32_t* mxbuf = reinterpret_cast<uint32_t*>(sm + M_MX);

        for (int t = 0;; t++) {
            mbar_wait(bar_full + 8 * slot, ph);
            float sa[4] = {}, sb[4] = {};
            {
                const uint32_t kb = sbase + slot * SLOT + koff;
#pragma unroll
                for (int ks = 0; ks < 8; ks++) {
                    uint32_t a[4];
                    ldsm4(a, kb + (ks >> 2) * 16384 + (((2 * (ks & 3) + kc) ^ kx) << 4));
                    if (ks & 1) mma16816(sb, a, qf[ks][0], qf[ks][1]); else mma16816(sa, a, qf[ks][0], qf[ks][1]);
                }
            }
            __syncwarp();
            if (lane == 0) mbar_arrive(bar_empty + 8 * slot);
            if (++slot == NSLOT) { slot = 0; ph ^= 1; }

            const float r0 = kh ? sa[2] + sb[2] : sa[0] + sb[0];
            const float r1 = kh ? sa[3] + sb[3] : sa[1] + sb[1];
            uint32_t sp = pack_bf16(r0, r1);
            sp = pack_bf16(bf_lo(sp) * SCALE, bf_hi(sp) * SCALE);
            uint32_t mx = sp;
#pragma unroll
            for (int o = 2; o <= 16; o <<= 1) mx = hmax2(mx, __shfl_xor_sync(0xffffffffu, mx, o));
            if (lane < 2) mxbuf[lane * 8 + warp] = mx;
            if (tid == 0) vars[1] = t + 1;
            TS(40 + t);
            cbar();
            {
                const uint4 m0 = *reinterpret_cast<const uint4*>(mxbuf + hp * 8), m1 = *reinterpret_cast<const uint4*>(mxbuf + hp * 8 + 4);
                uint32_t mt = hmax2(hmax2(hmax2(m0.x, m0.y), hmax2(m0.z, m0.w)), hmax2(hmax2(m1.x, m1.y), hmax2(m1.z, m1.w)));
                const uint32_t Mn = hmax2(M2, mt);
                const float a0 = ex2((bf_lo(M2) - bf_lo(Mn)) * LOG2E), a1 = ex2((bf_hi(M2) - bf_hi(Mn)) * LOG2E);
                const float p0 = ex2((bf_lo(sp) - bf_lo(Mn)) * LOG2E), p1 = ex2((bf_hi(sp) - bf_hi(Mn)) * LOG2E);
                M2 = Mn;
                l0 = fmaf(l0, a0, p0); l1 = fmaf(l1, a1, p1);
                const uint32_t pp = pack_bf16(p0, p1);
                unsigned char* pd = sm + M_P + (2 * hp) * QS_PITCH + (16 * warp + r8 + 8 * kh) * 2;
                *reinterpret_cast<uint16_t*>(pd) = (uint16_t)(pp & 0xFFFF);
                *reinterpret_cast<uint16_t*>(pd + QS_PITCH) = (uint16_t)(pp >> 16);
#pragma unroll
                for (int c = 0; c < 2; c++) { oacc[c][0] *= a0; oacc[c][1] *= a1; oacc[c][2] *= a0; oacc[c][3] *= a1; }
            }
            if (t == NTILE - 1) break;
            cbar();
            uint32_t pb[8][2];
            {
                uint32_t t4[4];
#pragma unroll
                for (int u = 0; u < 4; u++) {
                    ldsm4(t4, poff + u * 64);
                    pb[2 * u][0] = t4[0]; pb[2 * u][1] = t4[1]; pb[2 * u + 1][0] = t4[2]; pb[2 * u + 1][1] = t4[3];
                }
            }
            mbar_wait(bar_full + 8 * slot, ph);
            {
                const uint32_t vb = sbase + slot * SLOT + voff;
#pragma unroll
                for (int ks = 0; ks < 8; ks++) {
                    uint32_t a[4];
                    ldsm4t(a, vb + ks * 2048);
                    mma16816(oacc[ks & 1], a, pb[ks][0], pb[ks][1]);
                }
            }
            __syncwarp();
            if (lane == 0) mbar_arrive(bar_empty + 8 * slot);
            if (++slot == NSLOT) { slot = 0; ph ^= 1; }
            if (t == NTILE - 2) { slot = SEQ_K15 % NSLOT; ph = (SEQ_K15 / NSLOT) & 1; }
        }
    } else {
        Spin sp;
        while (vars[1] < RESET_TILE) { sp.tick(); __nanosleep(256); }
        const unsigned epoch = vars[0];
#pragma unroll 1
        for (int u = lane; u < 128; u += 32) {
            st_rel128(&g_partO[((pair * 4 + (u >> 5)) * 4 + split) * 128 + (u & 31) * 4], SENT);
            const int seg = u >> 2;
            st_rel128(&g_ypart[(((seg >> 3) * 32 + (cta & 3) * 8 + (seg & 7)) * 32 + (cta >> 2)) * 16 + (u & 3) * 4], SENT);
        }
        if (lane < 4) st_rel64(&g_ml[(pair * 4 + lane) * 4 + split], SENT, SENT);
        if (lane < 2) st_rel128(&g_h[(cta >> 5) * 512 + (cta & 31) * 16 + lane * 8], SENT);
        if (cta < NFFN) {
#pragma unroll 1
            for (int e = lane; e < 512; e += 32) st_rel128(&g_dpart[((e >> 2) * NFFN + cta) * 16 + (e & 3) * 4], SENT);
        }
        __threadfence();
        __syncwarp();
        if (lane == 0) {
            atomicAdd(&g_cnt1, 1u);
            unsigned v; Spin sp2;
            while (true) {
                asm volatile("ld.acquire.gpu.global.u32 %0, [%1];" : "=r"(v) : "l"(&g_cnt1) : "memory");
                if ((int)(v - (epoch + 1) * NCTA) >= 0) break;
                sp2.tick(); __nanosleep(128);
            }
            mbar_arrive(bar_ready);
        }
        TSX(24, lane == 0);
        while (vars[1] < WARM_TILE) { sp.tick(); __nanosleep(256); }
        TSX(25, lane == 0);
    }

    {
        float s0 = l0, s1 = l1;
#pragma unroll
        for (int o = 2; o <= 16; o <<= 1) { s0 += __shfl_xor_sync(0xffffffffu, s0, o); s1 += __shfl_xor_sync(0xffffffffu, s1, o); }
        if (lane < 2) *reinterpret_cast<float2*>(sm + M_L + w * 16 + lane * 8) = make_float2(s0, s1);
        if (live) mbar_wait(bar_ready, 0);
        cbar_p(live);
        if (w == 0) {
            const uint32_t other = __shfl_sync(0xffffffffu, M2, lane >> 1);
            float l = 0.f;
#pragma unroll
            for (int ww = 0; ww < 8; ww++) l += *reinterpret_cast<const float*>(sm + M_L + ww * 16 + (lane & 3) * 4);
            const float m = (lane & 1) ? bf_hi(other) : bf_lo(other);
            st64_p(&g_ml[(pair * 4 + (lane & 3)) * 4 + split], __float_as_uint(m), __float_as_uint(l), live && lane < 4);
        }
        uint32_t pb[8][2];
        {
            uint32_t t4[4];
#pragma unroll
            for (int u = 0; u < 4; u++) {
                ldsm4(t4, poff + u * 64);
                pb[2 * u][0] = t4[0]; pb[2 * u][1] = t4[1]; pb[2 * u + 1][0] = t4[2]; pb[2 * u + 1][1] = t4[3];
            }
        }
        if (live) mbar_wait(bar_full + 8 * slot, ph);
        {
            const uint32_t vb = sbase + slot * SLOT + voff;
#pragma unroll
            for (int ks = 0; ks < 8; ks++) {
                uint32_t a[4];
                ldsm4t(a, vb + ks * 2048);
                mma16816(oacc[ks & 1], a, pb[ks][0], pb[ks][1]);
            }
        }
        if (++slot == NSLOT) { slot = 0; ph ^= 1; }
        TS(4);
        const float v0 = kh ? oacc[0][2] + oacc[1][2] : oacc[0][0] + oacc[1][0];
        const float v1 = kh ? oacc[0][3] + oacc[1][3] : oacc[0][1] + oacc[1][1];
        float* dst = &g_partO[((pair * 4 + 2 * hp) * 4 + split) * 128 + 16 * w + r8 + 8 * kh];
        st32_p(dst, __float_as_uint(v0), live);
        st32_p(dst + 512, __float_as_uint(v1), live);
    }

    {
        if (w < 4) {
            const int head = cta >> 2;
            const int ph_idx = (w * 8 + (head >> 2)) * 4 + (head & 3);
            const float* po = live ? &g_partO[ph_idx * 512 + lane * 4] : reinterpret_cast<const float*>(x) + lane * 4;
            const float* pm = live ? reinterpret_cast<const float*>(&g_ml[ph_idx * 4]) : reinterpret_cast<const float*>(x);
            uint4 o0, o1, o2, o3, ma, mb;
            Spin sp;
            while (true) {
                o0 = ld_poll4(po); o1 = ld_poll4(po + 128); o2 = ld_poll4(po + 256); o3 = ld_poll4(po + 384);
                ma = ld_poll4(pm); mb = ld_poll4(pm + 4);
                if (__all_sync(0xffffffffu, (valid4(o0) & valid4(o1) & valid4(o2) & valid4(o3) & valid4(ma) & valid4(mb)) | !live)) break;
                sp.tick();
            }
            TS(6);
            const float m0 = __uint_as_float(ma.x), m1 = __uint_as_float(ma.z), m2 = __uint_as_float(mb.x), m3 = __uint_as_float(mb.z);
            const float M = fmaxf(fmaxf(m0, m1), fmaxf(m2, m3));
            float w0 = ex2((m0 - M) * LOG2E), w1 = ex2((m1 - M) * LOG2E), w2 = ex2((m2 - M) * LOG2E), w3 = ex2((m3 - M) * LOG2E);
            const float L = w0 * __uint_as_float(ma.y) + w1 * __uint_as_float(ma.w) + w2 * __uint_as_float(mb.y) + w3 * __uint_as_float(mb.w);
            const float inv = 1.0f / L;
            w0 *= inv; w1 *= inv; w2 *= inv; w3 *= inv;
            const float e0 = w0 * __uint_as_float(o0.x) + w1 * __uint_as_float(o1.x) + w2 * __uint_as_float(o2.x) + w3 * __uint_as_float(o3.x);
            const float e1 = w0 * __uint_as_float(o0.y) + w1 * __uint_as_float(o1.y) + w2 * __uint_as_float(o2.y) + w3 * __uint_as_float(o3.y);
            const float e2 = w0 * __uint_as_float(o0.z) + w1 * __uint_as_float(o1.z) + w2 * __uint_as_float(o2.z) + w3 * __uint_as_float(o3.z);
            const float e3 = w0 * __uint_as_float(o0.w) + w1 * __uint_as_float(o1.w) + w2 * __uint_as_float(o2.w) + w3 * __uint_as_float(o3.w);
            *reinterpret_cast<uint2*>(sm + M_QS + w * QS_PITCH + lane * 8) = make_uint2(pack_bf16(e0, e1), pack_bf16(e2, e3));
            __syncwarp();
        }
        uint32_t af[8][4];
        if (live) mbar_wait(bar_full + 8 * (SEQ_WO % NSLOT), (SEQ_WO / NSLOT) & 1);
        {
            const uint32_t wb = sbase + (SEQ_WO % NSLOT) * SLOT + voff;
#pragma unroll
            for (int ks = 0; ks < 8; ks++) ldsm4t(af[ks], wb + ks * 2048);
        }
        TS(5);
        cbar_p(live);
        TS(7);
        float acc[2][4] = {};
        {
            uint32_t t4[4];
#pragma unroll
            for (int u = 0; u < 4; u++) {
                ldsm4(t4, smb + M_QS + (lane & 3) * QS_PITCH + (4 * u + (lane >> 3)) * 16);
                mma16816(acc[0], af[2 * u], t4[0], t4[1]);
                mma16816(acc[1], af[2 * u + 1], t4[2], t4[3]);
            }
        }
        TSD(33, tid == 0, acc[1][0]);
        const float v0 = kh ? acc[0][2] + acc[1][2] : acc[0][0] + acc[1][0];
        const float v1 = kh ? acc[0][3] + acc[1][3] : acc[0][1] + acc[1][1];
        float* dst = &g_ypart[(((2 * hp) * 32 + (cta & 3) * 8 + w) * 32 + (cta >> 2)) * 16 + r8 + 8 * kh];
        st32_p(dst, __float_as_uint(v0), live);
        st32_p(dst + 32 * 32 * 16, __float_as_uint(v1), live);
        TS(8);
    }

    uint32_t gf[8][4];
    uint32_t df[4][4];
    float hres = 0.f;

    if (w == 0) {
        const float* src = live ? &g_ypart[(cta * 32 + lane) * 16] : reinterpret_cast<const float*>(x) + lane * 16;
        uint4 y0, y1, y2, y3;
        Spin sp;
        while (true) {
            y0 = ld_poll4(src); y1 = ld_poll4(src + 4); y2 = ld_poll4(src + 8); y3 = ld_poll4(src + 12);
            if (__all_sync(0xffffffffu, (valid4(y0) & valid4(y1) & valid4(y2) & valid4(y3)) | !live)) break;
            sp.tick();
        }
        TS(9);
        float v0, v1, v2, v3, v4, v5, v6, v7;
        {
            const bool up = lane & 16;
#define RSTEP(dst, lo, hi, m) { const float _l = __uint_as_float(lo), _h = __uint_as_float(hi); dst = (up ? _h : _l) + __shfl_xor_sync(0xffffffffu, up ? _l : _h, m); }
            RSTEP(v0, y0.x, y2.x, 16) RSTEP(v1, y0.y, y2.y, 16) RSTEP(v2, y0.z, y2.z, 16) RSTEP(v3, y0.w, y2.w, 16)
            RSTEP(v4, y1.x, y3.x, 16) RSTEP(v5, y1.y, y3.y, 16) RSTEP(v6, y1.z, y3.z, 16) RSTEP(v7, y1.w, y3.w, 16)
#undef RSTEP
        }
        TSD(30, tid == 0, v7);
#define RSTEP(dst, a, b, m) { const bool _u = lane & m; dst = (_u ? b : a) + __shfl_xor_sync(0xffffffffu, _u ? a : b, m); }
        RSTEP(v0, v0, v4, 8) RSTEP(v1, v1, v5, 8) RSTEP(v2, v2, v6, 8) RSTEP(v3, v3, v7, 8)
        RSTEP(v0, v0, v2, 4) RSTEP(v1, v1, v3, 4)
        RSTEP(v0, v0, v1, 2)
#undef RSTEP
        v0 += __shfl_xor_sync(0xffffffffu, v0, 1);
        TSD(31, tid == 0, v0);
        hres = bf16r(xres + bf16r(v0));
        TSD(32, tid == 0, hres);
        st16_p(&g_h[(cta >> 5) * 512 + (cta & 31) * 16 + (lane >> 1)], (uint16_t)(__float_as_uint(hres) >> 16), live && !(lane & 1));
        TS(10);
    }

    if (cta < NFFN) {
        if (live) mbar_wait(bar_full + 8 * (SEQ_WGU % NSLOT), (SEQ_WGU / NSLOT) & 1);
        {
            const uint32_t wb = sbase + (SEQ_WGU % NSLOT) * SLOT;
#pragma unroll
            for (int ks = 0; ks < 4; ks++) {
                const int k = 64 * w + 16 * ks + (lane & 7) + (lane >> 4) * 8;
                const uint32_t a = wb + k * 32 + ((((lane >> 3) & 1) ^ ((k >> 2) & 1)) << 4);
                ldsm4t(gf[2 * ks], a);
                ldsm4t(gf[2 * ks + 1], a + 16384);
            }
        }
        TS(11);
        if (w >= 4 || !live) {
            const uint4* hr = live ? reinterpret_cast<const uint4*>(g_h + (w - 4) * 512) : reinterpret_cast<const uint4*>(x);
            uint4 a, b;
            Spin sp;
            while (true) {
                a = ld_poll4(hr + lane); b = ld_poll4(hr + 32 + lane);
                if (__all_sync(0xffffffffu, (valid8h(a) & valid8h(b)) | !live)) break;
                sp.tick();
            }
            TSX(13, tid == 128);
            __syncwarp();
            ln_row_store(a, b, sm + M_XN + (w & 3) * XN_PITCH, lane);
            TSX(14, tid == 128);
        }
        cbar_p(live);
        float acc[2][4] = {};
        {
            uint32_t t4[4];
#pragma unroll
            for (int u = 0; u < 2; u++) {
                ldsm4(t4, smb + M_XN + (lane & 3) * XN_PITCH + (8 * w + 4 * u + (lane >> 3)) * 16);
                mma16816(acc[0], gf[4 * u + 0], t4[0], t4[1]);
                mma16816(acc[1], gf[4 * u + 1], t4[0], t4[1]);
                mma16816(acc[0], gf[4 * u + 2], t4[2], t4[3]);
                mma16816(acc[1], gf[4 * u + 3], t4[2], t4[3]);
            }
        }
        float* red = reinterpret_cast<float*>(sm + M_RED);
#pragma unroll
        for (int mt = 0; mt < 2; mt++) {
            float2 v = kh ? make_float2(acc[mt][2], acc[mt][3]) : make_float2(acc[mt][0], acc[mt][1]);
            *reinterpret_cast<float2*>(red + ((w * 2 + mt) * 16 + r8 + 8 * kh) * 4 + 2 * hp) = v;
        }
        if (live) {
            if (WD_LATE) { mbar_wait(bar_w, 0); mbar_wait(bar_w + 8, 0); }
            else mbar_wait(bar_full + 8 * (SEQ_WD % NSLOT), (SEQ_WD / NSLOT) & 1);
        }
        {
            const uint32_t wb = sbase + (SEQ_WD % NSLOT) * SLOT + w * 2048 + ((lane & 7) + (lane >> 4) * 8) * 128;
#pragma unroll
            for (int i = 0; i < 4; i++) ldsm4t(df[i], wb + (((2 * i + ((lane >> 3) & 1)) ^ (lane & 7)) << 4));
        }
        TS(12);
        cbar_p(live);
        TS(16);
        if (ltid < 64) {
            const int c = ltid >> 2, b = ltid & 3;
            float g = 0.f, u = 0.f;
#pragma unroll
            for (int ww = 0; ww < 8; ww++) { g += red[((ww * 2) * 16 + c) * 4 + b]; u += red[((ww * 2 + 1) * 16 + c) * 4 + b]; }
            g = bf16r(g); u = bf16r(u);
            const float inner = 0.7978845608028654f * (g + 0.044715f * g * g * g);
            const float th = 1.0f - __fdividef(2.0f, __expf(2.0f * inner) + 1.0f);
            const float ge = bf16r(0.5f * g * (1.0f + th));
            *reinterpret_cast<__nv_bfloat16*>(sm + M_ACT + b * 32 + c * 2) = __float2bfloat16_rn(ge * u);
        }
        cbar_p(live);
        TS(17);
        {
            const uint32_t b0 = *reinterpret_cast<const uint32_t*>(sm + M_ACT + (r8 & 3) * 32 + q4 * 4);
            const uint32_t b1 = *reinterpret_cast<const uint32_t*>(sm + M_ACT + (r8 & 3) * 32 + 16 + q4 * 4);
#pragma unroll
            for (int i = 0; i < 4; i++) {
                float c[4] = {};
                mma16816(c, df[i], b0, b1);
                const float v0 = kh ? c[2] : c[0], v1 = kh ? c[3] : c[1];
                float* dst = &g_dpart[(((2 * hp) * 32 + 4 * w + i) * NFFN + cta) * 16 + r8 + 8 * kh];
                st32_p(dst, __float_as_uint(v0), live);
                st32_p(dst + 32 * NFFN * 16, __float_as_uint(v1), live);
            }
        }
        TS(18);
    }

    {
        const int quad = ltid & 3, jj = ltid >> 2;
        const float* src = (live ? &g_dpart[cta * NFFN * 16] : reinterpret_cast<const float*>(x)) + jj * 16 + quad * 4;
        const bool two = live && (jj + 64 < NFFN);
        uint4 a, b = make_uint4(0, 0, 0, 0);
        Spin sp;
        while (true) {
            a = ld_poll4(src);
            if (two) b = ld_poll4(src + 64 * 16);
            if (__all_sync(0xffffffffu, (valid4(a) & valid4(b)) | !live)) break;
            sp.tick();
        }
        TS(19);
        float v[4] = {__uint_as_float(a.x) + __uint_as_float(b.x), __uint_as_float(a.y) + __uint_as_float(b.y),
                      __uint_as_float(a.z) + __uint_as_float(b.z), __uint_as_float(a.w) + __uint_as_float(b.w)};
        __syncwarp();
        {
            const bool up = lane & 16;
            const float s0 = up ? v[0] : v[2], s1 = up ? v[1] : v[3];
            const float k0 = up ? v[2] : v[0], k1 = up ? v[3] : v[1];
            v[0] = k0 + __shfl_xor_sync(0xffffffffu, s0, 16);
            v[1] = k1 + __shfl_xor_sync(0xffffffffu, s1, 16);
            const bool up2 = lane & 8;
            const float s = up2 ? v[0] : v[1], k = up2 ? v[1] : v[0];
            v[0] = k + __shfl_xor_sync(0xffffffffu, s, 8);
            v[0] += __shfl_xor_sync(0xffffffffu, v[0], 4);
            if (!(lane & 4)) reinterpret_cast<float*>(sm + M_RED2)[w * 16 + 4 * quad + ((lane & 16) ? 2 : 0) + ((lane & 8) ? 1 : 0)] = v[0];
        }
        cbar_p(live);
        TS(21);
        if (w == 0) {
            const float* r2 = reinterpret_cast<const float*>(sm + M_RED2) + (lane & 1) * 64 + (lane >> 1);
            float s = r2[0] + r2[16] + r2[32] + r2[48];
            s += __shfl_xor_sync(0xffffffffu, s, 1);
            st16_p(out + (cta >> 5) * 512 + (cta & 31) * 16 + (lane >> 1),
                   __bfloat16_as_ushort(__float2bfloat16_rn(hres + bf16r(s))), live && !(lane & 1));
        }
    }
    TS(22);
    if (tid == 0) TSG(62);

    TSX(23, !live && lane == 0);
}

typedef CUresult (*EncodeFn)(CUtensorMap*, CUtensorMapDataType, cuuint32_t, void*, const cuuint64_t*, const cuuint64_t*,
                             const cuuint32_t*, const cuuint32_t*, CUtensorMapInterleave, CUtensorMapSwizzle,
                             CUtensorMapL2promotion, CUtensorMapFloatOOBfill);

void encode(EncodeFn fn, CUtensorMap* m, const void* base, int rank, const cuuint64_t* dims, const cuuint64_t* strides,
            const cuuint32_t* box, CUtensorMapSwizzle sw, CUtensorMapL2promotion promo) {
    cuuint32_t es[3] = {1, 1, 1};
    fn(m, CU_TENSOR_MAP_DATA_TYPE_BFLOAT16, (cuuint32_t)rank, const_cast<void*>(base), dims, strides, box, es,
       CU_TENSOR_MAP_INTERLEAVE_NONE, sw, promo, CU_TENSOR_MAP_FLOAT_OOB_FILL_NONE);
}

}

extern "C" void kernel_launch(void* const* d_in, const int* in_sizes, int n_in, void* d_out, int out_size) {
    (void)in_sizes; (void)n_in; (void)out_size;
    static EncodeFn enc = nullptr;
    if (!enc) {
        void* fn = nullptr;
        cudaDriverEntryPointQueryResult qr;
        cudaGetDriverEntryPoint("cuTensorMapEncodeTiled", &fn, cudaEnableDefault, &qr);
        enc = (EncodeFn)fn;
        cudaFuncSetAttribute(fused_decode_kernel, cudaFuncAttributeMaxDynamicSharedMemorySize, SMEM_BYTES);
    }
    const void* x = d_in[0];
    Maps maps;
    {
        cuuint64_t dims[3] = {64, 262144, 2}; cuuint64_t str[2] = {256, 128}; cuuint32_t box[3] = {64, 128, 2};
        encode(enc, &maps.m[0], d_in[1], 3, dims, str, box, CU_TENSOR_MAP_SWIZZLE_128B, CU_TENSOR_MAP_L2_PROMOTION_L2_256B);
        encode(enc, &maps.m[1], d_in[2], 3, dims, str, box, CU_TENSOR_MAP_SWIZZLE_128B, CU_TENSOR_MAP_L2_PROMOTION_L2_256B);
    }
    {
        cuuint64_t dims[3] = {4096, 512, 1}; cuuint64_t str[2] = {8192, 8192 * 512}; cuuint32_t box[3] = {32, 256, 1};
        encode(enc, &maps.m[2], d_in[3], 3, dims, str, box, CU_TENSOR_MAP_SWIZZLE_64B, CU_TENSOR_MAP_L2_PROMOTION_L2_128B);
    }
    {
        cuuint64_t dims[3] = {64, 4096, 8}; cuuint64_t str[2] = {1024, 128}; cuuint32_t box[3] = {64, 128, 2};
        encode(enc, &maps.m[3], d_in[4], 3, dims, str, box, CU_TENSOR_MAP_SWIZZLE_128B, CU_TENSOR_MAP_L2_PROMOTION_L2_256B);
    }
    {
        cuuint64_t dims[3] = {1792, 512, 1}; cuuint64_t str[2] = {3584, 3584 * 512}; cuuint32_t box[3] = {16, 256, 1};
        encode(enc, &maps.m[4], d_in[6], 3, dims, str, box, CU_TENSOR_MAP_SWIZZLE_32B, CU_TENSOR_MAP_L2_PROMOTION_L2_128B);
        encode(enc, &maps.m[5], d_in[7], 3, dims, str, box, CU_TENSOR_MAP_SWIZZLE_32B, CU_TENSOR_MAP_L2_PROMOTION_L2_128B);
    }
    {
        cuuint64_t dims[3] = {64, 1792, 8}; cuuint64_t str[2] = {1024, 128}; cuuint32_t box[3] = {64, 16, 4};
        encode(enc, &maps.m[6], d_in[8], 3, dims, str, box, CU_TENSOR_MAP_SWIZZLE_128B, CU_TENSOR_MAP_L2_PROMOTION_L2_256B);
    }
    fused_decode_kernel<<<NCTA, NTHREADS, SMEM_BYTES, cudaStreamPerThread>>>(maps, (const __nv_bfloat16*)x, (__nv_bfloat16*)d_out);
}
```

```cpp
#include <cuda_runtime.h>
#include <cuda_bf16.h>
#include <cuda.h>
#include <stdint.h>

namespace {

constexpr int NCTA      = 128;
constexpr int NTHREADS  = 320;
constexpr int SLOT      = 32768;
constexpr int NSLOT     = 6;
constexpr int NTILE     = 16;
constexpr int NFFN      = 112;
#define DEPTH_LO 2
#define DEPTH_HI 3
#define LEAD_THR8 4
#define GATE_MARGIN 0
#define WDEPTH 2
#define SEQ_WO 33
constexpr int SEQ_K15 = (SEQ_WO == 31) ? 32 : 31;
constexpr int NSEQ    = 34;
constexpr int SLOT_WGU = 4, SLOT_WD = 5;
#define RESET_TILE 8
constexpr uint32_t SENT = 0xFFFFFFFFu;

constexpr int OFF_XN   = NSLOT * SLOT;
constexpr int XN_PITCH = 1040;
constexpr int OFF_QS   = OFF_XN + 4 * XN_PITCH;
constexpr int QS_PITCH = 272;
constexpr int OFF_P    = OFF_QS + 4 * QS_PITCH;
constexpr int OFF_RED  = OFF_P + 4 * QS_PITCH;
constexpr int OFF_MX   = OFF_RED + 4096;
constexpr int OFF_L    = OFF_MX + 64;
constexpr int OFF_ACT  = OFF_L + 128;
constexpr int OFF_RED2 = OFF_ACT + 128;
constexpr int OFF_CS   = OFF_RED2 + 512;
constexpr int OFF_ST   = OFF_CS + 512;
constexpr int OFF_BAR  = OFF_ST + 32;
constexpr int OFF_VAR  = OFF_BAR + 160;
constexpr int SMEM_USED = OFF_VAR + 64;
constexpr int SMEM_BYTES = SMEM_USED + 1024;
static_assert(OFF_RED % 16 == 0 && OFF_MX % 16 == 0 && OFF_ST % 8 == 0 && OFF_BAR % 8 == 0, "alignment");

__device__ uint2    g_q[4 * 2048];
__device__ float    g_partO[32 * 4 * 4 * 128];
__device__ float2   g_ml[32 * 4 * 4];
__device__ float    g_ypart[4 * 32 * 32 * 16];
__device__ uint16_t g_h[4 * 512];
__device__ float    g_dpart[4 * 32 * NFFN * 16];
__device__ unsigned g_cnt0, g_cnt1, g_prog;
#define TS(i)
#define TSX(i, cond)
#define TSG(i)
#define TSD(i, cond, dep)

__device__ __forceinline__ uint32_t smem_u32(const void* p) { return (uint32_t)__cvta_generic_to_shared(p); }
__device__ __forceinline__ void mbar_init(uint32_t bar, uint32_t cnt) {
    asm volatile("mbarrier.init.shared::cta.b64 [%0], %1;" ::"r"(bar), "r"(cnt) : "memory");
}
__device__ __forceinline__ void mbar_expect_tx(uint32_t bar, uint32_t bytes) {
    asm volatile("mbarrier.arrive.expect_tx.shared::cta.b64 _, [%0], %1;" ::"r"(bar), "r"(bytes) : "memory");
}
__device__ __forceinline__ void mbar_arrive(uint32_t bar) {
    asm volatile("mbarrier.arrive.shared::cta.b64 _, [%0];" ::"r"(bar) : "memory");
}
__device__ __forceinline__ bool mbar_try(uint32_t bar, uint32_t parity) {
    uint32_t ok;
    asm volatile("{\n.reg .pred p;\nmbarrier.try_wait.parity.shared::cta.b64 p, [%1], %2;\nselp.u32 %0, 1, 0, p;\n}"
                 : "=r"(ok) : "r"(bar), "r"(parity) : "memory");
    return ok != 0;
}
constexpr uint32_t SPIN_LIMIT = 1u << 22;
__device__ __forceinline__ void mbar_wait(uint32_t bar, uint32_t parity) {
    uint32_t it = 0;
    while (!mbar_try(bar, parity)) { if (++it > SPIN_LIMIT) __trap(); }
}
__device__ __forceinline__ void tma3d(uint32_t dst, const CUtensorMap* m, int c0, int c1, int c2, uint32_t bar, uint64_t pol) {
    asm volatile("cp.async.bulk.tensor.3d.shared::cluster.global.mbarrier::complete_tx::bytes.L2::cache_hint [%0], [%1, {%3, %4, %5}], [%2], %6;"
                 ::"r"(dst), "l"(m), "r"(bar), "r"(c0), "r"(c1), "r"(c2), "l"(pol) : "memory");
}
__device__ __forceinline__ void tma3d_prefetch(const CUtensorMap* m, int c0, int c1, int c2) {
    asm volatile("cp.async.bulk.prefetch.tensor.3d.L2.global.tile [%0, {%1, %2, %3}];" ::"l"(m), "r"(c0), "r"(c1), "r"(c2) : "memory");
}
__device__ __forceinline__ void ldsm4(uint32_t (&r)[4], uint32_t addr) {
    asm volatile("ldmatrix.sync.aligned.m8n8.x4.shared.b16 {%0,%1,%2,%3}, [%4];"
                 : "=r"(r[0]), "=r"(r[1]), "=r"(r[2]), "=r"(r[3]) : "r"(addr) : "memory");
}
__device__ __forceinline__ void ldsm4t(uint32_t (&r)[4], uint32_t addr) {
    asm volatile("ldmatrix.sync.aligned.m8n8.x4.trans.shared.b16 {%0,%1,%2,%3}, [%4];"
                 : "=r"(r[0]), "=r"(r[1]), "=r"(r[2]), "=r"(r[3]) : "r"(addr) : "memory");
}
__device__ __forceinline__ void mma16816(float (&c)[4], const uint32_t (&a)[4], uint32_t b0, uint32_t b1) {
    asm volatile("mma.sync.aligned.m16n8k16.row.col.f32.bf16.bf16.f32 {%0,%1,%2,%3}, {%4,%5,%6,%7}, {%8,%9}, {%0,%1,%2,%3};"
                 : "+f"(c[0]), "+f"(c[1]), "+f"(c[2]), "+f"(c[3])
                 : "r"(a[0]), "r"(a[1]), "r"(a[2]), "r"(a[3]), "r"(b0), "r"(b1));
}
__device__ __forceinline__ void cbar() { asm volatile("bar.sync 1, 256;" ::: "memory"); }
__device__ __forceinline__ void bar_sync(int id, int n) { asm volatile("bar.sync %0, %1;" ::"r"(id), "r"(n) : "memory"); }
__device__ __forceinline__ void bar_arrive(int id, int n) { asm volatile("bar.arrive %0, %1;" ::"r"(id), "r"(n) : "memory"); }
__device__ __forceinline__ uint4 ld_poll4(const void* p) {
    uint4 v;
    asm volatile("ld.relaxed.gpu.global.v4.u32 {%0,%1,%2,%3}, [%4];" : "=r"(v.x), "=r"(v.y), "=r"(v.z), "=r"(v.w) : "l"(p) : "memory");
    return v;
}
__device__ __forceinline__ uint2 ld_poll2(const void* p) {
    uint2 v;
    asm volatile("ld.relaxed.gpu.global.v2.u32 {%0,%1}, [%2];" : "=r"(v.x), "=r"(v.y) : "l"(p) : "memory");
    return v;
}
__device__ __forceinline__ void st_rel32(void* p, uint32_t v) { asm volatile("st.relaxed.gpu.global.u32 [%0], %1;" ::"l"(p), "r"(v) : "memory"); }
__device__ __forceinline__ void st_rel16(void* p, uint16_t v) { asm volatile("st.relaxed.gpu.global.u16 [%0], %1;" ::"l"(p), "h"(v) : "memory"); }
__device__ __forceinline__ void st_rel64(void* p, uint32_t a, uint32_t b) { asm volatile("st.relaxed.gpu.global.v2.u32 [%0], {%1,%2};" ::"l"(p), "r"(a), "r"(b) : "memory"); }
__device__ __forceinline__ void st_rel128(void* p, uint32_t v) { asm volatile("st.relaxed.gpu.global.v4.u32 [%0], {%1,%1,%1,%1};" ::"l"(p), "r"(v) : "memory"); }
__device__ __forceinline__ uint32_t umax4(const uint4& v) { return max(max(v.x, v.y), max(v.z, v.w)); }
template <class T> __device__ __forceinline__ void pin(T*& p) { asm volatile("" : "+l"(p)); }
__device__ __forceinline__ bool valid8h(const uint4& v) {
    return (__vcmpeq2(v.x, SENT) | __vcmpeq2(v.y, SENT) | __vcmpeq2(v.z, SENT) | __vcmpeq2(v.w, SENT)) == 0;
}
struct Spin {
    uint32_t it = 0;
    __device__ __forceinline__ void tick() { if (++it > SPIN_LIMIT) __trap(); }
};
__device__ __forceinline__ uint32_t pack_bf16(float lo, float hi) {
    uint32_t r; asm("cvt.rn.bf16x2.f32 %0, %1, %2;" : "=r"(r) : "f"(hi), "f"(lo)); return r;
}
__device__ __forceinline__ float bf16r(float x) { return __uint_as_float(pack_bf16(0.f, x) & 0xFFFF0000u); }
__device__ __forceinline__ float bf_lo(uint32_t v) { return __uint_as_float(v << 16); }
__device__ __forceinline__ float bf_hi(uint32_t v) { return __uint_as_float(v & 0xFFFF0000u); }
__device__ __forceinline__ uint32_t hmax2(uint32_t a, uint32_t b) {
    uint32_t r; asm("max.bf16x2 %0, %1, %2;" : "=r"(r) : "r"(a), "r"(b)); return r;
}
__device__ __forceinline__ float ex2(float x) { float r; asm("ex2.approx.ftz.f32 %0, %1;" : "=f"(r) : "f"(x)); return r; }

__device__ __forceinline__ float2 ln_stats(const uint4& a, const uint4& b, float (&v)[16]) {
    v[0] = bf_lo(a.x); v[1] = bf_hi(a.x); v[2] = bf_lo(a.y); v[3] = bf_hi(a.y);
    v[4] = bf_lo(a.z); v[5] = bf_hi(a.z); v[6] = bf_lo(a.w); v[7] = bf_hi(a.w);
    v[8] = bf_lo(b.x); v[9] = bf_hi(b.x); v[10] = bf_lo(b.y); v[11] = bf_hi(b.y);
    v[12] = bf_lo(b.z); v[13] = bf_hi(b.z); v[14] = bf_lo(b.w); v[15] = bf_hi(b.w);
    const float shift = __shfl_sync(0xffffffffu, v[0], 0);
    float s = 0.f, ss = 0.f;
#pragma unroll
    for (int i = 0; i < 16; i++) { float d = v[i] - shift; s += d; ss = fmaf(d, d, ss); }
#pragma unroll
    for (int o = 16; o > 0; o >>= 1) { s += __shfl_xor_sync(0xffffffffu, s, o); ss += __shfl_xor_sync(0xffffffffu, ss, o); }
    const float md = s * (1.0f / 512.0f);
    const float var = fmaxf(ss * (1.0f / 512.0f) - md * md, 0.f);
    const float m = bf16r(shift + md);
    const float sd = bf16r(sqrtf(bf16r(bf16r(var) + 1e-5f)));
    return make_float2(m, 1.0f / sd);
}

struct Maps { CUtensorMap m[7]; };

__global__ void __launch_bounds__(NTHREADS, 1)
fused_decode_kernel(const __grid_constant__ Maps maps,
                    const __nv_bfloat16* __restrict__ x, __nv_bfloat16* __restrict__ out)
{
    extern __shared__ __align__(1024) unsigned char smem_raw[];
    unsigned char* smem = smem_raw + ((1024u - (smem_u32(smem_raw) & 1023u)) & 1023u);
    const uint32_t sbase = smem_u32(smem);
    const uint32_t bar_full = sbase + OFF_BAR, bar_empty = sbase + OFF_BAR + 48, bar_ready = sbase + OFF_BAR + 96, bar_w = sbase + OFF_BAR + 104;
    volatile unsigned* vars = reinterpret_cast<volatile unsigned*>(smem + OFF_VAR);
    const int tid = threadIdx.x, warp = tid >> 5, lane = tid & 31;
    const int cta = blockIdx.x;

    if (tid == 0) TSG(0);
    if (tid == 256) {
        for (int i = 0; i < NSLOT; i++) { mbar_init(bar_full + 8 * i, 1); mbar_init(bar_empty + 8 * i, 8); }
        mbar_init(bar_ready, 1);
        for (int i = 0; i < 6; i++) mbar_init(bar_w + 8 * i, 1);
        vars[1] = 0; vars[2] = 0;
        asm volatile("fence.mbarrier_init.release.cluster;" ::: "memory");
    }
    __syncthreads();

    if (warp == 8) {
        if (lane == 0) {
            uint64_t pol_first, pol_norm;
            asm volatile("createpolicy.fractional.L2::evict_first.b64 %0, 1.0;" : "=l"(pol_first));
            asm volatile("createpolicy.fractional.L2::evict_normal.b64 %0, 1.0;" : "=l"(pol_norm));
            const int key0 = cta * (NTILE * 128);
            int arrived = 0;
            unsigned gbase = 0, grel = 0;
            int nkv = 0;
            for (int i = 0; i < NSEQ; i++) {
                const int slot = i % NSLOT;
                const bool is_w = (i == 0) || (i == SEQ_WO);
                if (i >= NSLOT) mbar_wait(bar_empty + 8 * slot, ((i / NSLOT) - 1) & 1);
                const int lead8 = (nkv * NCTA - (int)grel) / (NCTA / 8);
                const int d = (i > 2 && lead8 > LEAD_THR8) ? DEPTH_LO : DEPTH_HI;
                while (arrived < i - d + 1) { mbar_wait(bar_full + 8 * (arrived % NSLOT), (arrived / NSLOT) & 1); arrived++; }
                const uint32_t dst = sbase + slot * SLOT, fb = bar_full + 8 * slot;
                int mi, c0 = 0, c1 = 0, c2 = 0, nbox = 1;
                if (i == 0)            { mi = 2; c0 = cta * 32; nbox = 2; }
                else if (i == SEQ_WO)  { mi = 3; c1 = (cta >> 2) * 128; c2 = (cta & 3) * 2; }
                else                   { mi = nkv & 1; c1 = key0 + (nkv >> 1) * 128; }
                mbar_expect_tx(fb, 32768);
                for (int j = 0; j < nbox; j++) tma3d(dst + j * 16384, &maps.m[mi], c0, c1 + j * 256, c2, fb, is_w ? pol_norm : pol_first);
                if (!is_w) {
                    if (nkv < 31) {
                        const unsigned g = atomicAdd(&g_prog, 1u);
                        if (nkv == 0) gbase = g & ~(unsigned)(NCTA * 32 - 1);
                        grel = g - gbase;
                    } else {
                        asm volatile("red.relaxed.gpu.global.add.u32 [%0], 1;" ::"l"(&g_prog) : "memory");
                    }
                    nkv++;
                }
            }
            if (cta < NFFN) {
                mbar_wait(bar_empty + 8 * SLOT_WGU, (34 / NSLOT - 1) & 1);
                mbar_wait(bar_empty + 8 * SLOT_WD, (35 / NSLOT - 1) & 1);
                if ((int)grel < NCTA * 32 - GATE_MARGIN) {
                    Spin sp; unsigned v;
                    while (true) {
                        asm volatile("ld.relaxed.gpu.global.u32 %0, [%1];" : "=r"(v) : "l"(&g_prog) : "memory");
                        if ((int)(v - gbase) >= NCTA * 32 - GATE_MARGIN) break;
                        sp.tick(); __nanosleep(64);
                    }
                }
                TSX(26, true);
                for (int k = 0; k < 6; k++) {
                    if (k >= WDEPTH) mbar_wait(bar_w + 8 * (k - WDEPTH), 0);
                    mbar_expect_tx(bar_w + 8 * k, 8192);
                    const int mi = (k < 4) ? 4 + (k >> 1) : 6;
                    const int c0 = (k < 4) ? cta * 16 : 0, c1 = (k < 4) ? (k & 1) * 256 : cta * 16, c2 = (k < 4) ? 0 : (k - 4) * 4;
                    tma3d(sbase + SLOT_WGU * SLOT + k * 8192, &maps.m[mi], c0, c1, c2, bar_w + 8 * k, pol_norm);
                }
            }
            TSX(20, true);
        }
        return;
    }

    const int pair = cta >> 2, split = cta & 3;

    if (warp == 9) {
        Spin sp;
        while (vars[1] < RESET_TILE) { sp.tick(); __nanosleep(256); }
        const unsigned epoch = vars[0];
#pragma unroll 1
        for (int u = lane; u < 128; u += 32) {
            st_rel128(&g_partO[((pair * 4 + (u >> 5)) * 4 + split) * 128 + (u & 31) * 4], SENT);
            const int seg = u >> 2;
            st_rel128(&g_ypart[(((seg >> 3) * 32 + (cta & 3) * 8 + (seg & 7)) * 32 + (cta >> 2)) * 16 + (u & 3) * 4], SENT);
        }
        if (lane < 4) st_rel64(&g_ml[(pair * 4 + lane) * 4 + split], SENT, SENT);
        if (lane < 2) st_rel128(&g_h[(cta >> 5) * 512 + (cta & 31) * 16 + lane * 8], SENT);
        if (cta < NFFN) {
#pragma unroll 1
            for (int e = lane; e < 512; e += 32) st_rel128(&g_dpart[((e >> 2) * NFFN + cta) * 16 + (e & 3) * 4], SENT);
        }
        __threadfence();
        __syncwarp();
        if (lane == 0) {
            atomicAdd(&g_cnt1, 1u);
            unsigned v; Spin sp2;
            while (true) {
                asm volatile("ld.acquire.gpu.global.u32 %0, [%1];" : "=r"(v) : "l"(&g_cnt1) : "memory");
                if ((int)(v - (epoch + 1) * NCTA) >= 0) break;
                sp2.tick(); __nanosleep(128);
            }
            mbar_arrive(bar_ready);
        }
        TSX(24, lane == 0);
        return;
    }

    const int r8 = lane >> 2, q4 = lane & 3;
    const int hp = q4 & 1, kh = q4 >> 1;
    constexpr float LOG2E = 1.4426950408889634f;
    const int bq = pair >> 3, gq = pair & 7;

    if (tid == 0) vars[0] = atomicAdd(&g_cnt0, 1u) >> 7;
    if (warp == 7) st_rel128(&g_q[(lane >> 3) * 2048 + cta * 16 + (lane & 7) * 2], 0u);
    float xres = 0.f;
    if (warp == 0) xres = __bfloat162float(x[(cta >> 5) * 512 + (cta & 31) * 16 + (lane >> 1)]);

    if (warp < 4) {
        const uint4* xr = reinterpret_cast<const uint4*>(x + warp * 512);
        const uint4 a = __ldg(xr + lane), b = __ldg(xr + 32 + lane);
        float v[16];
        const float2 st = ln_stats(a, b, v);
        uint32_t o[8];
#pragma unroll
        for (int i = 0; i < 8; i++) o[i] = pack_bf16(bf16r(v[2 * i] - st.x) * st.y, bf16r(v[2 * i + 1] - st.x) * st.y);
        unsigned char* row = smem + OFF_XN + warp * XN_PITCH;
        *reinterpret_cast<uint4*>(row + lane * 16) = make_uint4(o[0], o[1], o[2], o[3]);
        *reinterpret_cast<uint4*>(row + 512 + lane * 16) = make_uint4(o[4], o[5], o[6], o[7]);
    }
    cbar();
    const uint32_t tag = vars[0] + 1;

    {
        uint32_t bfr[4][2];
        {
            uint32_t t4[4];
#pragma unroll
            for (int u = 0; u < 2; u++) {
                ldsm4(t4, sbase + OFF_XN + (lane & 3) * XN_PITCH + (8 * warp + 4 * u + (lane >> 3)) * 16);
                bfr[2 * u][0] = t4[0]; bfr[2 * u][1] = t4[1]; bfr[2 * u + 1][0] = t4[2]; bfr[2 * u + 1][1] = t4[3];
            }
        }
        mbar_wait(bar_full + 0, 0);
        TS(2);
        float acc[2][4] = {};
#pragma unroll
        for (int ks = 0; ks < 4; ks++) {
            const int k = 64 * warp + 16 * ks + (lane & 7) + (lane >> 4) * 8;
#pragma unroll
            for (int mt = 0; mt < 2; mt++) {
                uint32_t a[4];
                const int chunk = 2 * mt + ((lane >> 3) & 1);
                ldsm4t(a, sbase + k * 64 + ((chunk ^ ((k >> 1) & 3)) << 4));
                mma16816(acc[mt], a, bfr[ks][0], bfr[ks][1]);
            }
        }
        __syncwarp();
        if (lane == 0) mbar_arrive(bar_empty + 0);
        float* red = reinterpret_cast<float*>(smem + OFF_RED);
#pragma unroll
        for (int mt = 0; mt < 2; mt++) {
            float2 v = kh ? make_float2(acc[mt][2], acc[mt][3]) : make_float2(acc[mt][0], acc[mt][1]);
            *reinterpret_cast<float2*>(red + ((warp * 2 + mt) * 16 + r8 + 8 * kh) * 4 + 2 * hp) = v;
        }
        cbar();
        if (tid < 64) {
            const int b = tid >> 4, c2 = tid & 15;
            float s0 = 0.f, s1 = 0.f;
            const int c0 = 2 * c2, c1 = 2 * c2 + 1;
#pragma unroll
            for (int ww = 0; ww < 8; ww++) {
                s0 += red[((ww * 2 + (c0 >> 4)) * 16 + (c0 & 15)) * 4 + b];
                s1 += red[((ww * 2 + (c1 >> 4)) * 16 + (c1 & 15)) * 4 + b];
            }
            st_rel64(&g_q[b * 2048 + cta * 16 + c2], pack_bf16(s0, s1), tag);
        }
        {
            const uint2* src = &g_q[bq * 2048 + gq * 256 + tid];
            uint2 v;
            Spin sp;
            while (true) { v = ld_poll2(src); if (__all_sync(0xffffffffu, v.y == tag)) break; sp.tick(); }
            *reinterpret_cast<uint32_t*>(smem + OFF_QS + (tid >> 6) * QS_PITCH + (tid & 63) * 4) = v.x;
        }
        cbar();
    }
    TS(3);
    uint32_t qf[8][2];
    {
        uint32_t t4[4];
#pragma unroll
        for (int u = 0; u < 4; u++) {
            ldsm4(t4, sbase + OFF_QS + (lane & 3) * QS_PITCH + (4 * u + (lane >> 3)) * 16);
            qf[2 * u][0] = t4[0]; qf[2 * u][1] = t4[1]; qf[2 * u + 1][0] = t4[2]; qf[2 * u + 1][1] = t4[3];
        }
    }

    const uint32_t voff = (warp >> 2) * 16384 + ((lane & 7) + (lane >> 4) * 8) * 128 +
                          ((((2 * warp + ((lane >> 3) & 1)) & 7) ^ (lane & 7)) << 4);
    const uint32_t poff = sbase + OFF_P + (lane & 3) * QS_PITCH + (lane >> 3) * 16;
    const uint32_t koff = (16 * warp + (lane & 7) + ((lane >> 3) & 1) * 8) * 128;
    const uint32_t kx = lane & 7, kc = lane >> 4;
    constexpr float SCALE = 0.08838834764831845f;
    uint32_t* mxbuf = reinterpret_cast<uint32_t*>(smem + OFF_MX);
    uint32_t M2 = 0xFF80FF80u;
    float l0 = 0.f, l1 = 0.f;
    float oacc[2][4] = {};
    int slot = 1; uint32_t ph = 0;

    for (int t = 0;; t++) {
        mbar_wait(bar_full + 8 * slot, ph);
        float sa[4] = {}, sb[4] = {};
        {
            const uint32_t kb = sbase + slot * SLOT + koff;
#pragma unroll
            for (int ks = 0; ks < 8; ks++) {
                uint32_t a[4];
                ldsm4(a, kb + (ks >> 2) * 16384 + (((2 * (ks & 3) + kc) ^ kx) << 4));
                if (ks & 1) mma16816(sb, a, qf[ks][0], qf[ks][1]); else mma16816(sa, a, qf[ks][0], qf[ks][1]);
            }
        }
        __syncwarp();
        if (lane == 0) mbar_arrive(bar_empty + 8 * slot);
        if (++slot == NSLOT) { slot = 0; ph ^= 1; }

        const float r0 = kh ? sa[2] + sb[2] : sa[0] + sb[0];
        const float r1 = kh ? sa[3] + sb[3] : sa[1] + sb[1];
        uint32_t sp = pack_bf16(r0, r1);
        sp = pack_bf16(bf_lo(sp) * SCALE, bf_hi(sp) * SCALE);
        uint32_t mx = sp;
#pragma unroll
        for (int o = 2; o <= 16; o <<= 1) mx = hmax2(mx, __shfl_xor_sync(0xffffffffu, mx, o));
        if (lane < 2) mxbuf[lane * 8 + warp] = mx;
        if (tid == 0) vars[1] = t + 1;
        TS(40 + t);
        cbar();
        {
            const uint4 m0 = *reinterpret_cast<const uint4*>(mxbuf + hp * 8), m1 = *reinterpret_cast<const uint4*>(mxbuf + hp * 8 + 4);
            uint32_t mt = hmax2(hmax2(hmax2(m0.x, m0.y), hmax2(m0.z, m0.w)), hmax2(hmax2(m1.x, m1.y), hmax2(m1.z, m1.w)));
            const uint32_t Mn = hmax2(M2, mt);
            const float a0 = ex2((bf_lo(M2) - bf_lo(Mn)) * LOG2E), a1 = ex2((bf_hi(M2) - bf_hi(Mn)) * LOG2E);
            const float p0 = ex2((bf_lo(sp) - bf_lo(Mn)) * LOG2E), p1 = ex2((bf_hi(sp) - bf_hi(Mn)) * LOG2E);
            M2 = Mn;
            l0 = fmaf(l0, a0, p0); l1 = fmaf(l1, a1, p1);
            const uint32_t pp = pack_bf16(p0, p1);
            unsigned char* pd = smem + OFF_P + (2 * hp) * QS_PITCH + (16 * warp + r8 + 8 * kh) * 2;
            *reinterpret_cast<uint16_t*>(pd) = (uint16_t)(pp & 0xFFFF);
            *reinterpret_cast<uint16_t*>(pd + QS_PITCH) = (uint16_t)(pp >> 16);
#pragma unroll
            for (int c = 0; c < 2; c++) { oacc[c][0] *= a0; oacc[c][1] *= a1; oacc[c][2] *= a0; oacc[c][3] *= a1; }
        }
        if (t == NTILE - 1) break;
        cbar();
        uint32_t pb[8][2];
        {
            uint32_t t4[4];
#pragma unroll
            for (int u = 0; u < 4; u++) {
                ldsm4(t4, poff + u * 64);
                pb[2 * u][0] = t4[0]; pb[2 * u][1] = t4[1]; pb[2 * u + 1][0] = t4[2]; pb[2 * u + 1][1] = t4[3];
            }
        }
        mbar_wait(bar_full + 8 * slot, ph);
        {
            const uint32_t vb = sbase + slot * SLOT + voff;
#pragma unroll
            for (int ks = 0; ks < 8; ks++) {
                uint32_t a[4];
                ldsm4t(a, vb + ks * 2048);
                mma16816(oacc[ks & 1], a, pb[ks][0], pb[ks][1]);
            }
        }
        __syncwarp();
        if (lane == 0) mbar_arrive(bar_empty + 8 * slot);
        if (++slot == NSLOT) { slot = 0; ph ^= 1; }
        if (SEQ_WO == 31 && t == NTILE - 2) { if (++slot == NSLOT) { slot = 0; ph ^= 1; } }
    }

    const int head = cta >> 2;
    float* p_partO = &g_partO[((pair * 4 + 2 * hp) * 4 + split) * 128 + 16 * warp + r8 + 8 * kh];
    float* p_dpart = &g_dpart[(((2 * hp) * 32 + 4 * warp) * NFFN + cta) * 16 + r8 + 8 * kh];
    const float* p_dsrc = &g_dpart[(cta * NFFN + (tid >> 2)) * 16 + (tid & 3) * 4];
    __nv_bfloat16* p_out = out + (cta >> 5) * 512 + (cta & 31) * 16 + (lane >> 1);
    pin(p_partO); pin(p_dpart); pin(p_dsrc); pin(p_out);

    {
        float s0 = l0, s1 = l1;
#pragma unroll
        for (int o = 2; o <= 16; o <<= 1) { s0 += __shfl_xor_sync(0xffffffffu, s0, o); s1 += __shfl_xor_sync(0xffffffffu, s1, o); }
        if (lane < 2) *reinterpret_cast<float2*>(smem + OFF_L + warp * 16 + lane * 8) = make_float2(s0, s1);
        mbar_wait(bar_ready, 0);
        cbar();
        if (warp == 0) {
            const uint32_t other = __shfl_sync(0xffffffffu, M2, lane >> 1);
            float l = 0.f;
#pragma unroll
            for (int ww = 0; ww < 8; ww++) l += *reinterpret_cast<const float*>(smem + OFF_L + ww * 16 + (lane & 3) * 4);
            const float m = (lane & 1) ? bf_hi(other) : bf_lo(other);
            if (lane < 4) st_rel64(&g_ml[(pair * 4 + lane) * 4 + split], __float_as_uint(m), __float_as_uint(l));
        }
        uint32_t pb[8][2];
        {
            uint32_t t4[4];
#pragma unroll
            for (int u = 0; u < 4; u++) {
                ldsm4(t4, poff + u * 64);
                pb[2 * u][0] = t4[0]; pb[2 * u][1] = t4[1]; pb[2 * u + 1][0] = t4[2]; pb[2 * u + 1][1] = t4[3];
            }
        }
        float o2[2][4] = {};
        mbar_wait(bar_full + 8 * slot, ph);
        {
            const uint32_t vb = sbase + slot * SLOT + voff;
            uint32_t a[8][4];
#pragma unroll
            for (int ks = 0; ks < 8; ks++) ldsm4t(a[ks], vb + ks * 2048);
#pragma unroll
            for (int ks = 0; ks < 8; ks++) mma16816((ks & 2) ? o2[ks & 1] : oacc[ks & 1], a[ks], pb[ks][0], pb[ks][1]);
        }
        const float v0 = kh ? (oacc[0][2] + oacc[1][2]) + (o2[0][2] + o2[1][2]) : (oacc[0][0] + oacc[1][0]) + (o2[0][0] + o2[1][0]);
        const float v1 = kh ? (oacc[0][3] + oacc[1][3]) + (o2[0][3] + o2[1][3]) : (oacc[0][1] + oacc[1][1]) + (o2[0][1] + o2[1][1]);
        st_rel32(p_partO, __float_as_uint(v0));
        st_rel32(p_partO + 512, __float_as_uint(v1));
        TS(4);
    }

    float hres = 0.f;
    uint32_t df[4][4];
    if (warp < 4) {
        {
            const int ph_idx = (warp * 8 + (head >> 2)) * 4 + (head & 3);
            const float* po = &g_partO[ph_idx * 512 + lane * 4];
            const float* pm = reinterpret_cast<const float*>(&g_ml[ph_idx * 4]);
            uint4 o0, o1, o2, o3, ma, mb;
            Spin sp;
            while (true) {
                o0 = ld_poll4(po); o1 = ld_poll4(po + 128); o2 = ld_poll4(po + 256); o3 = ld_poll4(po + 384);
                ma = ld_poll4(pm); mb = ld_poll4(pm + 4);
                const uint32_t mxv = max(max(max(umax4(o0), umax4(o1)), max(umax4(o2), umax4(o3))), max(umax4(ma), umax4(mb)));
                if (__all_sync(0xffffffffu, mxv != SENT)) break;
                sp.tick();
            }
            TS(6);
            const float m0 = __uint_as_float(ma.x), m1 = __uint_as_float(ma.z), m2 = __uint_as_float(mb.x), m3 = __uint_as_float(mb.z);
            const float M = fmaxf(fmaxf(m0, m1), fmaxf(m2, m3));
            float w0 = ex2((m0 - M) * LOG2E), w1 = ex2((m1 - M) * LOG2E), w2 = ex2((m2 - M) * LOG2E), w3 = ex2((m3 - M) * LOG2E);
            const float L = w0 * __uint_as_float(ma.y) + w1 * __uint_as_float(ma.w) + w2 * __uint_as_float(mb.y) + w3 * __uint_as_float(mb.w);
            const float inv = __fdividef(1.0f, L);
            const float e0 = (w0 * __uint_as_float(o0.x) + w1 * __uint_as_float(o1.x) + w2 * __uint_as_float(o2.x) + w3 * __uint_as_float(o3.x)) * inv;
            const float e1 = (w0 * __uint_as_float(o0.y) + w1 * __uint_as_float(o1.y) + w2 * __uint_as_float(o2.y) + w3 * __uint_as_float(o3.y)) * inv;
            const float e2 = (w0 * __uint_as_float(o0.z) + w1 * __uint_as_float(o1.z) + w2 * __uint_as_float(o2.z) + w3 * __uint_as_float(o3.z)) * inv;
            const float e3 = (w0 * __uint_as_float(o0.w) + w1 * __uint_as_float(o1.w) + w2 * __uint_as_float(o2.w) + w3 * __uint_as_float(o3.w)) * inv;
            *reinterpret_cast<uint2*>(smem + OFF_QS + warp * QS_PITCH + lane * 8) = make_uint2(pack_bf16(e0, e1), pack_bf16(e2, e3));
            bar_arrive(2, 256);
        }
        if (warp == 0) {
            const float* src = &g_ypart[(cta * 32 + lane) * 16];
            uint16_t* p_h = &g_h[(cta >> 5) * 512 + (cta & 31) * 16 + (lane >> 1)];
            pin(p_h);
            uint4 y0, y1, y2, y3;
            Spin sp;
            while (true) {
                y0 = ld_poll4(src); y1 = ld_poll4(src + 4); y2 = ld_poll4(src + 8); y3 = ld_poll4(src + 12);
                if (__all_sync(0xffffffffu, max(max(umax4(y0), umax4(y1)), max(umax4(y2), umax4(y3))) != SENT)) break;
                sp.tick();
            }
            TS(9);
            float v0, v1, v2, v3, v4, v5, v6, v7;
            {
                const bool up = lane & 16;
#define RSTEP(dst, lo, hi, m) { const float _l = __uint_as_float(lo), _h = __uint_as_float(hi); dst = (up ? _h : _l) + __shfl_xor_sync(0xffffffffu, up ? _l : _h, m); }
                RSTEP(v0, y0.x, y2.x, 16) RSTEP(v1, y0.y, y2.y, 16) RSTEP(v2, y0.z, y2.z, 16) RSTEP(v3, y0.w, y2.w, 16)
                RSTEP(v4, y1.x, y3.x, 16) RSTEP(v5, y1.y, y3.y, 16) RSTEP(v6, y1.z, y3.z, 16) RSTEP(v7, y1.w, y3.w, 16)
#undef RSTEP
            }
#define RSTEP(dst, a, b, m) { const bool _u = lane & m; dst = (_u ? b : a) + __shfl_xor_sync(0xffffffffu, _u ? a : b, m); }
            RSTEP(v0, v0, v4, 8) RSTEP(v1, v1, v5, 8) RSTEP(v2, v2, v6, 8) RSTEP(v3, v3, v7, 8)
            RSTEP(v0, v0, v2, 4) RSTEP(v1, v1, v3, 4)
            RSTEP(v0, v0, v1, 2)
#undef RSTEP
            v0 += __shfl_xor_sync(0xffffffffu, v0, 1);
            hres = bf16r(xres + bf16r(v0));
            if (!(lane & 1)) st_rel16(p_h, (uint16_t)(__float_as_uint(hres) >> 16));
            TS(10);
        }
        if (cta < NFFN) {
            bar_sync(7, 128);
            const uint4* hr = reinterpret_cast<const uint4*>(g_h + warp * 512);
            uint4 a, b;
            Spin sp;
            while (true) {
                a = ld_poll4(hr + lane); b = ld_poll4(hr + 32 + lane);
                const bool ok = (__vcmpeq2(a.x, SENT) | __vcmpeq2(a.y, SENT) | __vcmpeq2(a.z, SENT) | __vcmpeq2(a.w, SENT) |
                                 __vcmpeq2(b.x, SENT) | __vcmpeq2(b.y, SENT) | __vcmpeq2(b.z, SENT) | __vcmpeq2(b.w, SENT)) == 0;
                if (__all_sync(0xffffffffu, ok)) break;
                sp.tick();
            }
            TS(13);
            unsigned char* row = smem + OFF_XN + warp * XN_PITCH;
            *reinterpret_cast<uint4*>(row + lane * 16) = a;
            *reinterpret_cast<uint4*>(row + 512 + lane * 16) = b;
            bar_arrive(3, 256);
            float v[16];
            const float2 st = ln_stats(a, b, v);
            if (lane == 0) *reinterpret_cast<float2*>(smem + OFF_ST + warp * 8) = st;
            bar_arrive(4, 256);
            TS(14);
            mbar_wait(bar_w + 32, 0); mbar_wait(bar_w + 40, 0);
            const uint32_t wb = sbase + SLOT_WD * SLOT + warp * 2048 + ((lane & 7) + (lane >> 4) * 8) * 128;
#pragma unroll
            for (int i = 0; i < 4; i++) ldsm4t(df[i], wb + (((2 * i + ((lane >> 3) & 1)) ^ (lane & 7)) << 4));
        }
    } else {
        const int m = warp - 4;
        {
            uint32_t af[2][8][4];
            float* p_y = &g_ypart[(((2 * hp) * 32 + (cta & 3) * 8 + 2 * m) * 32 + head) * 16 + r8 + 8 * kh];
            pin(p_y);
            mbar_wait(bar_full + 8 * (SEQ_WO % NSLOT), (SEQ_WO / NSLOT) & 1);
#pragma unroll
            for (int i = 0; i < 2; i++) {
                const int j = 2 * m + i;
                const uint32_t wb = sbase + (SEQ_WO % NSLOT) * SLOT + (j >> 2) * 16384 + ((lane & 7) + (lane >> 4) * 8) * 128 +
                                    ((((2 * j + ((lane >> 3) & 1)) & 7) ^ (lane & 7)) << 4);
#pragma unroll
                for (int ks = 0; ks < 8; ks++) ldsm4t(af[i][ks], wb + ks * 2048);
            }
            TSX(5, tid == 128);
            bar_sync(2, 256);
            TSX(7, tid == 128);
            float acc[2][2][4] = {};
            uint32_t t4[4][4];
#pragma unroll
            for (int u = 0; u < 4; u++) ldsm4(t4[u], sbase + OFF_QS + (lane & 3) * QS_PITCH + (4 * u + (lane >> 3)) * 16);
#pragma unroll
            for (int u = 0; u < 4; u++) {
#pragma unroll
                for (int i = 0; i < 2; i++) {
                    mma16816(acc[i][0], af[i][2 * u], t4[u][0], t4[u][1]);
                    mma16816(acc[i][1], af[i][2 * u + 1], t4[u][2], t4[u][3]);
                }
            }
#pragma unroll
            for (int i = 0; i < 2; i++) {
                const float v0 = kh ? acc[i][0][2] + acc[i][1][2] : acc[i][0][0] + acc[i][1][0];
                const float v1 = kh ? acc[i][0][3] + acc[i][1][3] : acc[i][0][1] + acc[i][1][1];
                st_rel32(p_y + i * 32 * 16, __float_as_uint(v0));
                st_rel32(p_y + i * 32 * 16 + 32 * 32 * 16, __float_as_uint(v1));
            }
            TSX(8, tid == 128);
        }
        if (cta < NFFN) {
            uint32_t gf[8][2][4];
            mbar_wait(bar_w, 0); mbar_wait(bar_w + 8, 0); mbar_wait(bar_w + 16, 0); mbar_wait(bar_w + 24, 0);
#pragma unroll
            for (int ks = 0; ks < 8; ks++) {
                const int k = 128 * m + 16 * ks + (lane & 7) + (lane >> 4) * 8;
                const uint32_t a = sbase + SLOT_WGU * SLOT + k * 32 + ((((lane >> 3) & 1) ^ ((k >> 2) & 1)) << 4);
                ldsm4t(gf[ks][0], a);
                ldsm4t(gf[ks][1], a + 16384);
            }
            TSX(11, tid == 128);
            float sg = 0.f, su = 0.f;
            {
                float cs[2][4] = {};
#pragma unroll
                for (int ks = 0; ks < 8; ks++) { mma16816(cs[0], gf[ks][0], 0x3F803F80u, 0x3F803F80u); mma16816(cs[1], gf[ks][1], 0x3F803F80u, 0x3F803F80u); }
                float* csb = reinterpret_cast<float*>(smem + OFF_CS);
                if (q4 == 0) {
                    csb[(m * 2 + 0) * 16 + r8] = cs[0][0]; csb[(m * 2 + 0) * 16 + r8 + 8] = cs[0][2];
                    csb[(m * 2 + 1) * 16 + r8] = cs[1][0]; csb[(m * 2 + 1) * 16 + r8 + 8] = cs[1][2];
                }
                bar_sync(5, 128);
                const int c = (tid & 63) >> 2;
#pragma unroll
                for (int ww = 0; ww < 4; ww++) { sg += csb[(ww * 2) * 16 + c]; su += csb[(ww * 2 + 1) * 16 + c]; }
            }
            mbar_wait(bar_w + 32, 0); mbar_wait(bar_w + 40, 0);
            {
                const uint32_t wb = sbase + SLOT_WD * SLOT + warp * 2048 + ((lane & 7) + (lane >> 4) * 8) * 128;
#pragma unroll
                for (int i = 0; i < 4; i++) ldsm4t(df[i], wb + (((2 * i + ((lane >> 3) & 1)) ^ (lane & 7)) << 4));
            }
            TSX(12, tid == 128);
            bar_sync(3, 256);
            float acc[2][2][4] = {};
            uint32_t t4[4][4];
#pragma unroll
            for (int u = 0; u < 4; u++) ldsm4(t4[u], sbase + OFF_XN + (lane & 3) * XN_PITCH + (16 * m + 4 * u + (lane >> 3)) * 16);
#pragma unroll
            for (int u = 0; u < 4; u++) {
#pragma unroll
                for (int i = 0; i < 2; i++) {
                    mma16816(acc[i][0], gf[2 * u][i], t4[u][0], t4[u][1]);
                    mma16816(acc[i][1], gf[2 * u + 1][i], t4[u][2], t4[u][3]);
                }
            }
            float* red = reinterpret_cast<float*>(smem + OFF_RED);
#pragma unroll
            for (int i = 0; i < 2; i++) {
                const float2 v = kh ? make_float2(acc[i][0][2] + acc[i][1][2], acc[i][0][3] + acc[i][1][3])
                                    : make_float2(acc[i][0][0] + acc[i][1][0], acc[i][0][1] + acc[i][1][1]);
                *reinterpret_cast<float2*>(red + ((m * 2 + i) * 16 + r8 + 8 * kh) * 4 + 2 * hp) = v;
            }
            bar_sync(4, 256);
            TSX(16, tid == 128);
            if (tid < 192) {
                const int c = (tid & 63) >> 2, b = tid & 3;
                const float2 st = *reinterpret_cast<const float2*>(smem + OFF_ST + b * 8);
                float g = 0.f, u = 0.f;
#pragma unroll
                for (int ww = 0; ww < 4; ww++) { g += red[((ww * 2) * 16 + c) * 4 + b]; u += red[((ww * 2 + 1) * 16 + c) * 4 + b]; }
                g = bf16r((g - st.x * sg) * st.y); u = bf16r((u - st.x * su) * st.y);
                const float inner = 0.7978845608028654f * (g + 0.044715f * g * g * g);
                const float th = 1.0f - __fdividef(2.0f, __expf(2.0f * inner) + 1.0f);
                const float ge = bf16r(0.5f * g * (1.0f + th));
                *reinterpret_cast<__nv_bfloat16*>(smem + OFF_ACT + b * 32 + c * 2) = __float2bfloat16_rn(ge * u);
            }
        }
    }
    if (cta < NFFN) {
        bar_sync(6, 256);
        TS(17);
        const uint32_t b0 = *reinterpret_cast<const uint32_t*>(smem + OFF_ACT + (r8 & 3) * 32 + q4 * 4);
        const uint32_t b1 = *reinterpret_cast<const uint32_t*>(smem + OFF_ACT + (r8 & 3) * 32 + 16 + q4 * 4);
        float c[4][4] = {};
#pragma unroll
        for (int i = 0; i < 4; i++) mma16816(c[i], df[i], b0, b1);
#pragma unroll
        for (int i = 0; i < 4; i++) {
            st_rel32(p_dpart + i * NFFN * 16, __float_as_uint(kh ? c[i][2] : c[i][0]));
            st_rel32(p_dpart + i * NFFN * 16 + 32 * NFFN * 16, __float_as_uint(kh ? c[i][3] : c[i][1]));
        }
        TS(18);
    }

    {
        const int quad = tid & 3;
        const bool two = (tid >> 2) + 64 < NFFN;
        uint4 a, b = make_uint4(0, 0, 0, 0);
        Spin sp;
        while (true) {
            a = ld_poll4(p_dsrc);
            if (two) b = ld_poll4(p_dsrc + 64 * 16);
            if (__all_sync(0xffffffffu, max(umax4(a), umax4(b)) != SENT)) break;
            sp.tick();
        }
        TS(19);
        float v[4] = {__uint_as_float(a.x) + __uint_as_float(b.x), __uint_as_float(a.y) + __uint_as_float(b.y),
                      __uint_as_float(a.z) + __uint_as_float(b.z), __uint_as_float(a.w) + __uint_as_float(b.w)};
        {
            const bool up = lane & 16;
            const float s0 = up ? v[0] : v[2], s1 = up ? v[1] : v[3];
            const float k0 = up ? v[2] : v[0], k1 = up ? v[3] : v[1];
            v[0] = k0 + __shfl_xor_sync(0xffffffffu, s0, 16);
            v[1] = k1 + __shfl_xor_sync(0xffffffffu, s1, 16);
            const bool up2 = lane & 8;
            const float s = up2 ? v[0] : v[1], k = up2 ? v[1] : v[0];
            v[0] = k + __shfl_xor_sync(0xffffffffu, s, 8);
            v[0] += __shfl_xor_sync(0xffffffffu, v[0], 4);
            if (!(lane & 4)) reinterpret_cast<float*>(smem + OFF_RED2)[warp * 16 + 4 * quad + ((lane & 16) ? 2 : 0) + ((lane & 8) ? 1 : 0)] = v[0];
        }
        cbar();
        TS(21);
        if (warp == 0) {
            const float* r2 = reinterpret_cast<const float*>(smem + OFF_RED2) + (lane & 1) * 64 + (lane >> 1);
            float s = (r2[0] + r2[16]) + (r2[32] + r2[48]);
            s += __shfl_xor_sync(0xffffffffu, s, 1);
            if (!(lane & 1)) *p_out = __float2bfloat16_rn(hres + bf16r(s));
        }
    }
    TS(22);
    if (tid == 0) TSG(62);
}

typedef CUresult (*EncodeFn)(CUtensorMap*, CUtensorMapDataType, cuuint32_t, void*, const cuuint64_t*, const cuuint64_t*,
                             const cuuint32_t*, const cuuint32_t*, CUtensorMapInterleave, CUtensorMapSwizzle,
                             CUtensorMapL2promotion, CUtensorMapFloatOOBfill);

void encode(EncodeFn fn, CUtensorMap* m, const void* base, int rank, const cuuint64_t* dims, const cuuint64_t* strides,
            const cuuint32_t* box, CUtensorMapSwizzle sw, CUtensorMapL2promotion promo) {
    cuuint32_t es[3] = {1, 1, 1};
    fn(m, CU_TENSOR_MAP_DATA_TYPE_BFLOAT16, (cuuint32_t)rank, const_cast<void*>(base), dims, strides, box, es,
       CU_TENSOR_MAP_INTERLEAVE_NONE, sw, promo, CU_TENSOR_MAP_FLOAT_OOB_FILL_NONE);
}

}

extern "C" void kernel_launch(void* const* d_in, const int* in_sizes, int n_in, void* d_out, int out_size) {
    (void)in_sizes; (void)n_in; (void)out_size;
    static EncodeFn enc = nullptr;
    if (!enc) {
        void* fn = nullptr;
        cudaDriverEntryPointQueryResult qr;
        cudaGetDriverEntryPoint("cuTensorMapEncodeTiled", &fn, cudaEnableDefault, &qr);
        enc = (EncodeFn)fn;
        cudaFuncSetAttribute(fused_decode_kernel, cudaFuncAttributeMaxDynamicSharedMemorySize, SMEM_BYTES);
    }
    const void* x = d_in[0];
    Maps maps;
    {
        cuuint64_t dims[3] = {64, 262144, 2}; cuuint64_t str[2] = {256, 128}; cuuint32_t box[3] = {64, 128, 2};
        encode(enc, &maps.m[0], d_in[1], 3, dims, str, box, CU_TENSOR_MAP_SWIZZLE_128B, CU_TENSOR_MAP_L2_PROMOTION_L2_256B);
        encode(enc, &maps.m[1], d_in[2], 3, dims, str, box, CU_TENSOR_MAP_SWIZZLE_128B, CU_TENSOR_MAP_L2_PROMOTION_L2_256B);
    }
    {
        cuuint64_t dims[3] = {4096, 512, 1}; cuuint64_t str[2] = {8192, 8192 * 512}; cuuint32_t box[3] = {32, 256, 1};
        encode(enc, &maps.m[2], d_in[3], 3, dims, str, box, CU_TENSOR_MAP_SWIZZLE_64B, CU_TENSOR_MAP_L2_PROMOTION_L2_128B);
    }
    {
        cuuint64_t dims[3] = {64, 4096, 8}; cuuint64_t str[2] = {1024, 128}; cuuint32_t box[3] = {64, 128, 2};
        encode(enc, &maps.m[3], d_in[4], 3, dims, str, box, CU_TENSOR_MAP_SWIZZLE_128B, CU_TENSOR_MAP_L2_PROMOTION_L2_256B);
    }
    {
        cuuint64_t dims[3] = {1792, 512, 1}; cuuint64_t str[2] = {3584, 3584 * 512}; cuuint32_t box[3] = {16, 256, 1};
        encode(enc, &maps.m[4], d_in[6], 3, dims, str, box, CU_TENSOR_MAP_SWIZZLE_32B, CU_TENSOR_MAP_L2_PROMOTION_L2_128B);
        encode(enc, &maps.m[5], d_in[7], 3, dims, str, box, CU_TENSOR_MAP_SWIZZLE_32B, CU_TENSOR_MAP_L2_PROMOTION_L2_128B);
    }
    {
        cuuint64_t dims[3] = {64, 1792, 8}; cuuint64_t str[2] = {1024, 128}; cuuint32_t box[3] = {64, 16, 4};
        encode(enc, &maps.m[6], d_in[8], 3, dims, str, box, CU_TENSOR_MAP_SWIZZLE_128B, CU_TENSOR_MAP_L2_PROMOTION_L2_256B);
    }
    fused_decode_kernel<<<NCTA, NTHREADS, SMEM_BYTES, cudaStreamPerThread>>>(maps, (const __nv_bfloat16*)x, (__nv_bfloat16*)d_out);
}
```

```cpp
#include <cuda_runtime.h>
#include <cuda_bf16.h>
#include <cuda.h>
#include <stdint.h>

namespace {

constexpr int NCTA      = 128;
constexpr int NTHREADS  = 320;
constexpr int SLOT      = 32768;
constexpr int NSLOT     = 6;
constexpr int NTILE     = 16;
constexpr int NFFN      = 112;
constexpr int DOWN0     = 64;
#define DEPTH_LO 2
#define DEPTH_HI 3
#define LEAD_THR8 4
#define GATE_MARGIN 0
#define WDEPTH 2
#define SEQ_WO 33
constexpr int SEQ_K15 = (SEQ_WO == 31) ? 32 : 31;
constexpr int NSEQ    = 34;
constexpr int SLOT_WGU = 4, SLOT_WD = 5, SLOT_ACT = 0;
#define DLY2 0
#define DLY3 0
#define DLY4 0
#define RESET_TILE 8
constexpr uint32_t SENT = 0xFFFFFFFFu;

constexpr int OFF_XN   = NSLOT * SLOT;
constexpr int XN_PITCH = 1040;
constexpr int OFF_QS   = OFF_XN + 4 * XN_PITCH;
constexpr int QS_PITCH = 272;
constexpr int OFF_P    = OFF_QS + 4 * QS_PITCH;
constexpr int OFF_RED  = OFF_P + 4 * QS_PITCH;
constexpr int OFF_MX   = OFF_RED + 4096;
constexpr int OFF_L    = OFF_MX + 64;
constexpr int OFF_ACT  = OFF_L + 128;
constexpr int ACT_PITCH = 3600;
constexpr int OFF_RED2 = OFF_ACT + 128;
constexpr int OFF_CS   = OFF_RED2 + 1024;
constexpr int OFF_ST   = OFF_CS + 512;
constexpr int OFF_BAR  = OFF_ST + 32;
constexpr int OFF_VAR  = OFF_BAR + 176;
constexpr int SMEM_USED = OFF_VAR + 64;
constexpr int SMEM_BYTES = SMEM_USED + 1024;
static_assert(OFF_RED % 16 == 0 && OFF_MX % 16 == 0 && OFF_ST % 8 == 0 && OFF_BAR % 8 == 0, "alignment");

__device__ uint2    g_q[4 * 2048];
__device__ float    g_partO[32 * 4 * 4 * 128];
__device__ float2   g_ml[32 * 4 * 4];
__device__ float    g_ypart[4 * 32 * 32 * 16];
__device__ uint16_t g_h[4 * 512];
__device__ uint16_t g_act[4 * 1792];
__device__ unsigned g_cnt0, g_cnt1, g_prog;
#define TS(i)
#define TSX(i, cond)
#define TSG(i)
#define TSD(i, cond, dep)

__device__ __forceinline__ uint32_t smem_u32(const void* p) { return (uint32_t)__cvta_generic_to_shared(p); }
__device__ __forceinline__ void mbar_init(uint32_t bar, uint32_t cnt) {
    asm volatile("mbarrier.init.shared::cta.b64 [%0], %1;" ::"r"(bar), "r"(cnt) : "memory");
}
__device__ __forceinline__ void mbar_expect_tx(uint32_t bar, uint32_t bytes) {
    asm volatile("mbarrier.arrive.expect_tx.shared::cta.b64 _, [%0], %1;" ::"r"(bar), "r"(bytes) : "memory");
}
__device__ __forceinline__ void mbar_arrive(uint32_t bar) {
    asm volatile("mbarrier.arrive.shared::cta.b64 _, [%0];" ::"r"(bar) : "memory");
}
__device__ __forceinline__ bool mbar_try(uint32_t bar, uint32_t parity) {
    uint32_t ok;
    asm volatile("{\n.reg .pred p;\nmbarrier.try_wait.parity.shared::cta.b64 p, [%1], %2;\nselp.u32 %0, 1, 0, p;\n}"
                 : "=r"(ok) : "r"(bar), "r"(parity) : "memory");
    return ok != 0;
}
constexpr uint32_t SPIN_LIMIT = 1u << 22;
__device__ __forceinline__ void mbar_wait(uint32_t bar, uint32_t parity) {
    uint32_t it = 0;
    while (!mbar_try(bar, parity)) { if (++it > SPIN_LIMIT) __trap(); }
}
__device__ __forceinline__ void tma3d(uint32_t dst, const CUtensorMap* m, int c0, int c1, int c2, uint32_t bar, uint64_t pol) {
    asm volatile("cp.async.bulk.tensor.3d.shared::cluster.global.mbarrier::complete_tx::bytes.L2::cache_hint [%0], [%1, {%3, %4, %5}], [%2], %6;"
                 ::"r"(dst), "l"(m), "r"(bar), "r"(c0), "r"(c1), "r"(c2), "l"(pol) : "memory");
}
__device__ __forceinline__ void tma3d_prefetch(const CUtensorMap* m, int c0, int c1, int c2) {
    asm volatile("cp.async.bulk.prefetch.tensor.3d.L2.global.tile [%0, {%1, %2, %3}];" ::"l"(m), "r"(c0), "r"(c1), "r"(c2) : "memory");
}
__device__ __forceinline__ void ldsm4(uint32_t (&r)[4], uint32_t addr) {
    asm volatile("ldmatrix.sync.aligned.m8n8.x4.shared.b16 {%0,%1,%2,%3}, [%4];"
                 : "=r"(r[0]), "=r"(r[1]), "=r"(r[2]), "=r"(r[3]) : "r"(addr) : "memory");
}
__device__ __forceinline__ void ldsm4t(uint32_t (&r)[4], uint32_t addr) {
    asm volatile("ldmatrix.sync.aligned.m8n8.x4.trans.shared.b16 {%0,%1,%2,%3}, [%4];"
                 : "=r"(r[0]), "=r"(r[1]), "=r"(r[2]), "=r"(r[3]) : "r"(addr) : "memory");
}
__device__ __forceinline__ void mma16816(float (&c)[4], const uint32_t (&a)[4], uint32_t b0, uint32_t b1) {
    asm volatile("mma.sync.aligned.m16n8k16.row.col.f32.bf16.bf16.f32 {%0,%1,%2,%3}, {%4,%5,%6,%7}, {%8,%9}, {%0,%1,%2,%3};"
                 : "+f"(c[0]), "+f"(c[1]), "+f"(c[2]), "+f"(c[3])
                 : "r"(a[0]), "r"(a[1]), "r"(a[2]), "r"(a[3]), "r"(b0), "r"(b1));
}
__device__ __forceinline__ void cbar() { asm volatile("bar.sync 1, 256;" ::: "memory"); }
__device__ __forceinline__ void bar_sync(int id, int n) { asm volatile("bar.sync %0, %1;" ::"r"(id), "r"(n) : "memory"); }
__device__ __forceinline__ void bar_arrive(int id, int n) { asm volatile("bar.arrive %0, %1;" ::"r"(id), "r"(n) : "memory"); }
__device__ __forceinline__ uint4 ld_poll4(const void* p) {
    uint4 v;
    asm volatile("ld.relaxed.gpu.global.v4.u32 {%0,%1,%2,%3}, [%4];" : "=r"(v.x), "=r"(v.y), "=r"(v.z), "=r"(v.w) : "l"(p) : "memory");
    return v;
}
__device__ __forceinline__ uint2 ld_poll2(const void* p) {
    uint2 v;
    asm volatile("ld.relaxed.gpu.global.v2.u32 {%0,%1}, [%2];" : "=r"(v.x), "=r"(v.y) : "l"(p) : "memory");
    return v;
}
__device__ __forceinline__ void st_rel32(void* p, uint32_t v) { asm volatile("st.relaxed.gpu.global.u32 [%0], %1;" ::"l"(p), "r"(v) : "memory"); }
__device__ __forceinline__ void st_rel16(void* p, uint16_t v) { asm volatile("st.relaxed.gpu.global.u16 [%0], %1;" ::"l"(p), "h"(v) : "memory"); }
__device__ __forceinline__ void st_rel64(void* p, uint32_t a, uint32_t b) { asm volatile("st.relaxed.gpu.global.v2.u32 [%0], {%1,%2};" ::"l"(p), "r"(a), "r"(b) : "memory"); }
__device__ __forceinline__ void st_rel128(void* p, uint32_t v) { asm volatile("st.relaxed.gpu.global.v4.u32 [%0], {%1,%1,%1,%1};" ::"l"(p), "r"(v) : "memory"); }
__device__ __forceinline__ uint32_t umax4(const uint4& v) { return max(max(v.x, v.y), max(v.z, v.w)); }
template <class T> __device__ __forceinline__ void pin(T*& p) { asm volatile("" : "+l"(p)); }
__device__ __forceinline__ bool valid8h(const uint4& v) {
    return (__vcmpeq2(v.x, SENT) | __vcmpeq2(v.y, SENT) | __vcmpeq2(v.z, SENT) | __vcmpeq2(v.w, SENT)) == 0;
}
struct Spin {
    uint32_t it = 0;
    __device__ __forceinline__ void tick() { if (++it > SPIN_LIMIT) __trap(); }
};
__device__ __forceinline__ uint32_t pack_bf16(float lo, float hi) {
    uint32_t r; asm("cvt.rn.bf16x2.f32 %0, %1, %2;" : "=r"(r) : "f"(hi), "f"(lo)); return r;
}
__device__ __forceinline__ void delay_cycles(int n) { if (n > 0) { const long long t0 = clock64(); while (clock64() - t0 < n) {} } }
__device__ __forceinline__ float bf16r(float x) { return __uint_as_float(pack_bf16(0.f, x) & 0xFFFF0000u); }
__device__ __forceinline__ float bf_lo(uint32_t v) { return __uint_as_float(v << 16); }
__device__ __forceinline__ float bf_hi(uint32_t v) { return __uint_as_float(v & 0xFFFF0000u); }
__device__ __forceinline__ uint32_t hmax2(uint32_t a, uint32_t b) {
    uint32_t r; asm("max.bf16x2 %0, %1, %2;" : "=r"(r) : "r"(a), "r"(b)); return r;
}
__device__ __forceinline__ float ex2(float x) { float r; asm("ex2.approx.ftz.f32 %0, %1;" : "=f"(r) : "f"(x)); return r; }

__device__ __forceinline__ float2 ln_stats(const uint4& a, const uint4& b, float (&v)[16]) {
    v[0] = bf_lo(a.x); v[1] = bf_hi(a.x); v[2] = bf_lo(a.y); v[3] = bf_hi(a.y);
    v[4] = bf_lo(a.z); v[5] = bf_hi(a.z); v[6] = bf_lo(a.w); v[7] = bf_hi(a.w);
    v[8] = bf_lo(b.x); v[9] = bf_hi(b.x); v[10] = bf_lo(b.y); v[11] = bf_hi(b.y);
    v[12] = bf_lo(b.z); v[13] = bf_hi(b.z); v[14] = bf_lo(b.w); v[15] = bf_hi(b.w);
    const float shift = __shfl_sync(0xffffffffu, v[0], 0);
    float s = 0.f, ss = 0.f;
#pragma unroll
    for (int i = 0; i < 16; i++) { float d = v[i] - shift; s += d; ss = fmaf(d, d, ss); }
#pragma unroll
    for (int o = 16; o > 0; o >>= 1) { s += __shfl_xor_sync(0xffffffffu, s, o); ss += __shfl_xor_sync(0xffffffffu, ss, o); }
    const float md = s * (1.0f / 512.0f);
    const float var = fmaxf(ss * (1.0f / 512.0f) - md * md, 0.f);
    const float m = bf16r(shift + md);
    const float sd = bf16r(sqrtf(bf16r(bf16r(var) + 1e-5f)));
    return make_float2(m, 1.0f / sd);
}

struct Maps { CUtensorMap m[7]; };

__global__ void __launch_bounds__(NTHREADS, 1)
fused_decode_kernel(const __grid_constant__ Maps maps,
                    const __nv_bfloat16* __restrict__ x, __nv_bfloat16* __restrict__ out)
{
    extern __shared__ __align__(1024) unsigned char smem_raw[];
    unsigned char* smem = smem_raw + ((1024u - (smem_u32(smem_raw) & 1023u)) & 1023u);
    const uint32_t sbase = smem_u32(smem);
    const uint32_t bar_full = sbase + OFF_BAR, bar_empty = sbase + OFF_BAR + 48, bar_ready = sbase + OFF_BAR + 96, bar_w = sbase + OFF_BAR + 104;
    volatile unsigned* vars = reinterpret_cast<volatile unsigned*>(smem + OFF_VAR);
    const int tid = threadIdx.x, warp = tid >> 5, lane = tid & 31;
    const int cta = blockIdx.x;

    if (tid == 0) TSG(0);
    if (tid == 256) {
        for (int i = 0; i < NSLOT; i++) { mbar_init(bar_full + 8 * i, 1); mbar_init(bar_empty + 8 * i, 8); }
        mbar_init(bar_ready, 1);
        for (int i = 0; i < 8; i++) mbar_init(bar_w + 8 * i, 1);
        vars[1] = 0; vars[2] = 0;
        asm volatile("fence.mbarrier_init.release.cluster;" ::: "memory");
    }
    __syncthreads();

    if (warp == 8) {
        if (lane == 0) {
            uint64_t pol_first, pol_norm;
            asm volatile("createpolicy.fractional.L2::evict_first.b64 %0, 1.0;" : "=l"(pol_first));
            asm volatile("createpolicy.fractional.L2::evict_normal.b64 %0, 1.0;" : "=l"(pol_norm));
            const int key0 = cta * (NTILE * 128);
            int arrived = 0;
            unsigned gbase = 0, grel = 0;
            int nkv = 0;
            for (int i = 0; i < NSEQ; i++) {
                const int slot = i % NSLOT;
                const bool is_w = (i == 0) || (i == SEQ_WO);
                if (i >= NSLOT) mbar_wait(bar_empty + 8 * slot, ((i / NSLOT) - 1) & 1);
                const int lead8 = (nkv * NCTA - (int)grel) / (NCTA / 8);
                const int d = (i > 2 && lead8 > LEAD_THR8) ? DEPTH_LO : DEPTH_HI;
                while (arrived < i - d + 1) { mbar_wait(bar_full + 8 * (arrived % NSLOT), (arrived / NSLOT) & 1); arrived++; }
                const uint32_t dst = sbase + slot * SLOT, fb = bar_full + 8 * slot;
                int mi, c0 = 0, c1 = 0, c2 = 0, nbox = 1;
                if (i == 0)            { mi = 2; c0 = cta * 32; nbox = 2; }
                else if (i == SEQ_WO)  { mi = 3; c1 = (cta >> 2) * 128; c2 = (cta & 3) * 2; }
                else                   { mi = nkv & 1; c1 = key0 + (nkv >> 1) * 128; }
                mbar_expect_tx(fb, 32768);
                for (int j = 0; j < nbox; j++) tma3d(dst + j * 16384, &maps.m[mi], c0, c1 + j * 256, c2, fb, is_w ? pol_norm : pol_first);
                if (!is_w) {
                    if (nkv < 31) {
                        const unsigned g = atomicAdd(&g_prog, 1u);
                        if (nkv == 0) gbase = g & ~(unsigned)(NCTA * 32 - 1);
                        grel = g - gbase;
                    } else {
                        asm volatile("red.relaxed.gpu.global.add.u32 [%0], 1;" ::"l"(&g_prog) : "memory");
                    }
                    nkv++;
                }
            }
            {
                mbar_wait(bar_empty + 8 * SLOT_WGU, (34 / NSLOT - 1) & 1);
                mbar_wait(bar_empty + 8 * SLOT_WD, (35 / NSLOT - 1) & 1);
                if ((int)grel < NCTA * 32 - GATE_MARGIN) {
                    Spin sp; unsigned v;
                    while (true) {
                        asm volatile("ld.relaxed.gpu.global.u32 %0, [%1];" : "=r"(v) : "l"(&g_prog) : "memory");
                        if ((int)(v - gbase) >= NCTA * 32 - GATE_MARGIN) break;
                        sp.tick(); __nanosleep(64);
                    }
                }
                TSX(26, true);
                const int k0 = (cta < NFFN) ? 0 : 4, k1 = (cta >= DOWN0) ? 8 : 4;
                for (int k = k0; k < k1; k++) {
                    if (k - k0 >= WDEPTH) mbar_wait(bar_w + 8 * (k - WDEPTH), 0);
                    const uint32_t wbar = bar_w + 8 * k;
                    if (k < 4) {
                        mbar_expect_tx(wbar, 8192);
                        tma3d(sbase + SLOT_WGU * SLOT + k * 8192, &maps.m[4 + (k >> 1)], cta * 16, (k & 1) * 256, 0, wbar, pol_norm);
                    } else {
                        const int r = (k - 4) * 512;
                        mbar_expect_tx(wbar, k < 7 ? 8192 : 4096);
                        tma3d(sbase + SLOT_WD * SLOT + r * 16, &maps.m[6], (cta - DOWN0) * 8, r, 0, wbar, pol_norm);
                        if (k < 7) tma3d(sbase + SLOT_WD * SLOT + (r + 256) * 16, &maps.m[6], (cta - DOWN0) * 8, r + 256, 0, wbar, pol_norm);
                    }
                }
            }
            TSX(20, true);
        }
        return;
    }

    const int pair = cta >> 2, split = cta & 3;

    if (warp == 9) {
        Spin sp;
        while (vars[1] < RESET_TILE) { sp.tick(); __nanosleep(256); }
        const unsigned epoch = vars[0];
#pragma unroll 1
        for (int u = lane; u < 128; u += 32) {
            st_rel128(&g_partO[((pair * 4 + (u >> 5)) * 4 + split) * 128 + (u & 31) * 4], SENT);
            const int seg = u >> 2;
            st_rel128(&g_ypart[(((seg >> 3) * 32 + (cta & 3) * 8 + (seg & 7)) * 32 + (cta >> 2)) * 16 + (u & 3) * 4], SENT);
        }
        if (lane < 4) st_rel64(&g_ml[(pair * 4 + lane) * 4 + split], SENT, SENT);
        if (lane < 2) st_rel128(&g_h[(cta >> 5) * 512 + (cta & 31) * 16 + lane * 8], SENT);
        if (cta < NFFN && lane < 8) st_rel128(&g_act[(lane >> 1) * 1792 + cta * 16 + (lane & 1) * 8], SENT);
        __threadfence();
        __syncwarp();
        if (lane == 0) {
            atomicAdd(&g_cnt1, 1u);
            unsigned v; Spin sp2;
            while (true) {
                asm volatile("ld.acquire.gpu.global.u32 %0, [%1];" : "=r"(v) : "l"(&g_cnt1) : "memory");
                if ((int)(v - (epoch + 1) * NCTA) >= 0) break;
                sp2.tick(); __nanosleep(128);
            }
            mbar_arrive(bar_ready);
        }
        TSX(24, lane == 0);
        return;
    }

    const int r8 = lane >> 2, q4 = lane & 3;
    const int hp = q4 & 1, kh = q4 >> 1;
    constexpr float LOG2E = 1.4426950408889634f;
    const int bq = pair >> 3, gq = pair & 7;

    if (tid == 0) vars[0] = atomicAdd(&g_cnt0, 1u) >> 7;
    if (warp == 7) st_rel128(&g_q[(lane >> 3) * 2048 + cta * 16 + (lane & 7) * 2], 0u);
    float xres = 0.f;
    if (warp == 0) xres = __bfloat162float(x[(cta >> 5) * 512 + (cta & 31) * 16 + (lane >> 1)]);

    if (warp < 4) {
        const uint4* xr = reinterpret_cast<const uint4*>(x + warp * 512);
        const uint4 a = __ldg(xr + lane), b = __ldg(xr + 32 + lane);
        float v[16];
        const float2 st = ln_stats(a, b, v);
        uint32_t o[8];
#pragma unroll
        for (int i = 0; i < 8; i++) o[i] = pack_bf16(bf16r(v[2 * i] - st.x) * st.y, bf16r(v[2 * i + 1] - st.x) * st.y);
        unsigned char* row = smem + OFF_XN + warp * XN_PITCH;
        *reinterpret_cast<uint4*>(row + lane * 16) = make_uint4(o[0], o[1], o[2], o[3]);
        *reinterpret_cast<uint4*>(row + 512 + lane * 16) = make_uint4(o[4], o[5], o[6], o[7]);
    }
    cbar();
    const uint32_t tag = vars[0] + 1;

    {
        uint32_t bfr[4][2];
        {
            uint32_t t4[4];
#pragma unroll
            for (int u = 0; u < 2; u++) {
                ldsm4(t4, sbase + OFF_XN + (lane & 3) * XN_PITCH + (8 * warp + 4 * u + (lane >> 3)) * 16);
                bfr[2 * u][0] = t4[0]; bfr[2 * u][1] = t4[1]; bfr[2 * u + 1][0] = t4[2]; bfr[2 * u + 1][1] = t4[3];
            }
        }
        mbar_wait(bar_full + 0, 0);
        TS(2);
        float acc[2][4] = {};
#pragma unroll
        for (int ks = 0; ks < 4; ks++) {
            const int k = 64 * warp + 16 * ks + (lane & 7) + (lane >> 4) * 8;
#pragma unroll
            for (int mt = 0; mt < 2; mt++) {
                uint32_t a[4];
                const int chunk = 2 * mt + ((lane >> 3) & 1);
                ldsm4t(a, sbase + k * 64 + ((chunk ^ ((k >> 1) & 3)) << 4));
                mma16816(acc[mt], a, bfr[ks][0], bfr[ks][1]);
            }
        }
        __syncwarp();
        if (lane == 0) mbar_arrive(bar_empty + 0);
        float* red = reinterpret_cast<float*>(smem + OFF_RED);
#pragma unroll
        for (int mt = 0; mt < 2; mt++) {
            float2 v = kh ? make_float2(acc[mt][2], acc[mt][3]) : make_float2(acc[mt][0], acc[mt][1]);
            *reinterpret_cast<float2*>(red + ((warp * 2 + mt) * 16 + r8 + 8 * kh) * 4 + 2 * hp) = v;
        }
        cbar();
        if (tid < 64) {
            const int b = tid >> 4, c2 = tid & 15;
            float s0 = 0.f, s1 = 0.f;
            const int c0 = 2 * c2, c1 = 2 * c2 + 1;
#pragma unroll
            for (int ww = 0; ww < 8; ww++) {
                s0 += red[((ww * 2 + (c0 >> 4)) * 16 + (c0 & 15)) * 4 + b];
                s1 += red[((ww * 2 + (c1 >> 4)) * 16 + (c1 & 15)) * 4 + b];
            }
            st_rel64(&g_q[b * 2048 + cta * 16 + c2], pack_bf16(s0, s1), tag);
        }
        {
            const uint2* src = &g_q[bq * 2048 + gq * 256 + tid];
            uint2 v;
            Spin sp;
            while (true) { v = ld_poll2(src); if (__all_sync(0xffffffffu, v.y == tag)) break; sp.tick(); }
            *reinterpret_cast<uint32_t*>(smem + OFF_QS + (tid >> 6) * QS_PITCH + (tid & 63) * 4) = v.x;
        }
        cbar();
    }
    TS(3);
    uint32_t qf[8][2];
    {
        uint32_t t4[4];
#pragma unroll
        for (int u = 0; u < 4; u++) {
            ldsm4(t4, sbase + OFF_QS + (lane & 3) * QS_PITCH + (4 * u + (lane >> 3)) * 16);
            qf[2 * u][0] = t4[0]; qf[2 * u][1] = t4[1]; qf[2 * u + 1][0] = t4[2]; qf[2 * u + 1][1] = t4[3];
        }
    }

    const uint32_t voff = (warp >> 2) * 16384 + ((lane & 7) + (lane >> 4) * 8) * 128 +
                          ((((2 * warp + ((lane >> 3) & 1)) & 7) ^ (lane & 7)) << 4);
    const uint32_t poff = sbase + OFF_P + (lane & 3) * QS_PITCH + (lane >> 3) * 16;
    const uint32_t koff = (16 * warp + (lane & 7) + ((lane >> 3) & 1) * 8) * 128;
    const uint32_t kx = lane & 7, kc = lane >> 4;
    constexpr float SCALE = 0.08838834764831845f;
    uint32_t* mxbuf = reinterpret_cast<uint32_t*>(smem + OFF_MX);
    uint32_t M2 = 0xFF80FF80u;
    float l0 = 0.f, l1 = 0.f;
    float oacc[2][4] = {};
    int slot = 1; uint32_t ph = 0;

    for (int t = 0;; t++) {
        mbar_wait(bar_full + 8 * slot, ph);
        float sa[4] = {}, sb[4] = {};
        {
            const uint32_t kb = sbase + slot * SLOT + koff;
#pragma unroll
            for (int ks = 0; ks < 8; ks++) {
                uint32_t a[4];
                ldsm4(a, kb + (ks >> 2) * 16384 + (((2 * (ks & 3) + kc) ^ kx) << 4));
                if (ks & 1) mma16816(sb, a, qf[ks][0], qf[ks][1]); else mma16816(sa, a, qf[ks][0], qf[ks][1]);
            }
        }
        __syncwarp();
        if (lane == 0) mbar_arrive(bar_empty + 8 * slot);
        if (++slot == NSLOT) { slot = 0; ph ^= 1; }

        const float r0 = kh ? sa[2] + sb[2] : sa[0] + sb[0];
        const float r1 = kh ? sa[3] + sb[3] : sa[1] + sb[1];
        uint32_t sp = pack_bf16(r0, r1);
        sp = pack_bf16(bf_lo(sp) * SCALE, bf_hi(sp) * SCALE);
        uint32_t mx = sp;
#pragma unroll
        for (int o = 2; o <= 16; o <<= 1) mx = hmax2(mx, __shfl_xor_sync(0xffffffffu, mx, o));
        if (lane < 2) mxbuf[lane * 8 + warp] = mx;
        if (tid == 0) vars[1] = t + 1;
        TS(40 + t);
        cbar();
        {
            const uint4 m0 = *reinterpret_cast<const uint4*>(mxbuf + hp * 8), m1 = *reinterpret_cast<const uint4*>(mxbuf + hp * 8 + 4);
            uint32_t mt = hmax2(hmax2(hmax2(m0.x, m0.y), hmax2(m0.z, m0.w)), hmax2(hmax2(m1.x, m1.y), hmax2(m1.z, m1.w)));
            const uint32_t Mn = hmax2(M2, mt);
            const float a0 = ex2((bf_lo(M2) - bf_lo(Mn)) * LOG2E), a1 = ex2((bf_hi(M2) - bf_hi(Mn)) * LOG2E);
            const float p0 = ex2((bf_lo(sp) - bf_lo(Mn)) * LOG2E), p1 = ex2((bf_hi(sp) - bf_hi(Mn)) * LOG2E);
            M2 = Mn;
            l0 = fmaf(l0, a0, p0); l1 = fmaf(l1, a1, p1);
            const uint32_t pp = pack_bf16(p0, p1);
            unsigned char* pd = smem + OFF_P + (2 * hp) * QS_PITCH + (16 * warp + r8 + 8 * kh) * 2;
            *reinterpret_cast<uint16_t*>(pd) = (uint16_t)(pp & 0xFFFF);
            *reinterpret_cast<uint16_t*>(pd + QS_PITCH) = (uint16_t)(pp >> 16);
#pragma unroll
            for (int c = 0; c < 2; c++) { oacc[c][0] *= a0; oacc[c][1] *= a1; oacc[c][2] *= a0; oacc[c][3] *= a1; }
        }
        if (t == NTILE - 1) break;
        cbar();
        uint32_t pb[8][2];
        {
            uint32_t t4[4];
#pragma unroll
            for (int u = 0; u < 4; u++) {
                ldsm4(t4, poff + u * 64);
                pb[2 * u][0] = t4[0]; pb[2 * u][1] = t4[1]; pb[2 * u + 1][0] = t4[2]; pb[2 * u + 1][1] = t4[3];
            }
        }
        mbar_wait(bar_full + 8 * slot, ph);
        {
            const uint32_t vb = sbase + slot * SLOT + voff;
#pragma unroll
            for (int ks = 0; ks < 8; ks++) {
                uint32_t a[4];
                ldsm4t(a, vb + ks * 2048);
                mma16816(oacc[ks & 1], a, pb[ks][0], pb[ks][1]);
            }
        }
        __syncwarp();
        if (lane == 0) mbar_arrive(bar_empty + 8 * slot);
        if (++slot == NSLOT) { slot = 0; ph ^= 1; }
        if (SEQ_WO == 31 && t == NTILE - 2) { if (++slot == NSLOT) { slot = 0; ph ^= 1; } }
    }

    const int head = cta >> 2;
    float* p_partO = &g_partO[((pair * 4 + 2 * hp) * 4 + split) * 128 + 16 * warp + r8 + 8 * kh];
    pin(p_partO);

    {
        float s0 = l0, s1 = l1;
#pragma unroll
        for (int o = 2; o <= 16; o <<= 1) { s0 += __shfl_xor_sync(0xffffffffu, s0, o); s1 += __shfl_xor_sync(0xffffffffu, s1, o); }
        if (lane < 2) *reinterpret_cast<float2*>(smem + OFF_L + warp * 16 + lane * 8) = make_float2(s0, s1);
        mbar_wait(bar_ready, 0);
        cbar();
        if (warp == 0) {
            const uint32_t other = __shfl_sync(0xffffffffu, M2, lane >> 1);
            float l = 0.f;
#pragma unroll
            for (int ww = 0; ww < 8; ww++) l += *reinterpret_cast<const float*>(smem + OFF_L + ww * 16 + (lane & 3) * 4);
            const float m = (lane & 1) ? bf_hi(other) : bf_lo(other);
            if (lane < 4) st_rel64(&g_ml[(pair * 4 + lane) * 4 + split], __float_as_uint(m), __float_as_uint(l));
        }
        uint32_t pb[8][2];
        {
            uint32_t t4[4];
#pragma unroll
            for (int u = 0; u < 4; u++) {
                ldsm4(t4, poff + u * 64);
                pb[2 * u][0] = t4[0]; pb[2 * u][1] = t4[1]; pb[2 * u + 1][0] = t4[2]; pb[2 * u + 1][1] = t4[3];
            }
        }
        float o2[2][4] = {};
        mbar_wait(bar_full + 8 * slot, ph);
        {
            const uint32_t vb = sbase + slot * SLOT + voff;
            uint32_t a[8][4];
#pragma unroll
            for (int ks = 0; ks < 8; ks++) ldsm4t(a[ks], vb + ks * 2048);
#pragma unroll
            for (int ks = 0; ks < 8; ks++) mma16816((ks & 2) ? o2[ks & 1] : oacc[ks & 1], a[ks], pb[ks][0], pb[ks][1]);
        }
        const float v0 = kh ? (oacc[0][2] + oacc[1][2]) + (o2[0][2] + o2[1][2]) : (oacc[0][0] + oacc[1][0]) + (o2[0][0] + o2[1][0]);
        const float v1 = kh ? (oacc[0][3] + oacc[1][3]) + (o2[0][3] + o2[1][3]) : (oacc[0][1] + oacc[1][1]) + (o2[0][1] + o2[1][1]);
        st_rel32(p_partO, __float_as_uint(v0));
        st_rel32(p_partO + 512, __float_as_uint(v1));
        TS(4);
    }

    if (warp < 4) {
        {
            const int ph_idx = (warp * 8 + (head >> 2)) * 4 + (head & 3);
            const float* po = &g_partO[ph_idx * 512 + lane * 4];
            const float* pm = reinterpret_cast<const float*>(&g_ml[ph_idx * 4]);
            uint4 o0, o1, o2, o3, ma, mb;
            Spin sp;
            while (true) {
                o0 = ld_poll4(po); o1 = ld_poll4(po + 128); o2 = ld_poll4(po + 256); o3 = ld_poll4(po + 384);
                ma = ld_poll4(pm); mb = ld_poll4(pm + 4);
                const uint32_t mxv = max(max(max(umax4(o0), umax4(o1)), max(umax4(o2), umax4(o3))), max(umax4(ma), umax4(mb)));
                if (__all_sync(0xffffffffu, mxv != SENT)) break;
                sp.tick();
            }
            TS(6);
            const float m0 = __uint_as_float(ma.x), m1 = __uint_as_float(ma.z), m2 = __uint_as_float(mb.x), m3 = __uint_as_float(mb.z);
            const float M = fmaxf(fmaxf(m0, m1), fmaxf(m2, m3));
            float w0 = ex2((m0 - M) * LOG2E), w1 = ex2((m1 - M) * LOG2E), w2 = ex2((m2 - M) * LOG2E), w3 = ex2((m3 - M) * LOG2E);
            const float L = w0 * __uint_as_float(ma.y) + w1 * __uint_as_float(ma.w) + w2 * __uint_as_float(mb.y) + w3 * __uint_as_float(mb.w);
            const float inv = __fdividef(1.0f, L);
            const float e0 = (w0 * __uint_as_float(o0.x) + w1 * __uint_as_float(o1.x) + w2 * __uint_as_float(o2.x) + w3 * __uint_as_float(o3.x)) * inv;
            const float e1 = (w0 * __uint_as_float(o0.y) + w1 * __uint_as_float(o1.y) + w2 * __uint_as_float(o2.y) + w3 * __uint_as_float(o3.y)) * inv;
            const float e2 = (w0 * __uint_as_float(o0.z) + w1 * __uint_as_float(o1.z) + w2 * __uint_as_float(o2.z) + w3 * __uint_as_float(o3.z)) * inv;
            const float e3 = (w0 * __uint_as_float(o0.w) + w1 * __uint_as_float(o1.w) + w2 * __uint_as_float(o2.w) + w3 * __uint_as_float(o3.w)) * inv;
            *reinterpret_cast<uint2*>(smem + OFF_QS + warp * QS_PITCH + lane * 8) = make_uint2(pack_bf16(e0, e1), pack_bf16(e2, e3));
            bar_arrive(2, 256);
        }
        if (warp == 0) {
            const float* src = &g_ypart[(cta * 32 + lane) * 16];
            uint16_t* p_h = &g_h[(cta >> 5) * 512 + (cta & 31) * 16 + (lane >> 1)];
            pin(p_h);
            delay_cycles(DLY2);
            uint4 y0, y1, y2, y3;
            Spin sp;
            while (true) {
                y0 = ld_poll4(src); y1 = ld_poll4(src + 4); y2 = ld_poll4(src + 8); y3 = ld_poll4(src + 12);
                if (__all_sync(0xffffffffu, max(max(umax4(y0), umax4(y1)), max(umax4(y2), umax4(y3))) != SENT)) break;
                sp.tick();
            }
            TS(9);
            float v0, v1, v2, v3, v4, v5, v6, v7;
            {
                const bool up = lane & 16;
#define RSTEP(dst, lo, hi, m) { const float _l = __uint_as_float(lo), _h = __uint_as_float(hi); dst = (up ? _h : _l) + __shfl_xor_sync(0xffffffffu, up ? _l : _h, m); }
                RSTEP(v0, y0.x, y2.x, 16) RSTEP(v1, y0.y, y2.y, 16) RSTEP(v2, y0.z, y2.z, 16) RSTEP(v3, y0.w, y2.w, 16)
                RSTEP(v4, y1.x, y3.x, 16) RSTEP(v5, y1.y, y3.y, 16) RSTEP(v6, y1.z, y3.z, 16) RSTEP(v7, y1.w, y3.w, 16)
#undef RSTEP
            }
#define RSTEP(dst, a, b, m) { const bool _u = lane & m; dst = (_u ? b : a) + __shfl_xor_sync(0xffffffffu, _u ? a : b, m); }
            RSTEP(v0, v0, v4, 8) RSTEP(v1, v1, v5, 8) RSTEP(v2, v2, v6, 8) RSTEP(v3, v3, v7, 8)
            RSTEP(v0, v0, v2, 4) RSTEP(v1, v1, v3, 4)
            RSTEP(v0, v0, v1, 2)
#undef RSTEP
            v0 += __shfl_xor_sync(0xffffffffu, v0, 1);
            const float hres = xres + bf16r(v0);
            if (!(lane & 1)) st_rel16(p_h, (uint16_t)(pack_bf16(hres, 0.f) & 0xFFFFu));
            TS(10);
        }
        {
            bar_sync(7, 128);
            const uint4* hr = reinterpret_cast<const uint4*>(g_h + warp * 512);
            delay_cycles(DLY3);
            uint4 a, b;
            Spin sp;
            while (true) {
                a = ld_poll4(hr + lane); b = ld_poll4(hr + 32 + lane);
                if (__all_sync(0xffffffffu, valid8h(a) & valid8h(b))) break;
                sp.tick();
            }
            TS(13);
            unsigned char* row = smem + OFF_XN + warp * XN_PITCH;
            *reinterpret_cast<uint4*>(row + lane * 16) = a;
            *reinterpret_cast<uint4*>(row + 512 + lane * 16) = b;
            if (cta < NFFN) {
                bar_arrive(3, 256);
                float v[16];
                const float2 st = ln_stats(a, b, v);
                if (lane == 0) *reinterpret_cast<float2*>(smem + OFF_ST + warp * 8) = st;
                bar_arrive(4, 256);
                TS(14);
            }
        }
    } else {
        const int m = warp - 4;
        {
            uint32_t af[2][8][4];
            float* p_y = &g_ypart[(((2 * hp) * 32 + (cta & 3) * 8 + 2 * m) * 32 + head) * 16 + r8 + 8 * kh];
            pin(p_y);
            mbar_wait(bar_full + 8 * (SEQ_WO % NSLOT), (SEQ_WO / NSLOT) & 1);
#pragma unroll
            for (int i = 0; i < 2; i++) {
                const int j = 2 * m + i;
                const uint32_t wb = sbase + (SEQ_WO % NSLOT) * SLOT + (j >> 2) * 16384 + ((lane & 7) + (lane >> 4) * 8) * 128 +
                                    ((((2 * j + ((lane >> 3) & 1)) & 7) ^ (lane & 7)) << 4);
#pragma unroll
                for (int ks = 0; ks < 8; ks++) ldsm4t(af[i][ks], wb + ks * 2048);
            }
            TSX(5, tid == 128);
            bar_sync(2, 256);
            TSX(7, tid == 128);
            float acc[2][2][4] = {};
            uint32_t t4[4][4];
#pragma unroll
            for (int u = 0; u < 4; u++) ldsm4(t4[u], sbase + OFF_QS + (lane & 3) * QS_PITCH + (4 * u + (lane >> 3)) * 16);
#pragma unroll
            for (int u = 0; u < 4; u++) {
#pragma unroll
                for (int i = 0; i < 2; i++) {
                    mma16816(acc[i][0], af[i][2 * u], t4[u][0], t4[u][1]);
                    mma16816(acc[i][1], af[i][2 * u + 1], t4[u][2], t4[u][3]);
                }
            }
#pragma unroll
            for (int i = 0; i < 2; i++) {
                const float v0 = kh ? acc[i][0][2] + acc[i][1][2] : acc[i][0][0] + acc[i][1][0];
                const float v1 = kh ? acc[i][0][3] + acc[i][1][3] : acc[i][0][1] + acc[i][1][1];
                st_rel32(p_y + i * 32 * 16, __float_as_uint(v0));
                st_rel32(p_y + i * 32 * 16 + 32 * 32 * 16, __float_as_uint(v1));
            }
            TSX(8, tid == 128);
        }
        if (cta < NFFN) {
            uint32_t gf[8][2][4];
            mbar_wait(bar_w, 0); mbar_wait(bar_w + 8, 0); mbar_wait(bar_w + 16, 0); mbar_wait(bar_w + 24, 0);
#pragma unroll
            for (int ks = 0; ks < 8; ks++) {
                const int k = 128 * m + 16 * ks + (lane & 7) + (lane >> 4) * 8;
                const uint32_t a = sbase + SLOT_WGU * SLOT + k * 32 + ((((lane >> 3) & 1) ^ ((k >> 2) & 1)) << 4);
                ldsm4t(gf[ks][0], a);
                ldsm4t(gf[ks][1], a + 16384);
            }
            TSX(11, tid == 128);
            float sg = 0.f, su = 0.f;
            {
                float cs[2][4] = {};
#pragma unroll
                for (int ks = 0; ks < 8; ks++) { mma16816(cs[0], gf[ks][0], 0x3F803F80u, 0x3F803F80u); mma16816(cs[1], gf[ks][1], 0x3F803F80u, 0x3F803F80u); }
                float* csb = reinterpret_cast<float*>(smem + OFF_CS);
                if (q4 == 0) {
                    csb[(m * 2 + 0) * 16 + r8] = cs[0][0]; csb[(m * 2 + 0) * 16 + r8 + 8] = cs[0][2];
                    csb[(m * 2 + 1) * 16 + r8] = cs[1][0]; csb[(m * 2 + 1) * 16 + r8 + 8] = cs[1][2];
                }
                bar_sync(5, 128);
                const int c = (tid & 63) >> 2;
#pragma unroll
                for (int ww = 0; ww < 4; ww++) { sg += csb[(ww * 2) * 16 + c]; su += csb[(ww * 2 + 1) * 16 + c]; }
            }
            uint16_t* p_act = &g_act[(tid & 3) * 1792 + cta * 16 + ((tid & 63) >> 2)];
            pin(p_act);
            TSX(12, tid == 128);
            bar_sync(3, 256);
            float acc[2][2][4] = {};
            uint32_t t4[4][4];
#pragma unroll
            for (int u = 0; u < 4; u++) ldsm4(t4[u], sbase + OFF_XN + (lane & 3) * XN_PITCH + (16 * m + 4 * u + (lane >> 3)) * 16);
#pragma unroll
            for (int u = 0; u < 4; u++) {
#pragma unroll
                for (int i = 0; i < 2; i++) {
                    mma16816(acc[i][0], gf[2 * u][i], t4[u][0], t4[u][1]);
                    mma16816(acc[i][1], gf[2 * u + 1][i], t4[u][2], t4[u][3]);
                }
            }
            float* red = reinterpret_cast<float*>(smem + OFF_RED);
#pragma unroll
            for (int i = 0; i < 2; i++) {
                const float2 v = kh ? make_float2(acc[i][0][2] + acc[i][1][2], acc[i][0][3] + acc[i][1][3])
                                    : make_float2(acc[i][0][0] + acc[i][1][0], acc[i][0][1] + acc[i][1][1]);
                *reinterpret_cast<float2*>(red + ((m * 2 + i) * 16 + r8 + 8 * kh) * 4 + 2 * hp) = v;
            }
            bar_sync(4, 256);
            TSX(16, tid == 128);
            if (tid < 192) {
                const int c = (tid & 63) >> 2, b = tid & 3;
                const float2 st = *reinterpret_cast<const float2*>(smem + OFF_ST + b * 8);
                float g = 0.f, u = 0.f;
#pragma unroll
                for (int ww = 0; ww < 4; ww++) { g += red[((ww * 2) * 16 + c) * 4 + b]; u += red[((ww * 2 + 1) * 16 + c) * 4 + b]; }
                g = bf16r((g - st.x * sg) * st.y); u = bf16r((u - st.x * su) * st.y);
                const float inner = 0.7978845608028654f * (g + 0.044715f * g * g * g);
                const float th = 1.0f - __fdividef(2.0f, __expf(2.0f * inner) + 1.0f);
                const float ge = bf16r(0.5f * g * (1.0f + th));
                st_rel16(p_act, (uint16_t)(pack_bf16(ge * u, 0.f) & 0xFFFFu));
                TSX(18, tid == 128);
            }
        }
    }
    if (cta >= DOWN0) {
        uint32_t wf[7][4];
        mbar_wait(bar_w + 32, 0); mbar_wait(bar_w + 40, 0); mbar_wait(bar_w + 48, 0); mbar_wait(bar_w + 56, 0);
        {
            const uint32_t wb = sbase + SLOT_WD * SLOT + (224 * warp + lane) * 16;
#pragma unroll
            for (int u = 0; u < 7; u++) ldsm4t(wf[u], wb + u * 512);
        }
        TSX(12, tid == 192);
        {
            const uint16_t* src = g_act + tid * 8;
            unsigned char* dst = smem + SLOT_ACT * SLOT;
            uint4 a0, a1, a2, a3 = make_uint4(0, 0, 0, 0);
            const bool four = tid < 128;
            Spin sp;
            delay_cycles(DLY4);
            while (true) {
                a0 = ld_poll4(src); a1 = ld_poll4(src + 2048); a2 = ld_poll4(src + 4096);
                if (four) a3 = ld_poll4(src + 6144);
                if (__all_sync(0xffffffffu, valid8h(a0) & valid8h(a1) & valid8h(a2) & valid8h(a3))) break;
                sp.tick();
            }
            TS(19);
            int e = tid;
            *reinterpret_cast<uint4*>(dst + (e / 224) * ACT_PITCH + (e % 224) * 16) = a0; e += 256;
            *reinterpret_cast<uint4*>(dst + (e / 224) * ACT_PITCH + (e % 224) * 16) = a1; e += 256;
            *reinterpret_cast<uint4*>(dst + (e / 224) * ACT_PITCH + (e % 224) * 16) = a2; e += 256;
            if (four) *reinterpret_cast<uint4*>(dst + (e / 224) * ACT_PITCH + (e % 224) * 16) = a3;
        }
        cbar();
        float acc[4][4] = {};
        {
            uint32_t t4[7][4];
            const uint32_t ab = sbase + SLOT_ACT * SLOT + (lane & 3) * ACT_PITCH + (28 * warp + (lane >> 3)) * 16;
#pragma unroll
            for (int u = 0; u < 7; u++) ldsm4(t4[u], ab + u * 64);
#pragma unroll
            for (int u = 0; u < 7; u++) {
                const uint32_t fa[4] = {wf[u][0], 0u, wf[u][1], 0u}, fb[4] = {wf[u][2], 0u, wf[u][3], 0u};
                mma16816(acc[(2 * u) & 3], fa, t4[u][0], t4[u][1]);
                mma16816(acc[(2 * u + 1) & 3], fb, t4[u][2], t4[u][3]);
            }
        }
        float* red2 = reinterpret_cast<float*>(smem + OFF_RED2);
        if (q4 < 2)
            *reinterpret_cast<float2*>(red2 + (warp * 8 + r8) * 4 + 2 * q4) =
                make_float2((acc[0][0] + acc[1][0]) + (acc[2][0] + acc[3][0]), (acc[0][1] + acc[1][1]) + (acc[2][1] + acc[3][1]));
        cbar();
        TS(21);
        if (tid < 32) {
            const int col = tid >> 2, b = tid & 3;
            float sum = 0.f;
#pragma unroll
            for (int ww = 0; ww < 8; ww++) sum += red2[(ww * 8 + col) * 4 + b];
            const int c = (cta - DOWN0) * 8 + col;
            const float h = __bfloat162float(*reinterpret_cast<const __nv_bfloat16*>(smem + OFF_XN + b * XN_PITCH + c * 2));
            out[b * 512 + c] = __float2bfloat16_rn(h + bf16r(sum));
        }
    }
    TS(22);
    if (tid == 0) TSG(62);
}

typedef CUresult (*EncodeFn)(CUtensorMap*, CUtensorMapDataType, cuuint32_t, void*, const cuuint64_t*, const cuuint64_t*,
                             const cuuint32_t*, const cuuint32_t*, CUtensorMapInterleave, CUtensorMapSwizzle,
                             CUtensorMapL2promotion, CUtensorMapFloatOOBfill);

void encode(EncodeFn fn, CUtensorMap* m, const void* base, int rank, const cuuint64_t* dims, const cuuint64_t* strides,
            const cuuint32_t* box, CUtensorMapSwizzle sw, CUtensorMapL2promotion promo) {
    cuuint32_t es[3] = {1, 1, 1};
    fn(m, CU_TENSOR_MAP_DATA_TYPE_BFLOAT16, (cuuint32_t)rank, const_cast<void*>(base), dims, strides, box, es,
       CU_TENSOR_MAP_INTERLEAVE_NONE, sw, promo, CU_TENSOR_MAP_FLOAT_OOB_FILL_NONE);
}

}

extern "C" void kernel_launch(void* const* d_in, const int* in_sizes, int n_in, void* d_out, int out_size) {
    (void)in_sizes; (void)n_in; (void)out_size;
    static EncodeFn enc = nullptr;
    if (!enc) {
        void* fn = nullptr;
        cudaDriverEntryPointQueryResult qr;
        cudaGetDriverEntryPoint("cuTensorMapEncodeTiled", &fn, cudaEnableDefault, &qr);
        enc = (EncodeFn)fn;
        cudaFuncSetAttribute(fused_decode_kernel, cudaFuncAttributeMaxDynamicSharedMemorySize, SMEM_BYTES);
    }
    const void* x = d_in[0];
    Maps maps;
    {
        cuuint64_t dims[3] = {64, 262144, 2}; cuuint64_t str[2] = {256, 128}; cuuint32_t box[3] = {64, 128, 2};
        encode(enc, &maps.m[0], d_in[1], 3, dims, str, box, CU_TENSOR_MAP_SWIZZLE_128B, CU_TENSOR_MAP_L2_PROMOTION_L2_256B);
        encode(enc, &maps.m[1], d_in[2], 3, dims, str, box, CU_TENSOR_MAP_SWIZZLE_128B, CU_TENSOR_MAP_L2_PROMOTION_L2_256B);
    }
    {
        cuuint64_t dims[3] = {4096, 512, 1}; cuuint64_t str[2] = {8192, 8192 * 512}; cuuint32_t box[3] = {32, 256, 1};
        encode(enc, &maps.m[2], d_in[3], 3, dims, str, box, CU_TENSOR_MAP_SWIZZLE_64B, CU_TENSOR_MAP_L2_PROMOTION_L2_128B);
    }
    {
        cuuint64_t dims[3] = {64, 4096, 8}; cuuint64_t str[2] = {1024, 128}; cuuint32_t box[3] = {64, 128, 2};
        encode(enc, &maps.m[3], d_in[4], 3, dims, str, box, CU_TENSOR_MAP_SWIZZLE_128B, CU_TENSOR_MAP_L2_PROMOTION_L2_256B);
    }
    {
        cuuint64_t dims[3] = {1792, 512, 1}; cuuint64_t str[2] = {3584, 3584 * 512}; cuuint32_t box[3] = {16, 256, 1};
        encode(enc, &maps.m[4], d_in[6], 3, dims, str, box, CU_TENSOR_MAP_SWIZZLE_32B, CU_TENSOR_MAP_L2_PROMOTION_L2_128B);
        encode(enc, &maps.m[5], d_in[7], 3, dims, str, box, CU_TENSOR_MAP_SWIZZLE_32B, CU_TENSOR_MAP_L2_PROMOTION_L2_128B);
    }
    {
        cuuint64_t dims[3] = {512, 1792, 1}; cuuint64_t str[2] = {1024, 1024 * 1792}; cuuint32_t box[3] = {8, 256, 1};
        encode(enc, &maps.m[6], d_in[8], 3, dims, str, box, CU_TENSOR_MAP_SWIZZLE_NONE, CU_TENSOR_MAP_L2_PROMOTION_L2_128B);
    }
    fused_decode_kernel<<<NCTA, NTHREADS, SMEM_BYTES, cudaStreamPerThread>>>(maps, (const __nv_bfloat16*)x, (__nv_bfloat16*)d_out);
}
```

```cpp
#include <cuda_runtime.h>
#include <cuda_bf16.h>
#include <cuda.h>
#include <stdint.h>

namespace {

constexpr int NCTA      = 128;
constexpr int NTHREADS  = 320;
constexpr int SLOT      = 32768;
constexpr int NSLOT     = 6;
constexpr int NTILE     = 16;
constexpr int NFFN      = 112;
#define DEPTH_LO 2
#define DEPTH_HI 3
#define LEAD_THR8 4
#define GATE_MARGIN 0
#define WDEPTH 2
#define SEQ_WO 33
constexpr int SEQ_K15 = (SEQ_WO == 31) ? 32 : 31;
constexpr int NSEQ    = 34;
constexpr int SLOT_WGU = 4, SLOT_WD = 5;
#define DLY2 0
#define DLY3 0
#define DLY4 0
#define EARLY_PF 2
#define RESET_TILE 8
constexpr uint32_t SENT = 0xFFFFFFFFu;

constexpr int OFF_XN   = NSLOT * SLOT;
constexpr int XN_PITCH = 1040;
constexpr int OFF_QS   = OFF_XN + 4 * XN_PITCH;
constexpr int QS_PITCH = 272;
constexpr int OFF_P    = OFF_QS + 4 * QS_PITCH;
constexpr int OFF_RED  = OFF_P + 4 * QS_PITCH;
constexpr int OFF_MX   = OFF_RED + 4096;
constexpr int OFF_L    = OFF_MX + 64;
constexpr int OFF_ACT  = OFF_L + 128;
constexpr int OFF_RED2 = OFF_ACT + 128;
constexpr int OFF_CS   = OFF_RED2 + 512;
constexpr int OFF_ST   = OFF_CS + 512;
constexpr int OFF_BAR  = OFF_ST + 32;
constexpr int OFF_VAR  = OFF_BAR + 192;
constexpr int SMEM_USED = OFF_VAR + 64;
constexpr int SMEM_BYTES = SMEM_USED + 1024;
static_assert(OFF_RED % 16 == 0 && OFF_MX % 16 == 0 && OFF_ST % 8 == 0 && OFF_BAR % 8 == 0, "alignment");

__device__ uint2    g_q[4 * 2048];
__device__ float    g_partO[32 * 4 * 4 * 128];
__device__ float2   g_ml[32 * 4 * 4];
__device__ float    g_ypart[4 * 32 * 32 * 16];
__device__ uint16_t g_h[4 * 512];
__device__ float    g_dpart[4 * 32 * NFFN * 16];
__device__ unsigned g_cnt0, g_cnt1, g_prog;
#define TS(i)
#define TSX(i, cond)
#define TSG(i)
#define TSD(i, cond, dep)

__device__ __forceinline__ uint32_t smem_u32(const void* p) { return (uint32_t)__cvta_generic_to_shared(p); }
__device__ __forceinline__ void mbar_init(uint32_t bar, uint32_t cnt) {
    asm volatile("mbarrier.init.shared::cta.b64 [%0], %1;" ::"r"(bar), "r"(cnt) : "memory");
}
__device__ __forceinline__ void mbar_expect_tx(uint32_t bar, uint32_t bytes) {
    asm volatile("mbarrier.arrive.expect_tx.shared::cta.b64 _, [%0], %1;" ::"r"(bar), "r"(bytes) : "memory");
}
__device__ __forceinline__ void mbar_arrive(uint32_t bar) {
    asm volatile("mbarrier.arrive.shared::cta.b64 _, [%0];" ::"r"(bar) : "memory");
}
__device__ __forceinline__ bool mbar_try(uint32_t bar, uint32_t parity) {
    uint32_t ok;
    asm volatile("{\n.reg .pred p;\nmbarrier.try_wait.parity.shared::cta.b64 p, [%1], %2;\nselp.u32 %0, 1, 0, p;\n}"
                 : "=r"(ok) : "r"(bar), "r"(parity) : "memory");
    return ok != 0;
}
constexpr uint32_t SPIN_LIMIT = 1u << 22;
__device__ __forceinline__ void mbar_wait(uint32_t bar, uint32_t parity) {
    uint32_t it = 0;
    while (!mbar_try(bar, parity)) { if (++it > SPIN_LIMIT) __trap(); }
}
__device__ __forceinline__ void tma3d(uint32_t dst, const CUtensorMap* m, int c0, int c1, int c2, uint32_t bar, uint64_t pol) {
    asm volatile("cp.async.bulk.tensor.3d.shared::cluster.global.mbarrier::complete_tx::bytes.L2::cache_hint [%0], [%1, {%3, %4, %5}], [%2], %6;"
                 ::"r"(dst), "l"(m), "r"(bar), "r"(c0), "r"(c1), "r"(c2), "l"(pol) : "memory");
}
__device__ __forceinline__ void tma3d_prefetch(const CUtensorMap* m, int c0, int c1, int c2) {
    asm volatile("cp.async.bulk.prefetch.tensor.3d.L2.global.tile [%0, {%1, %2, %3}];" ::"l"(m), "r"(c0), "r"(c1), "r"(c2) : "memory");
}
__device__ __forceinline__ void ldsm4(uint32_t (&r)[4], uint32_t addr) {
    asm volatile("ldmatrix.sync.aligned.m8n8.x4.shared.b16 {%0,%1,%2,%3}, [%4];"
                 : "=r"(r[0]), "=r"(r[1]), "=r"(r[2]), "=r"(r[3]) : "r"(addr) : "memory");
}
__device__ __forceinline__ void ldsm4t(uint32_t (&r)[4], uint32_t addr) {
    asm volatile("ldmatrix.sync.aligned.m8n8.x4.trans.shared.b16 {%0,%1,%2,%3}, [%4];"
                 : "=r"(r[0]), "=r"(r[1]), "=r"(r[2]), "=r"(r[3]) : "r"(addr) : "memory");
}
__device__ __forceinline__ void mma16816(float (&c)[4], const uint32_t (&a)[4], uint32_t b0, uint32_t b1) {
    asm volatile("mma.sync.aligned.m16n8k16.row.col.f32.bf16.bf16.f32 {%0,%1,%2,%3}, {%4,%5,%6,%7}, {%8,%9}, {%0,%1,%2,%3};"
                 : "+f"(c[0]), "+f"(c[1]), "+f"(c[2]), "+f"(c[3])
                 : "r"(a[0]), "r"(a[1]), "r"(a[2]), "r"(a[3]), "r"(b0), "r"(b1));
}
__device__ __forceinline__ void cbar() { asm volatile("bar.sync 1, 256;" ::: "memory"); }
__device__ __forceinline__ void bar_sync(int id, int n) { asm volatile("bar.sync %0, %1;" ::"r"(id), "r"(n) : "memory"); }
__device__ __forceinline__ void bar_arrive(int id, int n) { asm volatile("bar.arrive %0, %1;" ::"r"(id), "r"(n) : "memory"); }
__device__ __forceinline__ uint4 ld_poll4(const void* p) {
    uint4 v;
    asm volatile("ld.relaxed.gpu.global.v4.u32 {%0,%1,%2,%3}, [%4];" : "=r"(v.x), "=r"(v.y), "=r"(v.z), "=r"(v.w) : "l"(p) : "memory");
    return v;
}
__device__ __forceinline__ uint2 ld_poll2(const void* p) {
    uint2 v;
    asm volatile("ld.relaxed.gpu.global.v2.u32 {%0,%1}, [%2];" : "=r"(v.x), "=r"(v.y) : "l"(p) : "memory");
    return v;
}
__device__ __forceinline__ void st_rel32(void* p, uint32_t v) { asm volatile("st.relaxed.gpu.global.u32 [%0], %1;" ::"l"(p), "r"(v) : "memory"); }
__device__ __forceinline__ void st_rel16(void* p, uint16_t v) { asm volatile("st.relaxed.gpu.global.u16 [%0], %1;" ::"l"(p), "h"(v) : "memory"); }
__device__ __forceinline__ void st_rel64(void* p, uint32_t a, uint32_t b) { asm volatile("st.relaxed.gpu.global.v2.u32 [%0], {%1,%2};" ::"l"(p), "r"(a), "r"(b) : "memory"); }
__device__ __forceinline__ void st_rel128(void* p, uint32_t v) { asm volatile("st.relaxed.gpu.global.v4.u32 [%0], {%1,%1,%1,%1};" ::"l"(p), "r"(v) : "memory"); }
__device__ __forceinline__ uint32_t umax4(const uint4& v) { return max(max(v.x, v.y), max(v.z, v.w)); }
template <class T> __device__ __forceinline__ void pin(T*& p) { asm volatile("" : "+l"(p)); }
__device__ __forceinline__ bool valid8h(const uint4& v) {
    return (__vcmpeq2(v.x, SENT) | __vcmpeq2(v.y, SENT) | __vcmpeq2(v.z, SENT) | __vcmpeq2(v.w, SENT)) == 0;
}
struct Spin {
    uint32_t it = 0;
    __device__ __forceinline__ void tick() { if (++it > SPIN_LIMIT) __trap(); }
};
__device__ __forceinline__ uint32_t pack_bf16(float lo, float hi) {
    uint32_t r; asm("cvt.rn.bf16x2.f32 %0, %1, %2;" : "=r"(r) : "f"(hi), "f"(lo)); return r;
}
__device__ __forceinline__ void delay_cycles(int n) { if (n > 0) { const long long t0 = clock64(); while (clock64() - t0 < n) {} } }
__device__ __forceinline__ float bf16r(float x) { return __uint_as_float(pack_bf16(0.f, x) & 0xFFFF0000u); }
__device__ __forceinline__ float bf_lo(uint32_t v) { return __uint_as_float(v << 16); }
__device__ __forceinline__ float bf_hi(uint32_t v) { return __uint_as_float(v & 0xFFFF0000u); }
__device__ __forceinline__ uint32_t hmax2(uint32_t a, uint32_t b) {
    uint32_t r; asm("max.bf16x2 %0, %1, %2;" : "=r"(r) : "r"(a), "r"(b)); return r;
}
__device__ __forceinline__ float ex2(float x) { float r; asm("ex2.approx.ftz.f32 %0, %1;" : "=f"(r) : "f"(x)); return r; }

__device__ __forceinline__ float2 ln_stats(const uint4& a, const uint4& b, float (&v)[16]) {
    v[0] = bf_lo(a.x); v[1] = bf_hi(a.x); v[2] = bf_lo(a.y); v[3] = bf_hi(a.y);
    v[4] = bf_lo(a.z); v[5] = bf_hi(a.z); v[6] = bf_lo(a.w); v[7] = bf_hi(a.w);
    v[8] = bf_lo(b.x); v[9] = bf_hi(b.x); v[10] = bf_lo(b.y); v[11] = bf_hi(b.y);
    v[12] = bf_lo(b.z); v[13] = bf_hi(b.z); v[14] = bf_lo(b.w); v[15] = bf_hi(b.w);
    const float shift = __shfl_sync(0xffffffffu, v[0], 0);
    float s0 = 0.f, s1 = 0.f, s2 = 0.f, s3 = 0.f, q0 = 0.f, q1 = 0.f, q2 = 0.f, q3 = 0.f;
#pragma unroll
    for (int i = 0; i < 16; i += 4) {
        const float d0 = v[i] - shift, d1 = v[i + 1] - shift, d2 = v[i + 2] - shift, d3 = v[i + 3] - shift;
        s0 += d0; s1 += d1; s2 += d2; s3 += d3;
        q0 = fmaf(d0, d0, q0); q1 = fmaf(d1, d1, q1); q2 = fmaf(d2, d2, q2); q3 = fmaf(d3, d3, q3);
    }
    float s = (s0 + s1) + (s2 + s3), ss = (q0 + q1) + (q2 + q3);
#pragma unroll
    for (int o = 16; o > 0; o >>= 1) { s += __shfl_xor_sync(0xffffffffu, s, o); ss += __shfl_xor_sync(0xffffffffu, ss, o); }
    const float md = s * (1.0f / 512.0f);
    const float var = fmaxf(ss * (1.0f / 512.0f) - md * md, 0.f);
    const float m = bf16r(shift + md);
    float sq; asm("sqrt.approx.f32 %0, %1;" : "=f"(sq) : "f"(bf16r(bf16r(var) + 1e-5f)));
    const float sd = bf16r(sq);
    return make_float2(m, __fdividef(1.0f, sd));
}

struct Maps { CUtensorMap m[8]; };

__global__ void __launch_bounds__(NTHREADS, 1)
fused_decode_kernel(const __grid_constant__ Maps maps, const unsigned char* __restrict__ kraw, const unsigned char* __restrict__ vraw,
                    const __nv_bfloat16* __restrict__ x, __nv_bfloat16* __restrict__ out)
{
    extern __shared__ __align__(1024) unsigned char smem_raw[];
    unsigned char* smem = smem_raw + ((1024u - (smem_u32(smem_raw) & 1023u)) & 1023u);
    const uint32_t sbase = smem_u32(smem);
    const uint32_t bar_full = sbase + OFF_BAR, bar_empty = sbase + OFF_BAR + 48, bar_ready = sbase + OFF_BAR + 96, bar_w = sbase + OFF_BAR + 104, bar_vl = sbase + OFF_BAR + 152;
    volatile unsigned* vars = reinterpret_cast<volatile unsigned*>(smem + OFF_VAR);
    const int tid = threadIdx.x, warp = tid >> 5, lane = tid & 31;
    const int cta = blockIdx.x;

    if (tid == 0) TSG(0);
    if (warp == 8) {
        if (lane == 0) {
            const size_t off = (size_t)cta * (NTILE * 128) * 256;
#pragma unroll
            for (int i = 0; i < EARLY_PF; i++)
                asm volatile("cp.async.bulk.prefetch.L2.global [%0], %1;" ::"l"(((i & 1) ? vraw : kraw) + off + (i >> 1) * 32768), "r"(32768) : "memory");
            for (int i = 0; i < NSLOT; i++) { mbar_init(bar_full + 8 * i, 1); mbar_init(bar_empty + 8 * i, 8); }
            mbar_init(bar_ready, 1);
            for (int i = 0; i < 6; i++) mbar_init(bar_w + 8 * i, 1);
            for (int i = 0; i < 4; i++) mbar_init(bar_vl + 8 * i, 1);
            vars[1] = 0;
            asm volatile("fence.mbarrier_init.release.cluster;" ::: "memory");
        } else if (lane <= 8) {
            asm volatile("prefetch.tensormap [%0];" ::"l"(&maps.m[lane - 1]) : "memory");
        }
    }
    __syncthreads();

    if (warp == 8) {
        if (lane == 0) {
            uint64_t pol_first, pol_norm;
            asm volatile("createpolicy.fractional.L2::evict_first.b64 %0, 1.0;" : "=l"(pol_first));
            asm volatile("createpolicy.fractional.L2::evict_normal.b64 %0, 1.0;" : "=l"(pol_norm));
            const int key0 = cta * (NTILE * 128);
            int arrived = 0;
            unsigned gbase = 0, grel = 0;
            int nkv = 0;
            for (int i = 0; i < NSEQ; i++) {
                const int slot = i % NSLOT;
                const bool is_w = (i == 0) || (i == SEQ_WO);
                if (i >= NSLOT) mbar_wait(bar_empty + 8 * slot, ((i / NSLOT) - 1) & 1);
                const int lead8 = (nkv * NCTA - (int)grel) / (NCTA / 8);
                const int d = (i > 2 && lead8 > LEAD_THR8) ? DEPTH_LO : DEPTH_HI;
                while (arrived < i - d + 1) { mbar_wait(bar_full + 8 * (arrived % NSLOT), (arrived / NSLOT) & 1); arrived++; }
                const uint32_t dst = sbase + slot * SLOT, fb = bar_full + 8 * slot;
                int mi, c0 = 0, c1 = 0, c2 = 0, nbox = 1;
                if (i == 0)            { mi = 2; c0 = cta * 32; nbox = 2; }
                else if (i == SEQ_WO)  { mi = 3; c1 = (cta >> 2) * 128; c2 = (cta & 3) * 2; }
                else                   { mi = nkv & 1; c1 = key0 + (nkv >> 1) * 128; }
                if (!is_w && nkv == 31) {
                    for (int j = 0; j < 4; j++) {
                        mbar_expect_tx(bar_vl + 8 * j, 8192);
                        tma3d(dst + j * 8192, &maps.m[7], 0, c1 + j * 32, 0, bar_vl + 8 * j, pol_first);
                    }
                } else {
                    mbar_expect_tx(fb, 32768);
                    for (int j = 0; j < nbox; j++) tma3d(dst + j * 16384, &maps.m[mi], c0, c1 + j * 256, c2, fb, is_w ? pol_norm : pol_first);
                }
                if (!is_w) {
                    if (nkv < 31) {
                        const unsigned g = atomicAdd(&g_prog, 1u);
                        if (nkv == 0) gbase = g & ~(unsigned)(NCTA * 32 - 1);
                        grel = g - gbase;
                    } else {
                        asm volatile("red.relaxed.gpu.global.add.u32 [%0], 1;" ::"l"(&g_prog) : "memory");
                    }
                    nkv++;
                }
            }
            if (cta < NFFN) {
                mbar_wait(bar_empty + 8 * SLOT_WGU, (34 / NSLOT - 1) & 1);
                mbar_wait(bar_empty + 8 * SLOT_WD, (35 / NSLOT - 1) & 1);
                if ((int)grel < NCTA * 32 - GATE_MARGIN) {
                    Spin sp; unsigned v;
                    while (true) {
                        asm volatile("ld.relaxed.gpu.global.u32 %0, [%1];" : "=r"(v) : "l"(&g_prog) : "memory");
                        if ((int)(v - gbase) >= NCTA * 32 - GATE_MARGIN) break;
                        sp.tick(); __nanosleep(64);
                    }
                }
                TSX(26, true);
                for (int k = 0; k < 6; k++) {
                    if (k >= WDEPTH) mbar_wait(bar_w + 8 * (k - WDEPTH), 0);
                    mbar_expect_tx(bar_w + 8 * k, 8192);
                    const int mi = (k < 4) ? 4 + (k >> 1) : 6;
                    const int c0 = (k < 4) ? cta * 16 : 0, c1 = (k < 4) ? (k & 1) * 256 : cta * 16, c2 = (k < 4) ? 0 : (k - 4) * 4;
                    tma3d(sbase + SLOT_WGU * SLOT + k * 8192, &maps.m[mi], c0, c1, c2, bar_w + 8 * k, pol_norm);
                }
            }
            TSX(20, true);
        }
        return;
    }

    const int pair = cta >> 2, split = cta & 3;

    if (warp == 9) {
        Spin sp;
        while (vars[1] < RESET_TILE) { sp.tick(); __nanosleep(256); }
        const unsigned epoch = vars[0];
#pragma unroll 1
        for (int u = lane; u < 128; u += 32) {
            st_rel128(&g_partO[((pair * 4 + (u >> 5)) * 4 + split) * 128 + (u & 31) * 4], SENT);
            const int seg = u >> 2;
            st_rel128(&g_ypart[(((seg >> 3) * 32 + (cta & 3) * 8 + (seg & 7)) * 32 + (cta >> 2)) * 16 + (u & 3) * 4], SENT);
        }
        if (lane < 4) st_rel64(&g_ml[(pair * 4 + lane) * 4 + split], SENT, SENT);
        if (lane < 2) st_rel128(&g_h[(cta >> 5) * 512 + (cta & 31) * 16 + lane * 8], SENT);
        if (cta < NFFN) {
#pragma unroll 1
            for (int e = lane; e < 512; e += 32) st_rel128(&g_dpart[((e >> 2) * NFFN + cta) * 16 + (e & 3) * 4], SENT);
        }
        __threadfence();
        __syncwarp();
        if (lane == 0) {
            atomicAdd(&g_cnt1, 1u);
            unsigned v; Spin sp2;
            while (true) {
                asm volatile("ld.acquire.gpu.global.u32 %0, [%1];" : "=r"(v) : "l"(&g_cnt1) : "memory");
                if ((int)(v - (epoch + 1) * NCTA) >= 0) break;
                sp2.tick(); __nanosleep(128);
            }
            mbar_arrive(bar_ready);
        }
        TSX(24, lane == 0);
        return;
    }

    const int r8 = lane >> 2, q4 = lane & 3;
    const int hp = q4 & 1, kh = q4 >> 1;
    constexpr float LOG2E = 1.4426950408889634f;
    const int bq = pair >> 3, gq = pair & 7;

    if (tid == 0) vars[0] = atomicAdd(&g_cnt0, 1u) >> 7;
    if (warp == 7) st_rel128(&g_q[(lane >> 3) * 2048 + cta * 16 + (lane & 7) * 2], 0u);
    float xres = 0.f;
    if (warp == 0) xres = __bfloat162float(x[(cta >> 5) * 512 + (cta & 31) * 16 + (lane >> 1)]);

    if (warp < 4) {
        const uint4* xr = reinterpret_cast<const uint4*>(x + warp * 512);
        const uint4 a = __ldg(xr + lane), b = __ldg(xr + 32 + lane);
        float v[16];
        const float2 st = ln_stats(a, b, v);
        uint32_t o[8];
#pragma unroll
        for (int i = 0; i < 8; i++) o[i] = pack_bf16(bf16r(v[2 * i] - st.x) * st.y, bf16r(v[2 * i + 1] - st.x) * st.y);
        unsigned char* row = smem + OFF_XN + warp * XN_PITCH;
        *reinterpret_cast<uint4*>(row + lane * 16) = make_uint4(o[0], o[1], o[2], o[3]);
        *reinterpret_cast<uint4*>(row + 512 + lane * 16) = make_uint4(o[4], o[5], o[6], o[7]);
    }
    cbar();
    const uint32_t tag = vars[0] + 1;

    {
        uint32_t bfr[4][2];
        {
            uint32_t t4[4];
#pragma unroll
            for (int u = 0; u < 2; u++) {
                ldsm4(t4, sbase + OFF_XN + (lane & 3) * XN_PITCH + (8 * warp + 4 * u + (lane >> 3)) * 16);
                bfr[2 * u][0] = t4[0]; bfr[2 * u][1] = t4[1]; bfr[2 * u + 1][0] = t4[2]; bfr[2 * u + 1][1] = t4[3];
            }
        }
        mbar_wait(bar_full + 0, 0);
        TS(2);
        float acc[2][4] = {};
#pragma unroll
        for (int ks = 0; ks < 4; ks++) {
            const int k = 64 * warp + 16 * ks + (lane & 7) + (lane >> 4) * 8;
#pragma unroll
            for (int mt = 0; mt < 2; mt++) {
                uint32_t a[4];
                const int chunk = 2 * mt + ((lane >> 3) & 1);
                ldsm4t(a, sbase + k * 64 + ((chunk ^ ((k >> 1) & 3)) << 4));
                mma16816(acc[mt], a, bfr[ks][0], bfr[ks][1]);
            }
        }
        __syncwarp();
        if (lane == 0) mbar_arrive(bar_empty + 0);
        float* red = reinterpret_cast<float*>(smem + OFF_RED);
#pragma unroll
        for (int mt = 0; mt < 2; mt++) {
            float2 v = kh ? make_float2(acc[mt][2], acc[mt][3]) : make_float2(acc[mt][0], acc[mt][1]);
            *reinterpret_cast<float2*>(red + ((warp * 2 + mt) * 16 + r8 + 8 * kh) * 4 + 2 * hp) = v;
        }
        cbar();
        if (tid < 64) {
            const int b = tid >> 4, c2 = tid & 15;
            float s0 = 0.f, s1 = 0.f;
            const int c0 = 2 * c2, c1 = 2 * c2 + 1;
#pragma unroll
            for (int ww = 0; ww < 8; ww++) {
                s0 += red[((ww * 2 + (c0 >> 4)) * 16 + (c0 & 15)) * 4 + b];
                s1 += red[((ww * 2 + (c1 >> 4)) * 16 + (c1 & 15)) * 4 + b];
            }
            st_rel64(&g_q[b * 2048 + cta * 16 + c2], pack_bf16(s0, s1), tag);
        }
        {
            const uint2* src = &g_q[bq * 2048 + gq * 256 + tid];
            uint2 v;
            Spin sp;
            while (true) { v = ld_poll2(src); if (__all_sync(0xffffffffu, v.y == tag)) break; sp.tick(); }
            *reinterpret_cast<uint32_t*>(smem + OFF_QS + (tid >> 6) * QS_PITCH + (tid & 63) * 4) = v.x;
        }
        cbar();
    }
    TS(3);
    uint32_t qf[8][2];
    {
        uint32_t t4[4];
#pragma unroll
        for (int u = 0; u < 4; u++) {
            ldsm4(t4, sbase + OFF_QS + (lane & 3) * QS_PITCH + (4 * u + (lane >> 3)) * 16);
            qf[2 * u][0] = t4[0]; qf[2 * u][1] = t4[1]; qf[2 * u + 1][0] = t4[2]; qf[2 * u + 1][1] = t4[3];
        }
    }

    const uint32_t voff = (warp >> 2) * 16384 + ((lane & 7) + (lane >> 4) * 8) * 128 +
                          ((((2 * warp + ((lane >> 3) & 1)) & 7) ^ (lane & 7)) << 4);
    const uint32_t poff = sbase + OFF_P + (lane & 3) * QS_PITCH + (lane >> 3) * 16;
    const uint32_t koff = (16 * warp + (lane & 7) + ((lane >> 3) & 1) * 8) * 128;
    const uint32_t kx = lane & 7, kc = lane >> 4;
    constexpr float SCALE = 0.08838834764831845f;
    uint32_t* mxbuf = reinterpret_cast<uint32_t*>(smem + OFF_MX);
    uint32_t M2 = 0xFF80FF80u;
    float l0 = 0.f, l1 = 0.f;
    float oacc[2][4] = {};
    int slot = 1; uint32_t ph = 0;

    for (int t = 0;; t++) {
        mbar_wait(bar_full + 8 * slot, ph);
        float sa[4] = {}, sb[4] = {};
        {
            const uint32_t kb = sbase + slot * SLOT + koff;
#pragma unroll
            for (int ks = 0; ks < 8; ks++) {
                uint32_t a[4];
                ldsm4(a, kb + (ks >> 2) * 16384 + (((2 * (ks & 3) + kc) ^ kx) << 4));
                if (ks & 1) mma16816(sb, a, qf[ks][0], qf[ks][1]); else mma16816(sa, a, qf[ks][0], qf[ks][1]);
            }
        }
        __syncwarp();
        if (lane == 0) mbar_arrive(bar_empty + 8 * slot);
        if (++slot == NSLOT) { slot = 0; ph ^= 1; }

        const float r0 = kh ? sa[2] + sb[2] : sa[0] + sb[0];
        const float r1 = kh ? sa[3] + sb[3] : sa[1] + sb[1];
        uint32_t sp = pack_bf16(r0, r1);
        sp = pack_bf16(bf_lo(sp) * SCALE, bf_hi(sp) * SCALE);
        uint32_t mx = sp;
#pragma unroll
        for (int o = 2; o <= 16; o <<= 1) mx = hmax2(mx, __shfl_xor_sync(0xffffffffu, mx, o));
        if (lane < 2) mxbuf[lane * 8 + warp] = mx;
        if (tid == 0) vars[1] = t + 1;
        TS(40 + t);
        cbar();
        {
            const uint4 m0 = *reinterpret_cast<const uint4*>(mxbuf + hp * 8), m1 = *reinterpret_cast<const uint4*>(mxbuf + hp * 8 + 4);
            uint32_t mt = hmax2(hmax2(hmax2(m0.x, m0.y), hmax2(m0.z, m0.w)), hmax2(hmax2(m1.x, m1.y), hmax2(m1.z, m1.w)));
            const uint32_t Mn = hmax2(M2, mt);
            const float a0 = ex2((bf_lo(M2) - bf_lo(Mn)) * LOG2E), a1 = ex2((bf_hi(M2) - bf_hi(Mn)) * LOG2E);
            const float p0 = ex2((bf_lo(sp) - bf_lo(Mn)) * LOG2E), p1 = ex2((bf_hi(sp) - bf_hi(Mn)) * LOG2E);
            M2 = Mn;
            l0 = fmaf(l0, a0, p0); l1 = fmaf(l1, a1, p1);
            const uint32_t pp = pack_bf16(p0, p1);
            unsigned char* pd = smem + OFF_P + (2 * hp) * QS_PITCH + (16 * warp + r8 + 8 * kh) * 2;
            *reinterpret_cast<uint16_t*>(pd) = (uint16_t)(pp & 0xFFFF);
            *reinterpret_cast<uint16_t*>(pd + QS_PITCH) = (uint16_t)(pp >> 16);
#pragma unroll
            for (int c = 0; c < 2; c++) { oacc[c][0] *= a0; oacc[c][1] *= a1; oacc[c][2] *= a0; oacc[c][3] *= a1; }
        }
        if (t == NTILE - 1) break;
        cbar();
        uint32_t pb[8][2];
        {
            uint32_t t4[4];
#pragma unroll
            for (int u = 0; u < 4; u++) {
                ldsm4(t4, poff + u * 64);
                pb[2 * u][0] = t4[0]; pb[2 * u][1] = t4[1]; pb[2 * u + 1][0] = t4[2]; pb[2 * u + 1][1] = t4[3];
            }
        }
        mbar_wait(bar_full + 8 * slot, ph);
        {
            const uint32_t vb = sbase + slot * SLOT + voff;
#pragma unroll
            for (int ks = 0; ks < 8; ks++) {
                uint32_t a[4];
                ldsm4t(a, vb + ks * 2048);
                mma16816(oacc[ks & 1], a, pb[ks][0], pb[ks][1]);
            }
        }
        __syncwarp();
        if (lane == 0) mbar_arrive(bar_empty + 8 * slot);
        if (++slot == NSLOT) { slot = 0; ph ^= 1; }
        if (SEQ_WO == 31 && t == NTILE - 2) { if (++slot == NSLOT) { slot = 0; ph ^= 1; } }
    }

    const int head = cta >> 2;
    float* p_partO = &g_partO[((pair * 4 + 2 * hp) * 4 + split) * 128 + 16 * warp + r8 + 8 * kh];
    float* p_dpart = &g_dpart[(((2 * hp) * 32 + 4 * warp) * NFFN + cta) * 16 + r8 + 8 * kh];
    const float* p_dsrc = &g_dpart[(cta * NFFN + (tid >> 2)) * 16 + (tid & 3) * 4];
    __nv_bfloat16* p_out = out + (cta >> 5) * 512 + (cta & 31) * 16 + (lane >> 1);
    pin(p_partO); pin(p_dpart); pin(p_dsrc); pin(p_out);

    {
        float s0 = l0, s1 = l1;
#pragma unroll
        for (int o = 2; o <= 16; o <<= 1) { s0 += __shfl_xor_sync(0xffffffffu, s0, o); s1 += __shfl_xor_sync(0xffffffffu, s1, o); }
        if (lane < 2) *reinterpret_cast<float2*>(smem + OFF_L + warp * 16 + lane * 8) = make_float2(s0, s1);
        mbar_wait(bar_ready, 0);
        cbar();
        if (warp == 0) {
            const uint32_t other = __shfl_sync(0xffffffffu, M2, lane >> 1);
            float l = 0.f;
#pragma unroll
            for (int ww = 0; ww < 8; ww++) l += *reinterpret_cast<const float*>(smem + OFF_L + ww * 16 + (lane & 3) * 4);
            const float m = (lane & 1) ? bf_hi(other) : bf_lo(other);
            if (lane < 4) st_rel64(&g_ml[(pair * 4 + lane) * 4 + split], __float_as_uint(m), __float_as_uint(l));
        }
        uint32_t pb[8][2];
        {
            uint32_t t4[4];
#pragma unroll
            for (int u = 0; u < 4; u++) {
                ldsm4(t4, poff + u * 64);
                pb[2 * u][0] = t4[0]; pb[2 * u][1] = t4[1]; pb[2 * u + 1][0] = t4[2]; pb[2 * u + 1][1] = t4[3];
            }
        }
        float o2[2][4] = {};
        {
            const uint32_t vb = sbase + slot * SLOT + (warp >> 2) * 4096 + ((lane & 7) + (lane >> 4) * 8) * 128 +
                                ((((2 * warp + ((lane >> 3) & 1)) & 7) ^ (lane & 7)) << 4);
#pragma unroll
            for (int p = 0; p < 4; p++) {
                uint32_t a0[4], a1[4];
                mbar_wait(bar_vl + 8 * p, 0);
                if (p == 3) { TS(30); }
                ldsm4t(a0, vb + p * 8192);
                ldsm4t(a1, vb + p * 8192 + 2048);
                mma16816((p & 1) ? o2[0] : oacc[0], a0, pb[2 * p][0], pb[2 * p][1]);
                mma16816((p & 1) ? o2[1] : oacc[1], a1, pb[2 * p + 1][0], pb[2 * p + 1][1]);
            }
        }
        const float v0 = kh ? (oacc[0][2] + oacc[1][2]) + (o2[0][2] + o2[1][2]) : (oacc[0][0] + oacc[1][0]) + (o2[0][0] + o2[1][0]);
        const float v1 = kh ? (oacc[0][3] + oacc[1][3]) + (o2[0][3] + o2[1][3]) : (oacc[0][1] + oacc[1][1]) + (o2[0][1] + o2[1][1]);
        st_rel32(p_partO, __float_as_uint(v0));
        st_rel32(p_partO + 512, __float_as_uint(v1));
        TS(4);
    }

    float hres = 0.f;
    uint32_t df[4][4];
    if (warp < 4) {
        {
            const int ph_idx = (warp * 8 + (head >> 2)) * 4 + (head & 3);
            const float* po = &g_partO[ph_idx * 512 + lane * 4];
            const float* pm = reinterpret_cast<const float*>(&g_ml[ph_idx * 4]);
            uint4 o0, o1, o2, o3, ma, mb;
            Spin sp;
            while (true) {
                o0 = ld_poll4(po); o1 = ld_poll4(po + 128); o2 = ld_poll4(po + 256); o3 = ld_poll4(po + 384);
                ma = ld_poll4(pm); mb = ld_poll4(pm + 4);
                const uint32_t mxv = max(max(max(umax4(o0), umax4(o1)), max(umax4(o2), umax4(o3))), max(umax4(ma), umax4(mb)));
                if (__all_sync(0xffffffffu, mxv != SENT)) break;
                sp.tick();
            }
            TS(6);
            const float m0 = __uint_as_float(ma.x), m1 = __uint_as_float(ma.z), m2 = __uint_as_float(mb.x), m3 = __uint_as_float(mb.z);
            const float M = fmaxf(fmaxf(m0, m1), fmaxf(m2, m3));
            float w0 = ex2((m0 - M) * LOG2E), w1 = ex2((m1 - M) * LOG2E), w2 = ex2((m2 - M) * LOG2E), w3 = ex2((m3 - M) * LOG2E);
            const float L = w0 * __uint_as_float(ma.y) + w1 * __uint_as_float(ma.w) + w2 * __uint_as_float(mb.y) + w3 * __uint_as_float(mb.w);
            const float inv = __fdividef(1.0f, L);
            const float e0 = (w0 * __uint_as_float(o0.x) + w1 * __uint_as_float(o1.x) + w2 * __uint_as_float(o2.x) + w3 * __uint_as_float(o3.x)) * inv;
            const float e1 = (w0 * __uint_as_float(o0.y) + w1 * __uint_as_float(o1.y) + w2 * __uint_as_float(o2.y) + w3 * __uint_as_float(o3.y)) * inv;
            const float e2 = (w0 * __uint_as_float(o0.z) + w1 * __uint_as_float(o1.z) + w2 * __uint_as_float(o2.z) + w3 * __uint_as_float(o3.z)) * inv;
            const float e3 = (w0 * __uint_as_float(o0.w) + w1 * __uint_as_float(o1.w) + w2 * __uint_as_float(o2.w) + w3 * __uint_as_float(o3.w)) * inv;
            *reinterpret_cast<uint2*>(smem + OFF_QS + warp * QS_PITCH + lane * 8) = make_uint2(pack_bf16(e0, e1), pack_bf16(e2, e3));
            TSD(31, tid == 0, e0 + e1 + e2 + e3);
            bar_arrive(2, 256);
        }
        if (warp == 0) {
            const float* src = &g_ypart[(cta * 32 + lane) * 16];
            uint16_t* p_h = &g_h[(cta >> 5) * 512 + (cta & 31) * 16 + (lane >> 1)];
            pin(p_h);
            delay_cycles(DLY2);
            uint4 y0, y1, y2, y3;
            Spin sp;
            while (true) {
                y0 = ld_poll4(src); y1 = ld_poll4(src + 4); y2 = ld_poll4(src + 8); y3 = ld_poll4(src + 12);
                if (__all_sync(0xffffffffu, max(max(umax4(y0), umax4(y1)), max(umax4(y2), umax4(y3))) != SENT)) break;
                sp.tick();
            }
            TS(9);
            float v0, v1, v2, v3, v4, v5, v6, v7;
            {
                const bool up = lane & 16;
#define RSTEP(dst, lo, hi, m) { const float _l = __uint_as_float(lo), _h = __uint_as_float(hi); dst = (up ? _h : _l) + __shfl_xor_sync(0xffffffffu, up ? _l : _h, m); }
                RSTEP(v0, y0.x, y2.x, 16) RSTEP(v1, y0.y, y2.y, 16) RSTEP(v2, y0.z, y2.z, 16) RSTEP(v3, y0.w, y2.w, 16)
                RSTEP(v4, y1.x, y3.x, 16) RSTEP(v5, y1.y, y3.y, 16) RSTEP(v6, y1.z, y3.z, 16) RSTEP(v7, y1.w, y3.w, 16)
#undef RSTEP
            }
#define RSTEP(dst, a, b, m) { const bool _u = lane & m; dst = (_u ? b : a) + __shfl_xor_sync(0xffffffffu, _u ? a : b, m); }
            RSTEP(v0, v0, v4, 8) RSTEP(v1, v1, v5, 8) RSTEP(v2, v2, v6, 8) RSTEP(v3, v3, v7, 8)
            RSTEP(v0, v0, v2, 4) RSTEP(v1, v1, v3, 4)
            RSTEP(v0, v0, v1, 2)
#undef RSTEP
            v0 += __shfl_xor_sync(0xffffffffu, v0, 1);
            hres = bf16r(xres + bf16r(v0));
            if (!(lane & 1)) st_rel16(p_h, (uint16_t)(__float_as_uint(hres) >> 16));
            TS(10);
        }
        if (cta < NFFN) {
            bar_sync(7, 128);
            const uint4* hr = reinterpret_cast<const uint4*>(g_h + warp * 512);
            delay_cycles(DLY3);
            uint4 a, b;
            Spin sp;
            while (true) {
                a = ld_poll4(hr + lane); b = ld_poll4(hr + 32 + lane);
                const bool ok = (__vcmpeq2(a.x, SENT) | __vcmpeq2(a.y, SENT) | __vcmpeq2(a.z, SENT) | __vcmpeq2(a.w, SENT) |
                                 __vcmpeq2(b.x, SENT) | __vcmpeq2(b.y, SENT) | __vcmpeq2(b.z, SENT) | __vcmpeq2(b.w, SENT)) == 0;
                if (__all_sync(0xffffffffu, ok)) break;
                sp.tick();
            }
            TS(13);
            unsigned char* row = smem + OFF_XN + warp * XN_PITCH;
            *reinterpret_cast<uint4*>(row + lane * 16) = a;
            *reinterpret_cast<uint4*>(row + 512 + lane * 16) = b;
            bar_arrive(3, 256);
            float v[16];
            const float2 st = ln_stats(a, b, v);
            if (lane == 0) *reinterpret_cast<float2*>(smem + OFF_ST + warp * 8) = st;
            bar_arrive(4, 256);
            TS(14);
            mbar_wait(bar_w + 32, 0); mbar_wait(bar_w + 40, 0);
            const uint32_t wb = sbase + SLOT_WD * SLOT + warp * 2048 + ((lane & 7) + (lane >> 4) * 8) * 128;
#pragma unroll
            for (int i = 0; i < 4; i++) ldsm4t(df[i], wb + (((2 * i + ((lane >> 3) & 1)) ^ (lane & 7)) << 4));
        }
    } else {
        const int m = warp - 4;
        {
            uint32_t af[2][8][4];
            float* p_y = &g_ypart[(((2 * hp) * 32 + (cta & 3) * 8 + 2 * m) * 32 + head) * 16 + r8 + 8 * kh];
            pin(p_y);
            mbar_wait(bar_full + 8 * (SEQ_WO % NSLOT), (SEQ_WO / NSLOT) & 1);
#pragma unroll
            for (int i = 0; i < 2; i++) {
                const int j = 2 * m + i;
                const uint32_t wb = sbase + (SEQ_WO % NSLOT) * SLOT + (j >> 2) * 16384 + ((lane & 7) + (lane >> 4) * 8) * 128 +
                                    ((((2 * j + ((lane >> 3) & 1)) & 7) ^ (lane & 7)) << 4);
#pragma unroll
                for (int ks = 0; ks < 8; ks++) ldsm4t(af[i][ks], wb + ks * 2048);
            }
            TSX(5, tid == 128);
            bar_sync(2, 256);
            TSX(7, tid == 128);
            float acc[2][2][4] = {};
            uint32_t t4[4][4];
#pragma unroll
            for (int u = 0; u < 4; u++) ldsm4(t4[u], sbase + OFF_QS + (lane & 3) * QS_PITCH + (4 * u + (lane >> 3)) * 16);
            TSD(37, tid == 128, __uint_as_float(t4[0][0]));
#pragma unroll
            for (int u = 0; u < 4; u++) {
#pragma unroll
                for (int i = 0; i < 2; i++) {
                    mma16816(acc[i][0], af[i][2 * u], t4[u][0], t4[u][1]);
                    mma16816(acc[i][1], af[i][2 * u + 1], t4[u][2], t4[u][3]);
                }
            }
#pragma unroll
            for (int i = 0; i < 2; i++) {
                const float v0 = kh ? acc[i][0][2] + acc[i][1][2] : acc[i][0][0] + acc[i][1][0];
                const float v1 = kh ? acc[i][0][3] + acc[i][1][3] : acc[i][0][1] + acc[i][1][1];
                st_rel32(p_y + i * 32 * 16, __float_as_uint(v0));
                st_rel32(p_y + i * 32 * 16 + 32 * 32 * 16, __float_as_uint(v1));
            }
            TSX(8, tid == 128);
        }
        if (cta < NFFN) {
            uint32_t gf[8][2][4];
            mbar_wait(bar_w, 0); mbar_wait(bar_w + 8, 0); mbar_wait(bar_w + 16, 0); mbar_wait(bar_w + 24, 0);
#pragma unroll
            for (int ks = 0; ks < 8; ks++) {
                const int k = 128 * m + 16 * ks + (lane & 7) + (lane >> 4) * 8;
                const uint32_t a = sbase + SLOT_WGU * SLOT + k * 32 + ((((lane >> 3) & 1) ^ ((k >> 2) & 1)) << 4);
                ldsm4t(gf[ks][0], a);
                ldsm4t(gf[ks][1], a + 16384);
            }
            TSX(11, tid == 128);
            float sg = 0.f, su = 0.f;
            {
                float cs[2][4] = {};
#pragma unroll
                for (int ks = 0; ks < 8; ks++) { mma16816(cs[0], gf[ks][0], 0x3F803F80u, 0x3F803F80u); mma16816(cs[1], gf[ks][1], 0x3F803F80u, 0x3F803F80u); }
                float* csb = reinterpret_cast<float*>(smem + OFF_CS);
                if (q4 == 0) {
                    csb[(m * 2 + 0) * 16 + r8] = cs[0][0]; csb[(m * 2 + 0) * 16 + r8 + 8] = cs[0][2];
                    csb[(m * 2 + 1) * 16 + r8] = cs[1][0]; csb[(m * 2 + 1) * 16 + r8 + 8] = cs[1][2];
                }
                bar_sync(5, 128);
                const int c = (tid & 63) >> 2;
#pragma unroll
                for (int ww = 0; ww < 4; ww++) { sg += csb[(ww * 2) * 16 + c]; su += csb[(ww * 2 + 1) * 16 + c]; }
            }
            mbar_wait(bar_w + 32, 0); mbar_wait(bar_w + 40, 0);
            {
                const uint32_t wb = sbase + SLOT_WD * SLOT + warp * 2048 + ((lane & 7) + (lane >> 4) * 8) * 128;
#pragma unroll
                for (int i = 0; i < 4; i++) ldsm4t(df[i], wb + (((2 * i + ((lane >> 3) & 1)) ^ (lane & 7)) << 4));
            }
            TSX(12, tid == 128);
            bar_sync(3, 256);
            float acc[2][2][4] = {};
            uint32_t t4[4][4];
#pragma unroll
            for (int u = 0; u < 4; u++) ldsm4(t4[u], sbase + OFF_XN + (lane & 3) * XN_PITCH + (16 * m + 4 * u + (lane >> 3)) * 16);
            TSD(27, tid == 128, __uint_as_float(t4[0][0]));
#pragma unroll
            for (int u = 0; u < 4; u++) {
#pragma unroll
                for (int i = 0; i < 2; i++) {
                    mma16816(acc[i][0], gf[2 * u][i], t4[u][0], t4[u][1]);
                    mma16816(acc[i][1], gf[2 * u + 1][i], t4[u][2], t4[u][3]);
                }
            }
            TSD(28, tid == 128, acc[1][1][0] + acc[0][0][0] + acc[0][1][0] + acc[1][0][0]);
            float* red = reinterpret_cast<float*>(smem + OFF_RED);
#pragma unroll
            for (int i = 0; i < 2; i++) {
                const float2 v = kh ? make_float2(acc[i][0][2] + acc[i][1][2], acc[i][0][3] + acc[i][1][3])
                                    : make_float2(acc[i][0][0] + acc[i][1][0], acc[i][0][1] + acc[i][1][1]);
                *reinterpret_cast<float2*>(red + ((m * 2 + i) * 16 + r8 + 8 * kh) * 4 + 2 * hp) = v;
            }
            bar_sync(4, 256);
            TSX(16, tid == 128);
            if (tid < 192) {
                const int c = (tid & 63) >> 2, b = tid & 3;
                const float2 st = *reinterpret_cast<const float2*>(smem + OFF_ST + b * 8);
                float g = 0.f, u = 0.f;
#pragma unroll
                for (int ww = 0; ww < 4; ww++) { g += red[((ww * 2) * 16 + c) * 4 + b]; u += red[((ww * 2 + 1) * 16 + c) * 4 + b]; }
                TSD(29, tid == 128, g + u + st.x);
                g = bf16r((g - st.x * sg) * st.y); u = bf16r((u - st.x * su) * st.y);
                const float inner = 0.7978845608028654f * (g + 0.044715f * g * g * g);
                const float th = 1.0f - __fdividef(2.0f, __expf(2.0f * inner) + 1.0f);
                const float ge = bf16r(0.5f * g * (1.0f + th));
                *reinterpret_cast<__nv_bfloat16*>(smem + OFF_ACT + b * 32 + c * 2) = __float2bfloat16_rn(ge * u);
                TSD(32, tid == 128, ge * u);
            }
        }
    }
    if (cta < NFFN) {
        bar_sync(6, 256);
        TS(17);
        const uint32_t b0 = *reinterpret_cast<const uint32_t*>(smem + OFF_ACT + (r8 & 3) * 32 + q4 * 4);
        const uint32_t b1 = *reinterpret_cast<const uint32_t*>(smem + OFF_ACT + (r8 & 3) * 32 + 16 + q4 * 4);
        TSD(33, tid == 0, __uint_as_float(b0));
        float c[4][4] = {};
#pragma unroll
        for (int i = 0; i < 4; i++) mma16816(c[i], df[i], b0, b1);
#pragma unroll
        for (int i = 0; i < 4; i++) {
            st_rel32(p_dpart + i * NFFN * 16, __float_as_uint(kh ? c[i][2] : c[i][0]));
            st_rel32(p_dpart + i * NFFN * 16 + 32 * NFFN * 16, __float_as_uint(kh ? c[i][3] : c[i][1]));
        }
        TS(18);
    }

    {
        const int quad = tid & 3;
        const bool two = (tid >> 2) + 64 < NFFN;
        uint4 a, b = make_uint4(0, 0, 0, 0);
        Spin sp;
        delay_cycles(DLY4);
        while (true) {
            a = ld_poll4(p_dsrc);
            if (two) b = ld_poll4(p_dsrc + 64 * 16);
            if (__all_sync(0xffffffffu, max(umax4(a), umax4(b)) != SENT)) break;
            sp.tick();
        }
        TS(19);
        float v[4] = {__uint_as_float(a.x) + __uint_as_float(b.x), __uint_as_float(a.y) + __uint_as_float(b.y),
                      __uint_as_float(a.z) + __uint_as_float(b.z), __uint_as_float(a.w) + __uint_as_float(b.w)};
        {
            const bool up = lane & 16;
            const float s0 = up ? v[0] : v[2], s1 = up ? v[1] : v[3];
            const float k0 = up ? v[2] : v[0], k1 = up ? v[3] : v[1];
            v[0] = k0 + __shfl_xor_sync(0xffffffffu, s0, 16);
            v[1] = k1 + __shfl_xor_sync(0xffffffffu, s1, 16);
            const bool up2 = lane & 8;
            const float s = up2 ? v[0] : v[1], k = up2 ? v[1] : v[0];
            v[0] = k + __shfl_xor_sync(0xffffffffu, s, 8);
            v[0] += __shfl_xor_sync(0xffffffffu, v[0], 4);
            if (!(lane & 4)) reinterpret_cast<float*>(smem + OFF_RED2)[warp * 16 + 4 * quad + ((lane & 16) ? 2 : 0) + ((lane & 8) ? 1 : 0)] = v[0];
        }
        cbar();
        TS(21);
        if (warp == 0) {
            const float* r2 = reinterpret_cast<const float*>(smem + OFF_RED2) + (lane & 1) * 64 + (lane >> 1);
            float s = (r2[0] + r2[16]) + (r2[32] + r2[48]);
            TSD(34, tid == 0, s);
            s += __shfl_xor_sync(0xffffffffu, s, 1);
            if (!(lane & 1)) *p_out = __float2bfloat16_rn(hres + bf16r(s));
        }
    }
    TS(22);
    if (tid == 0) TSG(62);
}

typedef CUresult (*EncodeFn)(CUtensorMap*, CUtensorMapDataType, cuuint32_t, void*, const cuuint64_t*, const cuuint64_t*,
                             const cuuint32_t*, const cuuint32_t*, CUtensorMapInterleave, CUtensorMapSwizzle,
                             CUtensorMapL2promotion, CUtensorMapFloatOOBfill);

void encode(EncodeFn fn, CUtensorMap* m, const void* base, int rank, const cuuint64_t* dims, const cuuint64_t* strides,
            const cuuint32_t* box, CUtensorMapSwizzle sw, CUtensorMapL2promotion promo) {
    cuuint32_t es[3] = {1, 1, 1};
    fn(m, CU_TENSOR_MAP_DATA_TYPE_BFLOAT16, (cuuint32_t)rank, const_cast<void*>(base), dims, strides, box, es,
       CU_TENSOR_MAP_INTERLEAVE_NONE, sw, promo, CU_TENSOR_MAP_FLOAT_OOB_FILL_NONE);
}

}

extern "C" void kernel_launch(void* const* d_in, const int* in_sizes, int n_in, void* d_out, int out_size) {
    (void)in_sizes; (void)n_in; (void)out_size;
    static EncodeFn enc = nullptr;
    if (!enc) {
        void* fn = nullptr;
        cudaDriverEntryPointQueryResult qr;
        cudaGetDriverEntryPoint("cuTensorMapEncodeTiled", &fn, cudaEnableDefault, &qr);
        enc = (EncodeFn)fn;
        cudaFuncSetAttribute(fused_decode_kernel, cudaFuncAttributeMaxDynamicSharedMemorySize, SMEM_BYTES);
    }
    const void* x = d_in[0];
    Maps maps;
    {
        cuuint64_t dims[3] = {64, 262144, 2}; cuuint64_t str[2] = {256, 128}; cuuint32_t box[3] = {64, 128, 2};
        encode(enc, &maps.m[0], d_in[1], 3, dims, str, box, CU_TENSOR_MAP_SWIZZLE_128B, CU_TENSOR_MAP_L2_PROMOTION_L2_256B);
        encode(enc, &maps.m[1], d_in[2], 3, dims, str, box, CU_TENSOR_MAP_SWIZZLE_128B, CU_TENSOR_MAP_L2_PROMOTION_L2_256B);
    }
    {
        cuuint64_t dims[3] = {64, 262144, 2}; cuuint64_t str[2] = {256, 128}; cuuint32_t box[3] = {64, 32, 2};
        encode(enc, &maps.m[7], d_in[2], 3, dims, str, box, CU_TENSOR_MAP_SWIZZLE_128B, CU_TENSOR_MAP_L2_PROMOTION_L2_256B);
    }
    {
        cuuint64_t dims[3] = {4096, 512, 1}; cuuint64_t str[2] = {8192, 8192 * 512}; cuuint32_t box[3] = {32, 256, 1};
        encode(enc, &maps.m[2], d_in[3], 3, dims, str, box, CU_TENSOR_MAP_SWIZZLE_64B, CU_TENSOR_MAP_L2_PROMOTION_L2_128B);
    }
    {
        cuuint64_t dims[3] = {64, 4096, 8}; cuuint64_t str[2] = {1024, 128}; cuuint32_t box[3] = {64, 128, 2};
        encode(enc, &maps.m[3], d_in[4], 3, dims, str, box, CU_TENSOR_MAP_SWIZZLE_128B, CU_TENSOR_MAP_L2_PROMOTION_L2_256B);
    }
    {
        cuuint64_t dims[3] = {1792, 512, 1}; cuuint64_t str[2] = {3584, 3584 * 512}; cuuint32_t box[3] = {16, 256, 1};
        encode(enc, &maps.m[4], d_in[6], 3, dims, str, box, CU_TENSOR_MAP_SWIZZLE_32B, CU_TENSOR_MAP_L2_PROMOTION_L2_128B);
        encode(enc, &maps.m[5], d_in[7], 3, dims, str, box, CU_TENSOR_MAP_SWIZZLE_32B, CU_TENSOR_MAP_L2_PROMOTION_L2_128B);
    }
    {
        cuuint64_t dims[3] = {64, 1792, 8}; cuuint64_t str[2] = {1024, 128}; cuuint32_t box[3] = {64, 16, 4};
        encode(enc, &maps.m[6], d_in[8], 3, dims, str, box, CU_TENSOR_MAP_SWIZZLE_128B, CU_TENSOR_MAP_L2_PROMOTION_L2_256B);
    }
    fused_decode_kernel<<<NCTA, NTHREADS, SMEM_BYTES, cudaStreamPerThread>>>(maps, (const unsigned char*)d_in[1], (const unsigned char*)d_in[2],
        (const __nv_bfloat16*)x, (__nv_bfloat16*)d_out);
}
```

```cpp
#include <cuda_runtime.h>
#include <cuda_bf16.h>
#include <cuda.h>
#include <stdint.h>

namespace {

constexpr int NCTA      = 128;
constexpr int NTHREADS  = 320;
constexpr int SLOT      = 32768;
constexpr int NSLOT     = 6;
constexpr int NTILE     = 16;
constexpr int NFFN      = 112;
#define DEPTH_LO 2
#define DEPTH_HI 3
#define LEAD_THR8 4
#define GATE_MARGIN 0
#define WDEPTH 3
#define WO_MARGIN 112
#define SEQ_WO 33
constexpr int SEQ_K15 = (SEQ_WO == 31) ? 32 : 31;
constexpr int NSEQ    = 34;
constexpr int SLOT_WGU = 4, SLOT_WD = 5;
#define DLY2 0
#define DLY3 0
#define DLY4 500
#define EARLY_PF 0
#define VSPLIT 0
#define DEPTH_INIT 3
#define RESET_TILE 8
constexpr uint32_t SENT = 0xFFFFFFFFu;

constexpr int OFF_XN   = NSLOT * SLOT;
constexpr int XN_PITCH = 1040;
constexpr int OFF_QS   = OFF_XN + 4 * XN_PITCH;
constexpr int QS_PITCH = 272;
constexpr int OFF_P    = OFF_QS + 4 * QS_PITCH;
constexpr int OFF_RED  = OFF_P + 4 * QS_PITCH;
constexpr int OFF_MX   = OFF_RED + 4096;
constexpr int OFF_L    = OFF_MX + 64;
constexpr int OFF_ACT  = OFF_L + 128;
constexpr int OFF_RED2 = OFF_ACT + 128;
constexpr int OFF_CS   = OFF_RED2 + 512;
constexpr int OFF_ST   = OFF_CS + 512;
constexpr int OFF_BAR  = OFF_ST + 32;
constexpr int OFF_VAR  = OFF_BAR + 192;
constexpr int SMEM_USED = OFF_VAR + 64;
constexpr int SMEM_BYTES = SMEM_USED + 1024;
static_assert(OFF_RED % 16 == 0 && OFF_MX % 16 == 0 && OFF_ST % 8 == 0 && OFF_BAR % 8 == 0, "alignment");

__device__ uint2    g_q[4 * 2048];
__device__ float    g_partO[32 * 4 * 4 * 128];
__device__ float2   g_ml[32 * 4 * 4];
__device__ float    g_ypart[4 * 32 * 32 * 16];
__device__ uint16_t g_h[4 * 512];
__device__ float    g_dpart[4 * 32 * NFFN * 16];
__device__ unsigned g_cnt0, g_cnt1, g_prog;
#define TS(i)
#define TSX(i, cond)
#define TSG(i)
#define TSD(i, cond, dep)

__device__ __forceinline__ uint32_t smem_u32(const void* p) { return (uint32_t)__cvta_generic_to_shared(p); }
__device__ __forceinline__ void mbar_init(uint32_t bar, uint32_t cnt) {
    asm volatile("mbarrier.init.shared::cta.b64 [%0], %1;" ::"r"(bar), "r"(cnt) : "memory");
}
__device__ __forceinline__ void mbar_expect_tx(uint32_t bar, uint32_t bytes) {
    asm volatile("mbarrier.arrive.expect_tx.shared::cta.b64 _, [%0], %1;" ::"r"(bar), "r"(bytes) : "memory");
}
__device__ __forceinline__ void mbar_arrive(uint32_t bar) {
    asm volatile("mbarrier.arrive.shared::cta.b64 _, [%0];" ::"r"(bar) : "memory");
}
__device__ __forceinline__ bool mbar_try(uint32_t bar, uint32_t parity) {
    uint32_t ok;
    asm volatile("{\n.reg .pred p;\nmbarrier.try_wait.parity.shared::cta.b64 p, [%1], %2;\nselp.u32 %0, 1, 0, p;\n}"
                 : "=r"(ok) : "r"(bar), "r"(parity) : "memory");
    return ok != 0;
}
constexpr uint32_t SPIN_LIMIT = 1u << 22;
__device__ __forceinline__ void mbar_wait(uint32_t bar, uint32_t parity) {
    uint32_t it = 0;
    while (!mbar_try(bar, parity)) { if (++it > SPIN_LIMIT) __trap(); }
}
__device__ __forceinline__ void tma3d(uint32_t dst, const CUtensorMap* m, int c0, int c1, int c2, uint32_t bar, uint64_t pol) {
    asm volatile("cp.async.bulk.tensor.3d.shared::cluster.global.mbarrier::complete_tx::bytes.L2::cache_hint [%0], [%1, {%3, %4, %5}], [%2], %6;"
                 ::"r"(dst), "l"(m), "r"(bar), "r"(c0), "r"(c1), "r"(c2), "l"(pol) : "memory");
}
__device__ __forceinline__ void tma3d_prefetch(const CUtensorMap* m, int c0, int c1, int c2) {
    asm volatile("cp.async.bulk.prefetch.tensor.3d.L2.global.tile [%0, {%1, %2, %3}];" ::"l"(m), "r"(c0), "r"(c1), "r"(c2) : "memory");
}
__device__ __forceinline__ void ldsm4(uint32_t (&r)[4], uint32_t addr) {
    asm volatile("ldmatrix.sync.aligned.m8n8.x4.shared.b16 {%0,%1,%2,%3}, [%4];"
                 : "=r"(r[0]), "=r"(r[1]), "=r"(r[2]), "=r"(r[3]) : "r"(addr) : "memory");
}
__device__ __forceinline__ void ldsm4t(uint32_t (&r)[4], uint32_t addr) {
    asm volatile("ldmatrix.sync.aligned.m8n8.x4.trans.shared.b16 {%0,%1,%2,%3}, [%4];"
                 : "=r"(r[0]), "=r"(r[1]), "=r"(r[2]), "=r"(r[3]) : "r"(addr) : "memory");
}
__device__ __forceinline__ void mma16816(float (&c)[4], const uint32_t (&a)[4], uint32_t b0, uint32_t b1) {
    asm volatile("mma.sync.aligned.m16n8k16.row.col.f32.bf16.bf16.f32 {%0,%1,%2,%3}, {%4,%5,%6,%7}, {%8,%9}, {%0,%1,%2,%3};"
                 : "+f"(c[0]), "+f"(c[1]), "+f"(c[2]), "+f"(c[3])
                 : "r"(a[0]), "r"(a[1]), "r"(a[2]), "r"(a[3]), "r"(b0), "r"(b1));
}
__device__ __forceinline__ void cbar() { asm volatile("bar.sync 1, 256;" ::: "memory"); }
__device__ __forceinline__ void bar_sync(int id, int n) { asm volatile("bar.sync %0, %1;" ::"r"(id), "r"(n) : "memory"); }
__device__ __forceinline__ void bar_arrive(int id, int n) { asm volatile("bar.arrive %0, %1;" ::"r"(id), "r"(n) : "memory"); }
__device__ __forceinline__ uint4 ld_poll4(const void* p) {
    uint4 v;
    asm volatile("ld.relaxed.gpu.global.v4.u32 {%0,%1,%2,%3}, [%4];" : "=r"(v.x), "=r"(v.y), "=r"(v.z), "=r"(v.w) : "l"(p) : "memory");
    return v;
}
__device__ __forceinline__ uint2 ld_poll2(const void* p) {
    uint2 v;
    asm volatile("ld.relaxed.gpu.global.v2.u32 {%0,%1}, [%2];" : "=r"(v.x), "=r"(v.y) : "l"(p) : "memory");
    return v;
}
__device__ __forceinline__ void st_rel32(void* p, uint32_t v) { asm volatile("st.relaxed.gpu.global.u32 [%0], %1;" ::"l"(p), "r"(v) : "memory"); }
__device__ __forceinline__ void st_rel16(void* p, uint16_t v) { asm volatile("st.relaxed.gpu.global.u16 [%0], %1;" ::"l"(p), "h"(v) : "memory"); }
__device__ __forceinline__ void st_rel64(void* p, uint32_t a, uint32_t b) { asm volatile("st.relaxed.gpu.global.v2.u32 [%0], {%1,%2};" ::"l"(p), "r"(a), "r"(b) : "memory"); }
__device__ __forceinline__ void st_rel128(void* p, uint32_t v) { asm volatile("st.relaxed.gpu.global.v4.u32 [%0], {%1,%1,%1,%1};" ::"l"(p), "r"(v) : "memory"); }
__device__ __forceinline__ uint32_t umax4(const uint4& v) { return max(max(v.x, v.y), max(v.z, v.w)); }
template <class T> __device__ __forceinline__ void pin(T*& p) { asm volatile("" : "+l"(p)); }
__device__ __forceinline__ bool valid8h(const uint4& v) {
    return (__vcmpeq2(v.x, SENT) | __vcmpeq2(v.y, SENT) | __vcmpeq2(v.z, SENT) | __vcmpeq2(v.w, SENT)) == 0;
}
struct Spin {
    uint32_t it = 0;
    __device__ __forceinline__ void tick() { if (++it > SPIN_LIMIT) __trap(); }
};
__device__ __forceinline__ uint32_t pack_bf16(float lo, float hi) {
    uint32_t r; asm("cvt.rn.bf16x2.f32 %0, %1, %2;" : "=r"(r) : "f"(hi), "f"(lo)); return r;
}
__device__ __forceinline__ void delay_cycles(int n) { if (n > 0) { const long long t0 = clock64(); while (clock64() - t0 < n) {} } }
__device__ __forceinline__ float bf16r(float x) { return __uint_as_float(pack_bf16(0.f, x) & 0xFFFF0000u); }
__device__ __forceinline__ float bf_lo(uint32_t v) { return __uint_as_float(v << 16); }
__device__ __forceinline__ float bf_hi(uint32_t v) { return __uint_as_float(v & 0xFFFF0000u); }
__device__ __forceinline__ uint32_t hmax2(uint32_t a, uint32_t b) {
    uint32_t r; asm("max.bf16x2 %0, %1, %2;" : "=r"(r) : "r"(a), "r"(b)); return r;
}
__device__ __forceinline__ float ex2(float x) { float r; asm("ex2.approx.ftz.f32 %0, %1;" : "=f"(r) : "f"(x)); return r; }

__device__ __forceinline__ float2 ln_stats(const uint4& a, const uint4& b, float (&v)[16]) {
    v[0] = bf_lo(a.x); v[1] = bf_hi(a.x); v[2] = bf_lo(a.y); v[3] = bf_hi(a.y);
    v[4] = bf_lo(a.z); v[5] = bf_hi(a.z); v[6] = bf_lo(a.w); v[7] = bf_hi(a.w);
    v[8] = bf_lo(b.x); v[9] = bf_hi(b.x); v[10] = bf_lo(b.y); v[11] = bf_hi(b.y);
    v[12] = bf_lo(b.z); v[13] = bf_hi(b.z); v[14] = bf_lo(b.w); v[15] = bf_hi(b.w);
    const float shift = __shfl_sync(0xffffffffu, v[0], 0);
    float s0 = 0.f, s1 = 0.f, s2 = 0.f, s3 = 0.f, q0 = 0.f, q1 = 0.f, q2 = 0.f, q3 = 0.f;
#pragma unroll
    for (int i = 0; i < 16; i += 4) {
        const float d0 = v[i] - shift, d1 = v[i + 1] - shift, d2 = v[i + 2] - shift, d3 = v[i + 3] - shift;
        s0 += d0; s1 += d1; s2 += d2; s3 += d3;
        q0 = fmaf(d0, d0, q0); q1 = fmaf(d1, d1, q1); q2 = fmaf(d2, d2, q2); q3 = fmaf(d3, d3, q3);
    }
    float s = (s0 + s1) + (s2 + s3), ss = (q0 + q1) + (q2 + q3);
#pragma unroll
    for (int o = 16; o > 0; o >>= 1) { s += __shfl_xor_sync(0xffffffffu, s, o); ss += __shfl_xor_sync(0xffffffffu, ss, o); }
    const float md = s * (1.0f / 512.0f);
    const float var = fmaxf(ss * (1.0f / 512.0f) - md * md, 0.f);
    const float m = bf16r(shift + md);
    float sq; asm("sqrt.approx.f32 %0, %1;" : "=f"(sq) : "f"(bf16r(bf16r(var) + 1e-5f)));
    const float sd = bf16r(sq);
    return make_float2(m, __fdividef(1.0f, sd));
}

struct Maps { CUtensorMap m[8]; };

__global__ void __launch_bounds__(NTHREADS, 1)
fused_decode_kernel(const __grid_constant__ Maps maps, const unsigned char* __restrict__ kraw, const unsigned char* __restrict__ vraw,
                    const __nv_bfloat16* __restrict__ x, __nv_bfloat16* __restrict__ out)
{
    extern __shared__ __align__(1024) unsigned char smem_raw[];
    unsigned char* smem = smem_raw + ((1024u - (smem_u32(smem_raw) & 1023u)) & 1023u);
    const uint32_t sbase = smem_u32(smem);
    const uint32_t bar_full = sbase + OFF_BAR, bar_empty = sbase + OFF_BAR + 48, bar_ready = sbase + OFF_BAR + 96, bar_w = sbase + OFF_BAR + 104, bar_vl = sbase + OFF_BAR + 152;
    volatile unsigned* vars = reinterpret_cast<volatile unsigned*>(smem + OFF_VAR);
    const int tid = threadIdx.x, warp = tid >> 5, lane = tid & 31;
    const int cta = blockIdx.x;

    if (tid == 0) TSG(0);
    if (warp == 8) {
        if (lane == 0) {
            const size_t off = (size_t)cta * (NTILE * 128) * 256;
#pragma unroll
            for (int i = 0; i < EARLY_PF; i++)
                asm volatile("cp.async.bulk.prefetch.L2.global [%0], %1;" ::"l"(((i & 1) ? vraw : kraw) + off + (i >> 1) * 32768), "r"(32768) : "memory");
            for (int i = 0; i < NSLOT; i++) { mbar_init(bar_full + 8 * i, 1); mbar_init(bar_empty + 8 * i, 8); }
            mbar_init(bar_ready, 1);
            for (int i = 0; i < 6; i++) mbar_init(bar_w + 8 * i, 1);
            for (int i = 0; i < 4; i++) mbar_init(bar_vl + 8 * i, 1);
            vars[1] = 0;
            asm volatile("fence.mbarrier_init.release.cluster;" ::: "memory");
        } else if (lane <= 8) {
            asm volatile("prefetch.tensormap [%0];" ::"l"(&maps.m[lane - 1]) : "memory");
        }
    }
    __syncthreads();

    if (warp == 8) {
        if (lane == 0) {
            uint64_t pol_first, pol_norm;
            asm volatile("createpolicy.fractional.L2::evict_first.b64 %0, 1.0;" : "=l"(pol_first));
            asm volatile("createpolicy.fractional.L2::evict_normal.b64 %0, 1.0;" : "=l"(pol_norm));
            const int key0 = cta * (NTILE * 128);
            int arrived = 0;
            unsigned grel = 0;
            int nkv = 0;
            for (int i = 0; i < NSEQ; i++) {
                const int slot = i % NSLOT;
                const bool is_w = (i == 0) || (i == SEQ_WO);
                if (i >= NSLOT) mbar_wait(bar_empty + 8 * slot, ((i / NSLOT) - 1) & 1);
                const int lead8 = (nkv * NCTA - (int)grel) / (NCTA / 8);
                const int d = (i <= 2) ? DEPTH_INIT : ((lead8 > LEAD_THR8) ? DEPTH_LO : DEPTH_HI);
                while (arrived < i - d + 1) { mbar_wait(bar_full + 8 * (arrived % NSLOT), (arrived / NSLOT) & 1); arrived++; }
                if (i == SEQ_WO && (int)grel < NCTA * 32 - WO_MARGIN) {
                    Spin sp; unsigned v;
                    while (true) {
                        asm volatile("ld.relaxed.gpu.global.u32 %0, [%1];" : "=r"(v) : "l"(&g_prog) : "memory");
                        if ((int)v >= NCTA * 32 - WO_MARGIN) break;
                        sp.tick(); __nanosleep(64);
                    }
                }
                const uint32_t dst = sbase + slot * SLOT, fb = bar_full + 8 * slot;
                int mi, c0 = 0, c1 = 0, c2 = 0, nbox = 1;
                if (i == 0)            { mi = 2; c0 = cta * 32; nbox = 2; }
                else if (i == SEQ_WO)  { mi = 3; c1 = (cta >> 2) * 128; c2 = (cta & 3) * 2; }
                else                   { mi = nkv & 1; c1 = key0 + (nkv >> 1) * 128; }
                if (VSPLIT && !is_w && nkv == 31) {
                    for (int j = 0; j < 4; j++) {
                        mbar_expect_tx(bar_vl + 8 * j, 8192);
                        tma3d(dst + j * 8192, &maps.m[7], 0, c1 + j * 32, 0, bar_vl + 8 * j, pol_first);
                    }
                } else {
                    mbar_expect_tx(fb, 32768);
                    for (int j = 0; j < nbox; j++) tma3d(dst + j * 16384, &maps.m[mi], c0, c1 + j * 256, c2, fb, is_w ? pol_norm : pol_first);
                }
                if (!is_w) {
                    if (nkv < 31) {
                        grel = atomicAdd(&g_prog, 1u);
                    } else {
                        asm volatile("red.relaxed.gpu.global.add.u32 [%0], 1;" ::"l"(&g_prog) : "memory");
                    }
                    nkv++;
                }
            }
            if (cta < NFFN) {
                mbar_wait(bar_empty + 8 * SLOT_WGU, (34 / NSLOT - 1) & 1);
                mbar_wait(bar_empty + 8 * SLOT_WD, (35 / NSLOT - 1) & 1);
                if ((int)grel < NCTA * 32 - GATE_MARGIN) {
                    Spin sp; unsigned v;
                    while (true) {
                        asm volatile("ld.relaxed.gpu.global.u32 %0, [%1];" : "=r"(v) : "l"(&g_prog) : "memory");
                        if ((int)v >= NCTA * 32 - GATE_MARGIN) break;
                        sp.tick(); __nanosleep(64);
                    }
                }
                mbar_wait(bar_full + 8 * (SEQ_WO % NSLOT), (SEQ_WO / NSLOT) & 1);
                TSX(26, true);
                for (int k = 0; k < 6; k++) {
                    if (k >= WDEPTH) mbar_wait(bar_w + 8 * (k - WDEPTH), 0);
                    mbar_expect_tx(bar_w + 8 * k, 8192);
                    const int mi = (k < 4) ? 4 + (k >> 1) : 6;
                    const int c0 = (k < 4) ? cta * 16 : 0, c1 = (k < 4) ? (k & 1) * 256 : cta * 16, c2 = (k < 4) ? 0 : (k - 4) * 4;
                    tma3d(sbase + SLOT_WGU * SLOT + k * 8192, &maps.m[mi], c0, c1, c2, bar_w + 8 * k, pol_norm);
                }
            }
            TSX(20, true);
        }
        return;
    }

    const int pair = cta >> 2, split = cta & 3;

    if (warp == 9) {
        Spin sp;
        while (vars[1] < RESET_TILE) { sp.tick(); __nanosleep(256); }
        const unsigned epoch = vars[0];
#pragma unroll 1
        for (int u = lane; u < 128; u += 32) {
            st_rel128(&g_partO[((pair * 4 + (u >> 5)) * 4 + split) * 128 + (u & 31) * 4], SENT);
            const int seg = u >> 2;
            st_rel128(&g_ypart[(((seg >> 3) * 32 + (cta & 3) * 8 + (seg & 7)) * 32 + (cta >> 2)) * 16 + (u & 3) * 4], SENT);
        }
        if (lane < 4) st_rel64(&g_ml[(pair * 4 + lane) * 4 + split], SENT, SENT);
        if (lane < 2) st_rel128(&g_h[(cta >> 5) * 512 + (cta & 31) * 16 + lane * 8], SENT);
        if (cta < NFFN) {
#pragma unroll 1
            for (int e = lane; e < 512; e += 32) st_rel128(&g_dpart[((e >> 2) * NFFN + cta) * 16 + (e & 3) * 4], SENT);
        }
        __threadfence();
        __syncwarp();
        if (lane == 0) {
            atomicAdd(&g_cnt1, 1u);
            unsigned v; Spin sp2;
            while (true) {
                asm volatile("ld.acquire.gpu.global.u32 %0, [%1];" : "=r"(v) : "l"(&g_cnt1) : "memory");
                if ((int)(v - (epoch + 1) * NCTA) >= 0) break;
                sp2.tick(); __nanosleep(128);
            }
            mbar_arrive(bar_ready);
        }
        TSX(24, lane == 0);
        return;
    }

    const int r8 = lane >> 2, q4 = lane & 3;
    const int hp = q4 & 1, kh = q4 >> 1;
    constexpr float LOG2E = 1.4426950408889634f;
    const int bq = pair >> 3, gq = pair & 7;

    if (tid == 0) vars[0] = atomicAdd(&g_cnt0, 1u) >> 7;
    if (warp == 7) st_rel128(&g_q[(lane >> 3) * 2048 + cta * 16 + (lane & 7) * 2], 0u);
    float xres = 0.f;
    if (warp == 0) xres = __bfloat162float(x[(cta >> 5) * 512 + (cta & 31) * 16 + (lane >> 1)]);

    if (warp < 4) {
        const uint4* xr = reinterpret_cast<const uint4*>(x + warp * 512);
        const uint4 a = __ldg(xr + lane), b = __ldg(xr + 32 + lane);
        float v[16];
        const float2 st = ln_stats(a, b, v);
        uint32_t o[8];
#pragma unroll
        for (int i = 0; i < 8; i++) o[i] = pack_bf16(bf16r(v[2 * i] - st.x) * st.y, bf16r(v[2 * i + 1] - st.x) * st.y);
        unsigned char* row = smem + OFF_XN + warp * XN_PITCH;
        *reinterpret_cast<uint4*>(row + lane * 16) = make_uint4(o[0], o[1], o[2], o[3]);
        *reinterpret_cast<uint4*>(row + 512 + lane * 16) = make_uint4(o[4], o[5], o[6], o[7]);
    }
    cbar();
    const uint32_t tag = vars[0] + 1;

    {
        uint32_t bfr[4][2];
        {
            uint32_t t4[4];
#pragma unroll
            for (int u = 0; u < 2; u++) {
                ldsm4(t4, sbase + OFF_XN + (lane & 3) * XN_PITCH + (8 * warp + 4 * u + (lane >> 3)) * 16);
                bfr[2 * u][0] = t4[0]; bfr[2 * u][1] = t4[1]; bfr[2 * u + 1][0] = t4[2]; bfr[2 * u + 1][1] = t4[3];
            }
        }
        mbar_wait(bar_full + 0, 0);
        TS(2);
        float acc[2][4] = {};
#pragma unroll
        for (int ks = 0; ks < 4; ks++) {
            const int k = 64 * warp + 16 * ks + (lane & 7) + (lane >> 4) * 8;
#pragma unroll
            for (int mt = 0; mt < 2; mt++) {
                uint32_t a[4];
                const int chunk = 2 * mt + ((lane >> 3) & 1);
                ldsm4t(a, sbase + k * 64 + ((chunk ^ ((k >> 1) & 3)) << 4));
                mma16816(acc[mt], a, bfr[ks][0], bfr[ks][1]);
            }
        }
        __syncwarp();
        if (lane == 0) mbar_arrive(bar_empty + 0);
        float* red = reinterpret_cast<float*>(smem + OFF_RED);
#pragma unroll
        for (int mt = 0; mt < 2; mt++) {
            float2 v = kh ? make_float2(acc[mt][2], acc[mt][3]) : make_float2(acc[mt][0], acc[mt][1]);
            *reinterpret_cast<float2*>(red + ((warp * 2 + mt) * 16 + r8 + 8 * kh) * 4 + 2 * hp) = v;
        }
        cbar();
        if (tid < 64) {
            const int b = tid >> 4, c2 = tid & 15;
            float s0 = 0.f, s1 = 0.f;
            const int c0 = 2 * c2, c1 = 2 * c2 + 1;
#pragma unroll
            for (int ww = 0; ww < 8; ww++) {
                s0 += red[((ww * 2 + (c0 >> 4)) * 16 + (c0 & 15)) * 4 + b];
                s1 += red[((ww * 2 + (c1 >> 4)) * 16 + (c1 & 15)) * 4 + b];
            }
            st_rel64(&g_q[b * 2048 + cta * 16 + c2], pack_bf16(s0, s1), tag);
        }
        {
            const uint2* src = &g_q[bq * 2048 + gq * 256 + tid];
            uint2 v;
            Spin sp;
            while (true) { v = ld_poll2(src); if (__all_sync(0xffffffffu, v.y == tag)) break; sp.tick(); }
            *reinterpret_cast<uint32_t*>(smem + OFF_QS + (tid >> 6) * QS_PITCH + (tid & 63) * 4) = v.x;
        }
        cbar();
    }
    TS(3);
    uint32_t qf[8][2];
    {
        uint32_t t4[4];
#pragma unroll
        for (int u = 0; u < 4; u++) {
            ldsm4(t4, sbase + OFF_QS + (lane & 3) * QS_PITCH + (4 * u + (lane >> 3)) * 16);
            qf[2 * u][0] = t4[0]; qf[2 * u][1] = t4[1]; qf[2 * u + 1][0] = t4[2]; qf[2 * u + 1][1] = t4[3];
        }
    }

    const uint32_t voff = (warp >> 2) * 16384 + ((lane & 7) + (lane >> 4) * 8) * 128 +
                          ((((2 * warp + ((lane >> 3) & 1)) & 7) ^ (lane & 7)) << 4);
    const uint32_t poff = sbase + OFF_P + (lane & 3) * QS_PITCH + (lane >> 3) * 16;
    const uint32_t koff = (16 * warp + (lane & 7) + ((lane >> 3) & 1) * 8) * 128;
    const uint32_t kx = lane & 7, kc = lane >> 4;
    constexpr float SCALE = 0.08838834764831845f;
    uint32_t* mxbuf = reinterpret_cast<uint32_t*>(smem + OFF_MX);
    uint32_t M2 = 0xFF80FF80u;
    float l0 = 0.f, l1 = 0.f;
    float oacc[2][4] = {};
    int slot = 1; uint32_t ph = 0;

    for (int t = 0;; t++) {
        mbar_wait(bar_full + 8 * slot, ph);
        float sa[4] = {}, sb[4] = {};
        {
            const uint32_t kb = sbase + slot * SLOT + koff;
#pragma unroll
            for (int ks = 0; ks < 8; ks++) {
                uint32_t a[4];
                ldsm4(a, kb + (ks >> 2) * 16384 + (((2 * (ks & 3) + kc) ^ kx) << 4));
                if (ks & 1) mma16816(sb, a, qf[ks][0], qf[ks][1]); else mma16816(sa, a, qf[ks][0], qf[ks][1]);
            }
        }
        __syncwarp();
        if (lane == 0) mbar_arrive(bar_empty + 8 * slot);
        if (++slot == NSLOT) { slot = 0; ph ^= 1; }

        const float r0 = kh ? sa[2] + sb[2] : sa[0] + sb[0];
        const float r1 = kh ? sa[3] + sb[3] : sa[1] + sb[1];
        uint32_t sp = pack_bf16(r0, r1);
        sp = pack_bf16(bf_lo(sp) * SCALE, bf_hi(sp) * SCALE);
        uint32_t mx = sp;
#pragma unroll
        for (int o = 2; o <= 16; o <<= 1) mx = hmax2(mx, __shfl_xor_sync(0xffffffffu, mx, o));
        if (lane < 2) mxbuf[lane * 8 + warp] = mx;
        if (tid == 0) vars[1] = t + 1;
        TS(40 + t);
        cbar();
        {
            const uint4 m0 = *reinterpret_cast<const uint4*>(mxbuf + hp * 8), m1 = *reinterpret_cast<const uint4*>(mxbuf + hp * 8 + 4);
            uint32_t mt = hmax2(hmax2(hmax2(m0.x, m0.y), hmax2(m0.z, m0.w)), hmax2(hmax2(m1.x, m1.y), hmax2(m1.z, m1.w)));
            const uint32_t Mn = hmax2(M2, mt);
            const float a0 = ex2((bf_lo(M2) - bf_lo(Mn)) * LOG2E), a1 = ex2((bf_hi(M2) - bf_hi(Mn)) * LOG2E);
            const float p0 = ex2((bf_lo(sp) - bf_lo(Mn)) * LOG2E), p1 = ex2((bf_hi(sp) - bf_hi(Mn)) * LOG2E);
            M2 = Mn;
            l0 = fmaf(l0, a0, p0); l1 = fmaf(l1, a1, p1);
            const uint32_t pp = pack_bf16(p0, p1);
            unsigned char* pd = smem + OFF_P + (2 * hp) * QS_PITCH + (16 * warp + r8 + 8 * kh) * 2;
            *reinterpret_cast<uint16_t*>(pd) = (uint16_t)(pp & 0xFFFF);
            *reinterpret_cast<uint16_t*>(pd + QS_PITCH) = (uint16_t)(pp >> 16);
#pragma unroll
            for (int c = 0; c < 2; c++) { oacc[c][0] *= a0; oacc[c][1] *= a1; oacc[c][2] *= a0; oacc[c][3] *= a1; }
        }
        if (t == NTILE - 1) break;
        cbar();
        uint32_t pb[8][2];
        {
            uint32_t t4[4];
#pragma unroll
            for (int u = 0; u < 4; u++) {
                ldsm4(t4, poff + u * 64);
                pb[2 * u][0] = t4[0]; pb[2 * u][1] = t4[1]; pb[2 * u + 1][0] = t4[2]; pb[2 * u + 1][1] = t4[3];
            }
        }
        mbar_wait(bar_full + 8 * slot, ph);
        {
            const uint32_t vb = sbase + slot * SLOT + voff;
#pragma unroll
            for (int ks = 0; ks < 8; ks++) {
                uint32_t a[4];
                ldsm4t(a, vb + ks * 2048);
                mma16816(oacc[ks & 1], a, pb[ks][0], pb[ks][1]);
            }
        }
        __syncwarp();
        if (lane == 0) mbar_arrive(bar_empty + 8 * slot);
        if (++slot == NSLOT) { slot = 0; ph ^= 1; }
        if (SEQ_WO == 31 && t == NTILE - 2) { if (++slot == NSLOT) { slot = 0; ph ^= 1; } }
    }

    const int head = cta >> 2;
    float* p_partO = &g_partO[((pair * 4 + 2 * hp) * 4 + split) * 128 + 16 * warp + r8 + 8 * kh];
    float* p_dpart = &g_dpart[(((2 * hp) * 32 + 4 * warp) * NFFN + cta) * 16 + r8 + 8 * kh];
    const float* p_dsrc = &g_dpart[(cta * NFFN + (tid >> 2)) * 16 + (tid & 3) * 4];
    __nv_bfloat16* p_out = out + (cta >> 5) * 512 + (cta & 31) * 16 + (lane >> 1);
    pin(p_partO); pin(p_dpart); pin(p_dsrc); pin(p_out);

    {
        float s0 = l0, s1 = l1;
#pragma unroll
        for (int o = 2; o <= 16; o <<= 1) { s0 += __shfl_xor_sync(0xffffffffu, s0, o); s1 += __shfl_xor_sync(0xffffffffu, s1, o); }
        if (lane < 2) *reinterpret_cast<float2*>(smem + OFF_L + warp * 16 + lane * 8) = make_float2(s0, s1);
        mbar_wait(bar_ready, 0);
        cbar();
        if (warp == 0) {
            const uint32_t other = __shfl_sync(0xffffffffu, M2, lane >> 1);
            float l = 0.f;
#pragma unroll
            for (int ww = 0; ww < 8; ww++) l += *reinterpret_cast<const float*>(smem + OFF_L + ww * 16 + (lane & 3) * 4);
            const float m = (lane & 1) ? bf_hi(other) : bf_lo(other);
            if (lane < 4) st_rel64(&g_ml[(pair * 4 + lane) * 4 + split], __float_as_uint(m), __float_as_uint(l));
        }
        uint32_t pb[8][2];
        {
            uint32_t t4[4];
#pragma unroll
            for (int u = 0; u < 4; u++) {
                ldsm4(t4, poff + u * 64);
                pb[2 * u][0] = t4[0]; pb[2 * u][1] = t4[1]; pb[2 * u + 1][0] = t4[2]; pb[2 * u + 1][1] = t4[3];
            }
        }
        float o2[2][4] = {};
        if (VSPLIT) {
            const uint32_t vb = sbase + slot * SLOT + (warp >> 2) * 4096 + ((lane & 7) + (lane >> 4) * 8) * 128 +
                                ((((2 * warp + ((lane >> 3) & 1)) & 7) ^ (lane & 7)) << 4);
#pragma unroll
            for (int p = 0; p < 4; p++) {
                uint32_t a0[4], a1[4];
                mbar_wait(bar_vl + 8 * p, 0);
                if (p == 3) { TS(30); }
                ldsm4t(a0, vb + p * 8192);
                ldsm4t(a1, vb + p * 8192 + 2048);
                mma16816((p & 1) ? o2[0] : oacc[0], a0, pb[2 * p][0], pb[2 * p][1]);
                mma16816((p & 1) ? o2[1] : oacc[1], a1, pb[2 * p + 1][0], pb[2 * p + 1][1]);
            }
        } else {
            mbar_wait(bar_full + 8 * slot, ph);
            TS(30);
            const uint32_t vb = sbase + slot * SLOT + voff;
            uint32_t a[8][4];
#pragma unroll
            for (int ks = 0; ks < 8; ks++) ldsm4t(a[ks], vb + ks * 2048);
#pragma unroll
            for (int ks = 0; ks < 8; ks++) mma16816((ks & 2) ? o2[ks & 1] : oacc[ks & 1], a[ks], pb[ks][0], pb[ks][1]);
        }
        const float v0 = kh ? (oacc[0][2] + oacc[1][2]) + (o2[0][2] + o2[1][2]) : (oacc[0][0] + oacc[1][0]) + (o2[0][0] + o2[1][0]);
        const float v1 = kh ? (oacc[0][3] + oacc[1][3]) + (o2[0][3] + o2[1][3]) : (oacc[0][1] + oacc[1][1]) + (o2[0][1] + o2[1][1]);
        st_rel32(p_partO, __float_as_uint(v0));
        st_rel32(p_partO + 512, __float_as_uint(v1));
        TS(4);
    }

    float hres = 0.f;
    uint32_t df[4][4];
    if (warp < 4) {
        {
            const int ph_idx = (warp * 8 + (head >> 2)) * 4 + (head & 3);
            const float* po = &g_partO[ph_idx * 512 + lane * 4];
            const float* pm = reinterpret_cast<const float*>(&g_ml[ph_idx * 4]);
            uint4 o0, o1, o2, o3, ma, mb;
            Spin sp;
            while (true) {
                o0 = ld_poll4(po); o1 = ld_poll4(po + 128); o2 = ld_poll4(po + 256); o3 = ld_poll4(po + 384);
                ma = ld_poll4(pm); mb = ld_poll4(pm + 4);
                const uint32_t mxv = max(max(max(umax4(o0), umax4(o1)), max(umax4(o2), umax4(o3))), max(umax4(ma), umax4(mb)));
                if (__all_sync(0xffffffffu, mxv != SENT)) break;
                sp.tick();
            }
            TS(6);
            const float m0 = __uint_as_float(ma.x), m1 = __uint_as_float(ma.z), m2 = __uint_as_float(mb.x), m3 = __uint_as_float(mb.z);
            const float M = fmaxf(fmaxf(m0, m1), fmaxf(m2, m3));
            float w0 = ex2((m0 - M) * LOG2E), w1 = ex2((m1 - M) * LOG2E), w2 = ex2((m2 - M) * LOG2E), w3 = ex2((m3 - M) * LOG2E);
            const float L = w0 * __uint_as_float(ma.y) + w1 * __uint_as_float(ma.w) + w2 * __uint_as_float(mb.y) + w3 * __uint_as_float(mb.w);
            const float inv = __fdividef(1.0f, L);
            const float e0 = (w0 * __uint_as_float(o0.x) + w1 * __uint_as_float(o1.x) + w2 * __uint_as_float(o2.x) + w3 * __uint_as_float(o3.x)) * inv;
            const float e1 = (w0 * __uint_as_float(o0.y) + w1 * __uint_as_float(o1.y) + w2 * __uint_as_float(o2.y) + w3 * __uint_as_float(o3.y)) * inv;
            const float e2 = (w0 * __uint_as_float(o0.z) + w1 * __uint_as_float(o1.z) + w2 * __uint_as_float(o2.z) + w3 * __uint_as_float(o3.z)) * inv;
            const float e3 = (w0 * __uint_as_float(o0.w) + w1 * __uint_as_float(o1.w) + w2 * __uint_as_float(o2.w) + w3 * __uint_as_float(o3.w)) * inv;
            *reinterpret_cast<uint2*>(smem + OFF_QS + warp * QS_PITCH + lane * 8) = make_uint2(pack_bf16(e0, e1), pack_bf16(e2, e3));
            TSD(31, tid == 0, e0 + e1 + e2 + e3);
            bar_arrive(2, 256);
        }
        if (warp == 0) {
            const float* src = &g_ypart[(cta * 32 + lane) * 16];
            uint16_t* p_h = &g_h[(cta >> 5) * 512 + (cta & 31) * 16 + (lane >> 1)];
            pin(p_h);
            delay_cycles(DLY2);
            uint4 y0, y1, y2, y3;
            Spin sp;
            while (true) {
                y0 = ld_poll4(src); y1 = ld_poll4(src + 4); y2 = ld_poll4(src + 8); y3 = ld_poll4(src + 12);
                if (__all_sync(0xffffffffu, max(max(umax4(y0), umax4(y1)), max(umax4(y2), umax4(y3))) != SENT)) break;
                sp.tick();
            }
            TS(9);
            float v0, v1, v2, v3, v4, v5, v6, v7;
            {
                const bool up = lane & 16;
#define RSTEP(dst, lo, hi, m) { const float _l = __uint_as_float(lo), _h = __uint_as_float(hi); dst = (up ? _h : _l) + __shfl_xor_sync(0xffffffffu, up ? _l : _h, m); }
                RSTEP(v0, y0.x, y2.x, 16) RSTEP(v1, y0.y, y2.y, 16) RSTEP(v2, y0.z, y2.z, 16) RSTEP(v3, y0.w, y2.w, 16)
                RSTEP(v4, y1.x, y3.x, 16) RSTEP(v5, y1.y, y3.y, 16) RSTEP(v6, y1.z, y3.z, 16) RSTEP(v7, y1.w, y3.w, 16)
#undef RSTEP
            }
#define RSTEP(dst, a, b, m) { const bool _u = lane & m; dst = (_u ? b : a) + __shfl_xor_sync(0xffffffffu, _u ? a : b, m); }
            RSTEP(v0, v0, v4, 8) RSTEP(v1, v1, v5, 8) RSTEP(v2, v2, v6, 8) RSTEP(v3, v3, v7, 8)
            RSTEP(v0, v0, v2, 4) RSTEP(v1, v1, v3, 4)
            RSTEP(v0, v0, v1, 2)
#undef RSTEP
            v0 += __shfl_xor_sync(0xffffffffu, v0, 1);
            hres = bf16r(xres + bf16r(v0));
            if (!(lane & 1)) st_rel16(p_h, (uint16_t)(__float_as_uint(hres) >> 16));
            TS(10);
        }
        if (cta < NFFN) {
            bar_sync(7, 128);
            const uint4* hr = reinterpret_cast<const uint4*>(g_h + warp * 512);
            delay_cycles(DLY3);
            uint4 a, b;
            Spin sp;
            while (true) {
                a = ld_poll4(hr + lane); b = ld_poll4(hr + 32 + lane);
                const bool ok = (__vcmpeq2(a.x, SENT) | __vcmpeq2(a.y, SENT) | __vcmpeq2(a.z, SENT) | __vcmpeq2(a.w, SENT) |
                                 __vcmpeq2(b.x, SENT) | __vcmpeq2(b.y, SENT) | __vcmpeq2(b.z, SENT) | __vcmpeq2(b.w, SENT)) == 0;
                if (__all_sync(0xffffffffu, ok)) break;
                sp.tick();
            }
            TS(13);
            unsigned char* row = smem + OFF_XN + warp * XN_PITCH;
            *reinterpret_cast<uint4*>(row + lane * 16) = a;
            *reinterpret_cast<uint4*>(row + 512 + lane * 16) = b;
            bar_arrive(3, 256);
            float v[16];
            const float2 st = ln_stats(a, b, v);
            if (lane == 0) *reinterpret_cast<float2*>(smem + OFF_ST + warp * 8) = st;
            bar_arrive(4, 256);
            TS(14);
            mbar_wait(bar_w + 32, 0); mbar_wait(bar_w + 40, 0);
            const uint32_t wb = sbase + SLOT_WD * SLOT + warp * 2048 + ((lane & 7) + (lane >> 4) * 8) * 128;
#pragma unroll
            for (int i = 0; i < 4; i++) ldsm4t(df[i], wb + (((2 * i + ((lane >> 3) & 1)) ^ (lane & 7)) << 4));
        }
    } else {
        const int m = warp - 4;
        {
            uint32_t af[2][8][4];
            float* p_y = &g_ypart[(((2 * hp) * 32 + (cta & 3) * 8 + 2 * m) * 32 + head) * 16 + r8 + 8 * kh];
            pin(p_y);
            mbar_wait(bar_full + 8 * (SEQ_WO % NSLOT), (SEQ_WO / NSLOT) & 1);
#pragma unroll
            for (int i = 0; i < 2; i++) {
                const int j = 2 * m + i;
                const uint32_t wb = sbase + (SEQ_WO % NSLOT) * SLOT + (j >> 2) * 16384 + ((lane & 7) + (lane >> 4) * 8) * 128 +
                                    ((((2 * j + ((lane >> 3) & 1)) & 7) ^ (lane & 7)) << 4);
#pragma unroll
                for (int ks = 0; ks < 8; ks++) ldsm4t(af[i][ks], wb + ks * 2048);
            }
            TSX(5, tid == 128);
            bar_sync(2, 256);
            TSX(7, tid == 128);
            float acc[2][2][4] = {};
            uint32_t t4[4][4];
#pragma unroll
            for (int u = 0; u < 4; u++) ldsm4(t4[u], sbase + OFF_QS + (lane & 3) * QS_PITCH + (4 * u + (lane >> 3)) * 16);
            TSD(37, tid == 128, __uint_as_float(t4[0][0]));
#pragma unroll
            for (int u = 0; u < 4; u++) {
#pragma unroll
                for (int i = 0; i < 2; i++) {
                    mma16816(acc[i][0], af[i][2 * u], t4[u][0], t4[u][1]);
                    mma16816(acc[i][1], af[i][2 * u + 1], t4[u][2], t4[u][3]);
                }
            }
#pragma unroll
            for (int i = 0; i < 2; i++) {
                const float v0 = kh ? acc[i][0][2] + acc[i][1][2] : acc[i][0][0] + acc[i][1][0];
                const float v1 = kh ? acc[i][0][3] + acc[i][1][3] : acc[i][0][1] + acc[i][1][1];
                st_rel32(p_y + i * 32 * 16, __float_as_uint(v0));
                st_rel32(p_y + i * 32 * 16 + 32 * 32 * 16, __float_as_uint(v1));
            }
            TSX(8, tid == 128);
        }
        if (cta < NFFN) {
            uint32_t gf[8][2][4];
            mbar_wait(bar_w, 0); mbar_wait(bar_w + 8, 0); mbar_wait(bar_w + 16, 0); mbar_wait(bar_w + 24, 0);
#pragma unroll
            for (int ks = 0; ks < 8; ks++) {
                const int k = 128 * m + 16 * ks + (lane & 7) + (lane >> 4) * 8;
                const uint32_t a = sbase + SLOT_WGU * SLOT + k * 32 + ((((lane >> 3) & 1) ^ ((k >> 2) & 1)) << 4);
                ldsm4t(gf[ks][0], a);
                ldsm4t(gf[ks][1], a + 16384);
            }
            TSX(11, tid == 128);
            float sg = 0.f, su = 0.f;
            {
                float cs[2][4] = {};
#pragma unroll
                for (int ks = 0; ks < 8; ks++) { mma16816(cs[0], gf[ks][0], 0x3F803F80u, 0x3F803F80u); mma16816(cs[1], gf[ks][1], 0x3F803F80u, 0x3F803F80u); }
                float* csb = reinterpret_cast<float*>(smem + OFF_CS);
                if (q4 == 0) {
                    csb[(m * 2 + 0) * 16 + r8] = cs[0][0]; csb[(m * 2 + 0) * 16 + r8 + 8] = cs[0][2];
                    csb[(m * 2 + 1) * 16 + r8] = cs[1][0]; csb[(m * 2 + 1) * 16 + r8 + 8] = cs[1][2];
                }
                bar_sync(5, 128);
                const int c = (tid & 63) >> 2;
#pragma unroll
                for (int ww = 0; ww < 4; ww++) { sg += csb[(ww * 2) * 16 + c]; su += csb[(ww * 2 + 1) * 16 + c]; }
            }
            mbar_wait(bar_w + 32, 0); mbar_wait(bar_w + 40, 0);
            {
                const uint32_t wb = sbase + SLOT_WD * SLOT + warp * 2048 + ((lane & 7) + (lane >> 4) * 8) * 128;
#pragma unroll
                for (int i = 0; i < 4; i++) ldsm4t(df[i], wb + (((2 * i + ((lane >> 3) & 1)) ^ (lane & 7)) << 4));
            }
            TSX(12, tid == 128);
            bar_sync(3, 256);
            float acc[2][2][4] = {};
            uint32_t t4[4][4];
#pragma unroll
            for (int u = 0; u < 4; u++) ldsm4(t4[u], sbase + OFF_XN + (lane & 3) * XN_PITCH + (16 * m + 4 * u + (lane >> 3)) * 16);
            TSD(27, tid == 128, __uint_as_float(t4[0][0]));
#pragma unroll
            for (int u = 0; u < 4; u++) {
#pragma unroll
                for (int i = 0; i < 2; i++) {
                    mma16816(acc[i][0], gf[2 * u][i], t4[u][0], t4[u][1]);
                    mma16816(acc[i][1], gf[2 * u + 1][i], t4[u][2], t4[u][3]);
                }
            }
            TSD(28, tid == 128, acc[1][1][0] + acc[0][0][0] + acc[0][1][0] + acc[1][0][0]);
            float* red = reinterpret_cast<float*>(smem + OFF_RED);
#pragma unroll
            for (int i = 0; i < 2; i++) {
                const float2 v = kh ? make_float2(acc[i][0][2] + acc[i][1][2], acc[i][0][3] + acc[i][1][3])
                                    : make_float2(acc[i][0][0] + acc[i][1][0], acc[i][0][1] + acc[i][1][1]);
                *reinterpret_cast<float2*>(red + ((m * 2 + i) * 16 + r8 + 8 * kh) * 4 + 2 * hp) = v;
            }
            bar_sync(4, 256);
            TSX(16, tid == 128);
            if (tid < 192) {
                const int c = (tid & 63) >> 2, b = tid & 3;
                const float2 st = *reinterpret_cast<const float2*>(smem + OFF_ST + b * 8);
                float g = 0.f, u = 0.f;
#pragma unroll
                for (int ww = 0; ww < 4; ww++) { g += red[((ww * 2) * 16 + c) * 4 + b]; u += red[((ww * 2 + 1) * 16 + c) * 4 + b]; }
                TSD(29, tid == 128, g + u + st.x);
                g = bf16r((g - st.x * sg) * st.y); u = bf16r((u - st.x * su) * st.y);
                const float inner = 0.7978845608028654f * (g + 0.044715f * g * g * g);
                const float th = 1.0f - __fdividef(2.0f, __expf(2.0f * inner) + 1.0f);
                const float ge = bf16r(0.5f * g * (1.0f + th));
                *reinterpret_cast<__nv_bfloat16*>(smem + OFF_ACT + b * 32 + c * 2) = __float2bfloat16_rn(ge * u);
                TSD(32, tid == 128, ge * u);
            }
        }
    }
    if (cta < NFFN) {
        bar_sync(6, 256);
        TS(17);
        const uint32_t b0 = *reinterpret_cast<const uint32_t*>(smem + OFF_ACT + (r8 & 3) * 32 + q4 * 4);
        const uint32_t b1 = *reinterpret_cast<const uint32_t*>(smem + OFF_ACT + (r8 & 3) * 32 + 16 + q4 * 4);
        TSD(33, tid == 0, __uint_as_float(b0));
        float c[4][4] = {};
#pragma unroll
        for (int i = 0; i < 4; i++) mma16816(c[i], df[i], b0, b1);
#pragma unroll
        for (int i = 0; i < 4; i++) {
            st_rel32(p_dpart + i * NFFN * 16, __float_as_uint(kh ? c[i][2] : c[i][0]));
            st_rel32(p_dpart + i * NFFN * 16 + 32 * NFFN * 16, __float_as_uint(kh ? c[i][3] : c[i][1]));
        }
        TS(18);
    }

    {
        const int quad = tid & 3;
        const bool two = (tid >> 2) + 64 < NFFN;
        uint4 a, b = make_uint4(0, 0, 0, 0);
        Spin sp;
        delay_cycles(DLY4);
        while (true) {
            a = ld_poll4(p_dsrc);
            if (two) b = ld_poll4(p_dsrc + 64 * 16);
            if (__all_sync(0xffffffffu, max(umax4(a), umax4(b)) != SENT)) break;
            sp.tick();
        }
        TS(19);
        float v[4] = {__uint_as_float(a.x) + __uint_as_float(b.x), __uint_as_float(a.y) + __uint_as_float(b.y),
                      __uint_as_float(a.z) + __uint_as_float(b.z), __uint_as_float(a.w) + __uint_as_float(b.w)};
        {
            const bool up = lane & 16;
            const float s0 = up ? v[0] : v[2], s1 = up ? v[1] : v[3];
            const float k0 = up ? v[2] : v[0], k1 = up ? v[3] : v[1];
            v[0] = k0 + __shfl_xor_sync(0xffffffffu, s0, 16);
            v[1] = k1 + __shfl_xor_sync(0xffffffffu, s1, 16);
            const bool up2 = lane & 8;
            const float s = up2 ? v[0] : v[1], k = up2 ? v[1] : v[0];
            v[0] = k + __shfl_xor_sync(0xffffffffu, s, 8);
            v[0] += __shfl_xor_sync(0xffffffffu, v[0], 4);
            if (!(lane & 4)) reinterpret_cast<float*>(smem + OFF_RED2)[warp * 16 + 4 * quad + ((lane & 16) ? 2 : 0) + ((lane & 8) ? 1 : 0)] = v[0];
        }
        cbar();
        TS(21);
        if (warp == 0) {
            const float* r2 = reinterpret_cast<const float*>(smem + OFF_RED2) + (lane & 1) * 64 + (lane >> 1);
            float s = (r2[0] + r2[16]) + (r2[32] + r2[48]);
            TSD(34, tid == 0, s);
            s += __shfl_xor_sync(0xffffffffu, s, 1);
            if (!(lane & 1)) *p_out = __float2bfloat16_rn(hres + bf16r(s));
            if (cta == 0 && lane == 0) st_rel32(&g_prog, 0u);
        }
    }
    TS(22);
    if (tid == 0) TSG(62);
}

typedef CUresult (*EncodeFn)(CUtensorMap*, CUtensorMapDataType, cuuint32_t, void*, const cuuint64_t*, const cuuint64_t*,
                             const cuuint32_t*, const cuuint32_t*, CUtensorMapInterleave, CUtensorMapSwizzle,
                             CUtensorMapL2promotion, CUtensorMapFloatOOBfill);

void encode(EncodeFn fn, CUtensorMap* m, const void* base, int rank, const cuuint64_t* dims, const cuuint64_t* strides,
            const cuuint32_t* box, CUtensorMapSwizzle sw, CUtensorMapL2promotion promo) {
    cuuint32_t es[3] = {1, 1, 1};
    fn(m, CU_TENSOR_MAP_DATA_TYPE_BFLOAT16, (cuuint32_t)rank, const_cast<void*>(base), dims, strides, box, es,
       CU_TENSOR_MAP_INTERLEAVE_NONE, sw, promo, CU_TENSOR_MAP_FLOAT_OOB_FILL_NONE);
}

}

extern "C" void kernel_launch(void* const* d_in, const int* in_sizes, int n_in, void* d_out, int out_size) {
    (void)in_sizes; (void)n_in; (void)out_size;
    static EncodeFn enc = nullptr;
    if (!enc) {
        void* fn = nullptr;
        cudaDriverEntryPointQueryResult qr;
        cudaGetDriverEntryPoint("cuTensorMapEncodeTiled", &fn, cudaEnableDefault, &qr);
        enc = (EncodeFn)fn;
        cudaFuncSetAttribute(fused_decode_kernel, cudaFuncAttributeMaxDynamicSharedMemorySize, SMEM_BYTES);
    }
    const void* x = d_in[0];
    Maps maps;
    {
        cuuint64_t dims[3] = {64, 262144, 2}; cuuint64_t str[2] = {256, 128}; cuuint32_t box[3] = {64, 128, 2};
        encode(enc, &maps.m[0], d_in[1], 3, dims, str, box, CU_TENSOR_MAP_SWIZZLE_128B, CU_TENSOR_MAP_L2_PROMOTION_L2_256B);
        encode(enc, &maps.m[1], d_in[2], 3, dims, str, box, CU_TENSOR_MAP_SWIZZLE_128B, CU_TENSOR_MAP_L2_PROMOTION_L2_256B);
    }
    {
        cuuint64_t dims[3] = {64, 262144, 2}; cuuint64_t str[2] = {256, 128}; cuuint32_t box[3] = {64, 32, 2};
        encode(enc, &maps.m[7], d_in[2], 3, dims, str, box, CU_TENSOR_MAP_SWIZZLE_128B, CU_TENSOR_MAP_L2_PROMOTION_L2_256B);
    }
    {
        cuuint64_t dims[3] = {4096, 512, 1}; cuuint64_t str[2] = {8192, 8192 * 512}; cuuint32_t box[3] = {32, 256, 1};
        encode(enc, &maps.m[2], d_in[3], 3, dims, str, box, CU_TENSOR_MAP_SWIZZLE_64B, CU_TENSOR_MAP_L2_PROMOTION_L2_128B);
    }
    {
        cuuint64_t dims[3] = {64, 4096, 8}; cuuint64_t str[2] = {1024, 128}; cuuint32_t box[3] = {64, 128, 2};
        encode(enc, &maps.m[3], d_in[4], 3, dims, str, box, CU_TENSOR_MAP_SWIZZLE_128B, CU_TENSOR_MAP_L2_PROMOTION_L2_256B);
    }
    {
        cuuint64_t dims[3] = {1792, 512, 1}; cuuint64_t str[2] = {3584, 3584 * 512}; cuuint32_t box[3] = {16, 256, 1};
        encode(enc, &maps.m[4], d_in[6], 3, dims, str, box, CU_TENSOR_MAP_SWIZZLE_32B, CU_TENSOR_MAP_L2_PROMOTION_L2_128B);
        encode(enc, &maps.m[5], d_in[7], 3, dims, str, box, CU_TENSOR_MAP_SWIZZLE_32B, CU_TENSOR_MAP_L2_PROMOTION_L2_128B);
    }
    {
        cuuint64_t dims[3] = {64, 1792, 8}; cuuint64_t str[2] = {1024, 128}; cuuint32_t box[3] = {64, 16, 4};
        encode(enc, &maps.m[6], d_in[8], 3, dims, str, box, CU_TENSOR_MAP_SWIZZLE_128B, CU_TENSOR_MAP_L2_PROMOTION_L2_256B);
    }
    fused_decode_kernel<<<NCTA, NTHREADS, SMEM_BYTES, cudaStreamPerThread>>>(maps, (const unsigned char*)d_in[1], (const unsigned char*)d_in[2],
        (const __nv_bfloat16*)x, (__nv_bfloat16*)d_out);
}
```

```cpp
#include <cuda_runtime.h>
#include <cuda_bf16.h>
#include <cuda.h>
#include <stdint.h>

namespace {

constexpr int NCTA      = 128;
constexpr int NTHREADS  = 320;
constexpr int SLOT      = 32768;
constexpr int NSLOT     = 6;
constexpr int NTILE     = 16;
constexpr int NFFN      = 112;
#define DEPTH_LO 2
#define DEPTH_HI 3
#define LEAD_THR8 4
#define GATE_MARGIN 0
#define WDEPTH 3
#define WO_MARGIN 112
#define SEQ_WO 33
constexpr int SEQ_K15 = (SEQ_WO == 31) ? 32 : 31;
constexpr int NSEQ    = 34;
constexpr int SLOT_WGU = 4, SLOT_WD = 5;
#define DLY2 0
#define DLY3 0
#define DLY4 500
#define DLY4B 1100
#define EARLY_PF 0
#define VSPLIT 0
#define DEPTH_INIT 3
#define NKV_END 99
#define DEPTH_END 6
#define RESET_TILE 8
constexpr uint32_t SENT = 0xFFFFFFFFu;

constexpr int OFF_XN   = NSLOT * SLOT;
constexpr int XN_PITCH = 1040;
constexpr int OFF_QS   = OFF_XN + 4 * XN_PITCH;
constexpr int QS_PITCH = 272;
constexpr int OFF_P    = OFF_QS + 4 * QS_PITCH;
constexpr int OFF_RED  = OFF_P + 4 * QS_PITCH;
constexpr int OFF_MX   = OFF_RED + 4096;
constexpr int OFF_L    = OFF_MX + 64;
constexpr int OFF_ACT  = OFF_L + 128;
constexpr int OFF_RED2 = OFF_ACT + 128;
constexpr int OFF_CS   = OFF_RED2 + 512;
constexpr int OFF_ST   = OFF_CS + 512;
constexpr int OFF_BAR  = OFF_ST + 32;
constexpr int OFF_VAR  = OFF_BAR + 192;
constexpr int SMEM_USED = OFF_VAR + 64;
constexpr int SMEM_BYTES = SMEM_USED + 1024;
static_assert(OFF_RED % 16 == 0 && OFF_MX % 16 == 0 && OFF_ST % 8 == 0 && OFF_BAR % 8 == 0, "alignment");

__device__ uint2    g_q[4 * 2048];
__device__ float    g_partO[32 * 4 * 4 * 128];
__device__ float2   g_ml[32 * 4 * 4];
__device__ float    g_ypart[4 * 32 * 32 * 16];
__device__ uint16_t g_h[4 * 512];
__device__ float    g_dpart[4 * 32 * NFFN * 16];
__device__ unsigned g_cnt0, g_cnt1, g_prog;
#define TS(i)
#define TSX(i, cond)
#define TSG(i)
#define TSD(i, cond, dep)

__device__ __forceinline__ uint32_t smem_u32(const void* p) { return (uint32_t)__cvta_generic_to_shared(p); }
__device__ __forceinline__ void mbar_init(uint32_t bar, uint32_t cnt) {
    asm volatile("mbarrier.init.shared::cta.b64 [%0], %1;" ::"r"(bar), "r"(cnt) : "memory");
}
__device__ __forceinline__ void mbar_expect_tx(uint32_t bar, uint32_t bytes) {
    asm volatile("mbarrier.arrive.expect_tx.shared::cta.b64 _, [%0], %1;" ::"r"(bar), "r"(bytes) : "memory");
}
__device__ __forceinline__ void mbar_arrive(uint32_t bar) {
    asm volatile("mbarrier.arrive.shared::cta.b64 _, [%0];" ::"r"(bar) : "memory");
}
__device__ __forceinline__ bool mbar_try(uint32_t bar, uint32_t parity) {
    uint32_t ok;
    asm volatile("{\n.reg .pred p;\nmbarrier.try_wait.parity.shared::cta.b64 p, [%1], %2;\nselp.u32 %0, 1, 0, p;\n}"
                 : "=r"(ok) : "r"(bar), "r"(parity) : "memory");
    return ok != 0;
}
constexpr uint32_t SPIN_LIMIT = 1u << 22;
__device__ __forceinline__ void mbar_wait(uint32_t bar, uint32_t parity) {
    uint32_t it = 0;
    while (!mbar_try(bar, parity)) { if (++it > SPIN_LIMIT) __trap(); }
}
__device__ __forceinline__ void tma3d(uint32_t dst, const CUtensorMap* m, int c0, int c1, int c2, uint32_t bar, uint64_t pol) {
    asm volatile("cp.async.bulk.tensor.3d.shared::cluster.global.mbarrier::complete_tx::bytes.L2::cache_hint [%0], [%1, {%3, %4, %5}], [%2], %6;"
                 ::"r"(dst), "l"(m), "r"(bar), "r"(c0), "r"(c1), "r"(c2), "l"(pol) : "memory");
}
__device__ __forceinline__ void tma3d_prefetch(const CUtensorMap* m, int c0, int c1, int c2) {
    asm volatile("cp.async.bulk.prefetch.tensor.3d.L2.global.tile [%0, {%1, %2, %3}];" ::"l"(m), "r"(c0), "r"(c1), "r"(c2) : "memory");
}
__device__ __forceinline__ void ldsm4(uint32_t (&r)[4], uint32_t addr) {
    asm volatile("ldmatrix.sync.aligned.m8n8.x4.shared.b16 {%0,%1,%2,%3}, [%4];"
                 : "=r"(r[0]), "=r"(r[1]), "=r"(r[2]), "=r"(r[3]) : "r"(addr) : "memory");
}
__device__ __forceinline__ void ldsm4t(uint32_t (&r)[4], uint32_t addr) {
    asm volatile("ldmatrix.sync.aligned.m8n8.x4.trans.shared.b16 {%0,%1,%2,%3}, [%4];"
                 : "=r"(r[0]), "=r"(r[1]), "=r"(r[2]), "=r"(r[3]) : "r"(addr) : "memory");
}
__device__ __forceinline__ void mma16816(float (&c)[4], const uint32_t (&a)[4], uint32_t b0, uint32_t b1) {
    asm volatile("mma.sync.aligned.m16n8k16.row.col.f32.bf16.bf16.f32 {%0,%1,%2,%3}, {%4,%5,%6,%7}, {%8,%9}, {%0,%1,%2,%3};"
                 : "+f"(c[0]), "+f"(c[1]), "+f"(c[2]), "+f"(c[3])
                 : "r"(a[0]), "r"(a[1]), "r"(a[2]), "r"(a[3]), "r"(b0), "r"(b1));
}
__device__ __forceinline__ void cbar() { asm volatile("bar.sync 1, 256;" ::: "memory"); }
__device__ __forceinline__ void bar_sync(int id, int n) { asm volatile("bar.sync %0, %1;" ::"r"(id), "r"(n) : "memory"); }
__device__ __forceinline__ void bar_arrive(int id, int n) { asm volatile("bar.arrive %0, %1;" ::"r"(id), "r"(n) : "memory"); }
__device__ __forceinline__ uint4 ld_poll4(const void* p) {
    uint4 v;
    asm volatile("ld.relaxed.gpu.global.v4.u32 {%0,%1,%2,%3}, [%4];" : "=r"(v.x), "=r"(v.y), "=r"(v.z), "=r"(v.w) : "l"(p) : "memory");
    return v;
}
__device__ __forceinline__ uint2 ld_poll2(const void* p) {
    uint2 v;
    asm volatile("ld.relaxed.gpu.global.v2.u32 {%0,%1}, [%2];" : "=r"(v.x), "=r"(v.y) : "l"(p) : "memory");
    return v;
}
__device__ __forceinline__ void st_rel32(void* p, uint32_t v) { asm volatile("st.relaxed.gpu.global.u32 [%0], %1;" ::"l"(p), "r"(v) : "memory"); }
__device__ __forceinline__ void st_rel16(void* p, uint16_t v) { asm volatile("st.relaxed.gpu.global.u16 [%0], %1;" ::"l"(p), "h"(v) : "memory"); }
__device__ __forceinline__ void st_rel64(void* p, uint32_t a, uint32_t b) { asm volatile("st.relaxed.gpu.global.v2.u32 [%0], {%1,%2};" ::"l"(p), "r"(a), "r"(b) : "memory"); }
__device__ __forceinline__ void st_rel128(void* p, uint32_t v) { asm volatile("st.relaxed.gpu.global.v4.u32 [%0], {%1,%1,%1,%1};" ::"l"(p), "r"(v) : "memory"); }
__device__ __forceinline__ uint32_t umax4(const uint4& v) { return max(max(v.x, v.y), max(v.z, v.w)); }
template <class T> __device__ __forceinline__ void pin(T*& p) { asm volatile("" : "+l"(p)); }
__device__ __forceinline__ bool valid8h(const uint4& v) {
    return (__vcmpeq2(v.x, SENT) | __vcmpeq2(v.y, SENT) | __vcmpeq2(v.z, SENT) | __vcmpeq2(v.w, SENT)) == 0;
}
struct Spin {
    uint32_t it = 0;
    __device__ __forceinline__ void tick() { if (++it > SPIN_LIMIT) __trap(); }
};
__device__ __forceinline__ uint32_t pack_bf16(float lo, float hi) {
    uint32_t r; asm("cvt.rn.bf16x2.f32 %0, %1, %2;" : "=r"(r) : "f"(hi), "f"(lo)); return r;
}
__device__ __forceinline__ void delay_cycles(int n) { if (n > 0) { const long long t0 = clock64(); while (clock64() - t0 < n) {} } }
__device__ __forceinline__ float bf16r(float x) { return __uint_as_float(pack_bf16(0.f, x) & 0xFFFF0000u); }
__device__ __forceinline__ float bf_lo(uint32_t v) { return __uint_as_float(v << 16); }
__device__ __forceinline__ float bf_hi(uint32_t v) { return __uint_as_float(v & 0xFFFF0000u); }
__device__ __forceinline__ uint32_t hmax2(uint32_t a, uint32_t b) {
    uint32_t r; asm("max.bf16x2 %0, %1, %2;" : "=r"(r) : "r"(a), "r"(b)); return r;
}
__device__ __forceinline__ float ex2(float x) { float r; asm("ex2.approx.ftz.f32 %0, %1;" : "=f"(r) : "f"(x)); return r; }

__device__ __forceinline__ float2 ln_stats(const uint4& a, const uint4& b, float (&v)[16]) {
    v[0] = bf_lo(a.x); v[1] = bf_hi(a.x); v[2] = bf_lo(a.y); v[3] = bf_hi(a.y);
    v[4] = bf_lo(a.z); v[5] = bf_hi(a.z); v[6] = bf_lo(a.w); v[7] = bf_hi(a.w);
    v[8] = bf_lo(b.x); v[9] = bf_hi(b.x); v[10] = bf_lo(b.y); v[11] = bf_hi(b.y);
    v[12] = bf_lo(b.z); v[13] = bf_hi(b.z); v[14] = bf_lo(b.w); v[15] = bf_hi(b.w);
    const float shift = __shfl_sync(0xffffffffu, v[0], 0);
    float s0 = 0.f, s1 = 0.f, s2 = 0.f, s3 = 0.f, q0 = 0.f, q1 = 0.f, q2 = 0.f, q3 = 0.f;
#pragma unroll
    for (int i = 0; i < 16; i += 4) {
        const float d0 = v[i] - shift, d1 = v[i + 1] - shift, d2 = v[i + 2] - shift, d3 = v[i + 3] - shift;
        s0 += d0; s1 += d1; s2 += d2; s3 += d3;
        q0 = fmaf(d0, d0, q0); q1 = fmaf(d1, d1, q1); q2 = fmaf(d2, d2, q2); q3 = fmaf(d3, d3, q3);
    }
    float s = (s0 + s1) + (s2 + s3), ss = (q0 + q1) + (q2 + q3);
#pragma unroll
    for (int o = 16; o > 0; o >>= 1) { s += __shfl_xor_sync(0xffffffffu, s, o); ss += __shfl_xor_sync(0xffffffffu, ss, o); }
    const float md = s * (1.0f / 512.0f);
    const float var = fmaxf(ss * (1.0f / 512.0f) - md * md, 0.f);
    const float m = bf16r(shift + md);
    float sq; asm("sqrt.approx.f32 %0, %1;" : "=f"(sq) : "f"(bf16r(bf16r(var) + 1e-5f)));
    const float sd = bf16r(sq);
    return make_float2(m, __fdividef(1.0f, sd));
}

struct Maps { CUtensorMap m[8]; };

__global__ void __launch_bounds__(NTHREADS, 1)
fused_decode_kernel(const __grid_constant__ Maps maps, const unsigned char* __restrict__ kraw, const unsigned char* __restrict__ vraw,
                    const __nv_bfloat16* __restrict__ x, __nv_bfloat16* __restrict__ out)
{
    extern __shared__ __align__(1024) unsigned char smem_raw[];
    unsigned char* smem = smem_raw + ((1024u - (smem_u32(smem_raw) & 1023u)) & 1023u);
    const uint32_t sbase = smem_u32(smem);
    const uint32_t bar_full = sbase + OFF_BAR, bar_empty = sbase + OFF_BAR + 48, bar_ready = sbase + OFF_BAR + 96, bar_w = sbase + OFF_BAR + 104, bar_vl = sbase + OFF_BAR + 152;
    volatile unsigned* vars = reinterpret_cast<volatile unsigned*>(smem + OFF_VAR);
    const int tid = threadIdx.x, warp = tid >> 5, lane = tid & 31;
    const int cta = blockIdx.x;

    if (tid == 0) TSG(0);
    if (warp == 8) {
        if (lane == 0) {
            const size_t off = (size_t)cta * (NTILE * 128) * 256;
#pragma unroll
            for (int i = 0; i < EARLY_PF; i++)
                asm volatile("cp.async.bulk.prefetch.L2.global [%0], %1;" ::"l"(((i & 1) ? vraw : kraw) + off + (i >> 1) * 32768), "r"(32768) : "memory");
            for (int i = 0; i < NSLOT; i++) { mbar_init(bar_full + 8 * i, 1); mbar_init(bar_empty + 8 * i, 8); }
            mbar_init(bar_ready, 1);
            for (int i = 0; i < 6; i++) mbar_init(bar_w + 8 * i, 1);
            for (int i = 0; i < 4; i++) mbar_init(bar_vl + 8 * i, 1);
            vars[1] = 0;
            asm volatile("fence.mbarrier_init.release.cluster;" ::: "memory");
        } else if (lane <= 8) {
            asm volatile("prefetch.tensormap [%0];" ::"l"(&maps.m[lane - 1]) : "memory");
        }
    }
    if (warp == 8) { __syncwarp(); bar_arrive(8, NTHREADS); } else bar_sync(8, NTHREADS);

    if (warp == 8) {
        if (lane == 0) {
            uint64_t pol_first, pol_norm;
            asm volatile("createpolicy.fractional.L2::evict_first.b64 %0, 1.0;" : "=l"(pol_first));
            asm volatile("createpolicy.fractional.L2::evict_normal.b64 %0, 1.0;" : "=l"(pol_norm));
            const int key0 = cta * (NTILE * 128);
            int arrived = 0;
            unsigned grel = 0;
            int nkv = 0;
            for (int i = 0; i < NSEQ; i++) {
                const int slot = i % NSLOT;
                const bool is_w = (i == 0) || (i == SEQ_WO);
                if (i >= NSLOT) mbar_wait(bar_empty + 8 * slot, ((i / NSLOT) - 1) & 1);
                const int lead8 = (nkv * NCTA - (int)grel) / (NCTA / 8);
                const int d = (i <= 2) ? DEPTH_INIT : (nkv >= NKV_END) ? DEPTH_END : ((lead8 > LEAD_THR8) ? DEPTH_LO : DEPTH_HI);
                while (arrived < i - d + 1) { mbar_wait(bar_full + 8 * (arrived % NSLOT), (arrived / NSLOT) & 1); arrived++; }
                if (i == SEQ_WO && (int)grel < NCTA * 32 - WO_MARGIN) {
                    Spin sp; unsigned v;
                    while (true) {
                        asm volatile("ld.relaxed.gpu.global.u32 %0, [%1];" : "=r"(v) : "l"(&g_prog) : "memory");
                        if ((int)v >= NCTA * 32 - WO_MARGIN) break;
                        sp.tick(); __nanosleep(64);
                    }
                }
                const uint32_t dst = sbase + slot * SLOT, fb = bar_full + 8 * slot;
                int mi, c0 = 0, c1 = 0, c2 = 0, nbox = 1;
                if (i == 0)            { mi = 2; c0 = cta * 32; nbox = 2; }
                else if (i == SEQ_WO)  { mi = 3; c1 = (cta >> 2) * 128; c2 = (cta & 3) * 2; }
                else                   { mi = nkv & 1; c1 = key0 + (nkv >> 1) * 128; }
                if (VSPLIT && !is_w && nkv == 31) {
                    for (int j = 0; j < 4; j++) {
                        mbar_expect_tx(bar_vl + 8 * j, 8192);
                        tma3d(dst + j * 8192, &maps.m[7], 0, c1 + j * 32, 0, bar_vl + 8 * j, pol_first);
                    }
                } else {
                    mbar_expect_tx(fb, 32768);
                    for (int j = 0; j < nbox; j++) tma3d(dst + j * 16384, &maps.m[mi], c0, c1 + j * 256, c2, fb, is_w ? pol_norm : pol_first);
                }
                if (!is_w) {
                    if (nkv < 31) {
                        grel = atomicAdd(&g_prog, 1u);
                    } else {
                        asm volatile("red.relaxed.gpu.global.add.u32 [%0], 1;" ::"l"(&g_prog) : "memory");
                    }
                    nkv++;
                }
            }
            if (cta < NFFN) {
                mbar_wait(bar_empty + 8 * SLOT_WGU, (34 / NSLOT - 1) & 1);
                mbar_wait(bar_empty + 8 * SLOT_WD, (35 / NSLOT - 1) & 1);
                if ((int)grel < NCTA * 32 - GATE_MARGIN) {
                    Spin sp; unsigned v;
                    while (true) {
                        asm volatile("ld.relaxed.gpu.global.u32 %0, [%1];" : "=r"(v) : "l"(&g_prog) : "memory");
                        if ((int)v >= NCTA * 32 - GATE_MARGIN) break;
                        sp.tick(); __nanosleep(64);
                    }
                }
                mbar_wait(bar_full + 8 * (SEQ_WO % NSLOT), (SEQ_WO / NSLOT) & 1);
                TSX(26, true);
                for (int k = 0; k < 6; k++) {
                    if (k >= WDEPTH) mbar_wait(bar_w + 8 * (k - WDEPTH), 0);
                    mbar_expect_tx(bar_w + 8 * k, 8192);
                    const int mi = (k < 4) ? 4 + (k >> 1) : 6;
                    const int c0 = (k < 4) ? cta * 16 : 0, c1 = (k < 4) ? (k & 1) * 256 : cta * 16, c2 = (k < 4) ? 0 : (k - 4) * 4;
                    tma3d(sbase + SLOT_WGU * SLOT + k * 8192, &maps.m[mi], c0, c1, c2, bar_w + 8 * k, pol_norm);
                }
            }
            TSX(20, true);
        }
        return;
    }

    const int pair = cta >> 2, split = cta & 3;

    if (warp == 9) {
        Spin sp;
        while (vars[1] < RESET_TILE) { sp.tick(); __nanosleep(256); }
        const unsigned epoch = vars[0];
#pragma unroll 1
        for (int u = lane; u < 128; u += 32) {
            st_rel128(&g_partO[((pair * 4 + (u >> 5)) * 4 + split) * 128 + (u & 31) * 4], SENT);
            const int seg = u >> 2;
            st_rel128(&g_ypart[(((seg >> 3) * 32 + (cta & 3) * 8 + (seg & 7)) * 32 + (cta >> 2)) * 16 + (u & 3) * 4], SENT);
        }
        if (lane < 4) st_rel64(&g_ml[(pair * 4 + lane) * 4 + split], SENT, SENT);
        if (lane < 2) st_rel128(&g_h[(cta >> 5) * 512 + (cta & 31) * 16 + lane * 8], SENT);
        if (cta < NFFN) {
#pragma unroll 1
            for (int e = lane; e < 512; e += 32) st_rel128(&g_dpart[((e >> 2) * NFFN + cta) * 16 + (e & 3) * 4], SENT);
        }
        __threadfence();
        __syncwarp();
        if (lane == 0) {
            atomicAdd(&g_cnt1, 1u);
            unsigned v; Spin sp2;
            while (true) {
                asm volatile("ld.acquire.gpu.global.u32 %0, [%1];" : "=r"(v) : "l"(&g_cnt1) : "memory");
                if ((int)(v - (epoch + 1) * NCTA) >= 0) break;
                sp2.tick(); __nanosleep(128);
            }
            mbar_arrive(bar_ready);
        }
        TSX(24, lane == 0);
        return;
    }

    const int r8 = lane >> 2, q4 = lane & 3;
    const int hp = q4 & 1, kh = q4 >> 1;
    constexpr float LOG2E = 1.4426950408889634f;
    const int bq = pair >> 3, gq = pair & 7;

    if (tid == 0) vars[0] = atomicAdd(&g_cnt0, 1u) >> 7;
    if (warp == 7) st_rel128(&g_q[(lane >> 3) * 2048 + cta * 16 + (lane & 7) * 2], 0u);
    float xres = 0.f;
    if (warp == 0) xres = __bfloat162float(x[(cta >> 5) * 512 + (cta & 31) * 16 + (lane >> 1)]);

    if (warp < 4) {
        const uint4* xr = reinterpret_cast<const uint4*>(x + warp * 512);
        const uint4 a = __ldg(xr + lane), b = __ldg(xr + 32 + lane);
        float v[16];
        const float2 st = ln_stats(a, b, v);
        uint32_t o[8];
#pragma unroll
        for (int i = 0; i < 8; i++) o[i] = pack_bf16(bf16r(v[2 * i] - st.x) * st.y, bf16r(v[2 * i + 1] - st.x) * st.y);
        unsigned char* row = smem + OFF_XN + warp * XN_PITCH;
        *reinterpret_cast<uint4*>(row + lane * 16) = make_uint4(o[0], o[1], o[2], o[3]);
        *reinterpret_cast<uint4*>(row + 512 + lane * 16) = make_uint4(o[4], o[5], o[6], o[7]);
    }
    cbar();
    const uint32_t tag = vars[0] + 1;

    {
        uint32_t bfr[4][2];
        {
            uint32_t t4[4];
#pragma unroll
            for (int u = 0; u < 2; u++) {
                ldsm4(t4, sbase + OFF_XN + (lane & 3) * XN_PITCH + (8 * warp + 4 * u + (lane >> 3)) * 16);
                bfr[2 * u][0] = t4[0]; bfr[2 * u][1] = t4[1]; bfr[2 * u + 1][0] = t4[2]; bfr[2 * u + 1][1] = t4[3];
            }
        }
        mbar_wait(bar_full + 0, 0);
        TS(2);
        float acc[2][4] = {};
#pragma unroll
        for (int ks = 0; ks < 4; ks++) {
            const int k = 64 * warp + 16 * ks + (lane & 7) + (lane >> 4) * 8;
#pragma unroll
            for (int mt = 0; mt < 2; mt++) {
                uint32_t a[4];
                const int chunk = 2 * mt + ((lane >> 3) & 1);
                ldsm4t(a, sbase + k * 64 + ((chunk ^ ((k >> 1) & 3)) << 4));
                mma16816(acc[mt], a, bfr[ks][0], bfr[ks][1]);
            }
        }
        __syncwarp();
        if (lane == 0) mbar_arrive(bar_empty + 0);
        float* red = reinterpret_cast<float*>(smem + OFF_RED);
#pragma unroll
        for (int mt = 0; mt < 2; mt++) {
            float2 v = kh ? make_float2(acc[mt][2], acc[mt][3]) : make_float2(acc[mt][0], acc[mt][1]);
            *reinterpret_cast<float2*>(red + ((warp * 2 + mt) * 16 + r8 + 8 * kh) * 4 + 2 * hp) = v;
        }
        cbar();
        if (tid < 64) {
            const int b = tid >> 4, c2 = tid & 15;
            float s0 = 0.f, s1 = 0.f;
            const int c0 = 2 * c2, c1 = 2 * c2 + 1;
#pragma unroll
            for (int ww = 0; ww < 8; ww++) {
                s0 += red[((ww * 2 + (c0 >> 4)) * 16 + (c0 & 15)) * 4 + b];
                s1 += red[((ww * 2 + (c1 >> 4)) * 16 + (c1 & 15)) * 4 + b];
            }
            st_rel64(&g_q[b * 2048 + cta * 16 + c2], pack_bf16(s0, s1), tag);
        }
        {
            const uint2* src = &g_q[bq * 2048 + gq * 256 + tid];
            uint2 v;
            Spin sp;
            while (true) { v = ld_poll2(src); if (__all_sync(0xffffffffu, v.y == tag)) break; sp.tick(); }
            *reinterpret_cast<uint32_t*>(smem + OFF_QS + (tid >> 6) * QS_PITCH + (tid & 63) * 4) = v.x;
        }
        cbar();
    }
    TS(3);
    uint32_t qf[8][2];
    {
        uint32_t t4[4];
#pragma unroll
        for (int u = 0; u < 4; u++) {
            ldsm4(t4, sbase + OFF_QS + (lane & 3) * QS_PITCH + (4 * u + (lane >> 3)) * 16);
            qf[2 * u][0] = t4[0]; qf[2 * u][1] = t4[1]; qf[2 * u + 1][0] = t4[2]; qf[2 * u + 1][1] = t4[3];
        }
    }

    const uint32_t voff = (warp >> 2) * 16384 + ((lane & 7) + (lane >> 4) * 8) * 128 +
                          ((((2 * warp + ((lane >> 3) & 1)) & 7) ^ (lane & 7)) << 4);
    const uint32_t poff = sbase + OFF_P + (lane & 3) * QS_PITCH + (lane >> 3) * 16;
    const uint32_t koff = (16 * warp + (lane & 7) + ((lane >> 3) & 1) * 8) * 128;
    const uint32_t kx = lane & 7, kc = lane >> 4;
    constexpr float SCALE = 0.08838834764831845f;
    uint32_t* mxbuf = reinterpret_cast<uint32_t*>(smem + OFF_MX);
    uint32_t M2 = 0xFF80FF80u;
    float l0 = 0.f, l1 = 0.f;
    float oacc[2][4] = {};
    int slot = 1; uint32_t ph = 0;

    for (int t = 0;; t++) {
        mbar_wait(bar_full + 8 * slot, ph);
        float sa[4] = {}, sb[4] = {};
        {
            const uint32_t kb = sbase + slot * SLOT + koff;
#pragma unroll
            for (int ks = 0; ks < 8; ks++) {
                uint32_t a[4];
                ldsm4(a, kb + (ks >> 2) * 16384 + (((2 * (ks & 3) + kc) ^ kx) << 4));
                if (ks & 1) mma16816(sb, a, qf[ks][0], qf[ks][1]); else mma16816(sa, a, qf[ks][0], qf[ks][1]);
            }
        }
        __syncwarp();
        if (lane == 0) mbar_arrive(bar_empty + 8 * slot);
        if (++slot == NSLOT) { slot = 0; ph ^= 1; }

        const float r0 = kh ? sa[2] + sb[2] : sa[0] + sb[0];
        const float r1 = kh ? sa[3] + sb[3] : sa[1] + sb[1];
        uint32_t sp = pack_bf16(r0, r1);
        sp = pack_bf16(bf_lo(sp) * SCALE, bf_hi(sp) * SCALE);
        uint32_t mx = sp;
#pragma unroll
        for (int o = 2; o <= 16; o <<= 1) mx = hmax2(mx, __shfl_xor_sync(0xffffffffu, mx, o));
        if (lane < 2) mxbuf[lane * 8 + warp] = mx;
        if (tid == 0) vars[1] = t + 1;
        TS(40 + t);
        cbar();
        {
            const uint4 m0 = *reinterpret_cast<const uint4*>(mxbuf + hp * 8), m1 = *reinterpret_cast<const uint4*>(mxbuf + hp * 8 + 4);
            uint32_t mt = hmax2(hmax2(hmax2(m0.x, m0.y), hmax2(m0.z, m0.w)), hmax2(hmax2(m1.x, m1.y), hmax2(m1.z, m1.w)));
            const uint32_t Mn = hmax2(M2, mt);
            const float a0 = ex2((bf_lo(M2) - bf_lo(Mn)) * LOG2E), a1 = ex2((bf_hi(M2) - bf_hi(Mn)) * LOG2E);
            const float p0 = ex2((bf_lo(sp) - bf_lo(Mn)) * LOG2E), p1 = ex2((bf_hi(sp) - bf_hi(Mn)) * LOG2E);
            M2 = Mn;
            l0 = fmaf(l0, a0, p0); l1 = fmaf(l1, a1, p1);
            const uint32_t pp = pack_bf16(p0, p1);
            unsigned char* pd = smem + OFF_P + (2 * hp) * QS_PITCH + (16 * warp + r8 + 8 * kh) * 2;
            *reinterpret_cast<uint16_t*>(pd) = (uint16_t)(pp & 0xFFFF);
            *reinterpret_cast<uint16_t*>(pd + QS_PITCH) = (uint16_t)(pp >> 16);
#pragma unroll
            for (int c = 0; c < 2; c++) { oacc[c][0] *= a0; oacc[c][1] *= a1; oacc[c][2] *= a0; oacc[c][3] *= a1; }
        }
        if (t == NTILE - 1) break;
        cbar();
        uint32_t pb[8][2];
        {
            uint32_t t4[4];
#pragma unroll
            for (int u = 0; u < 4; u++) {
                ldsm4(t4, poff + u * 64);
                pb[2 * u][0] = t4[0]; pb[2 * u][1] = t4[1]; pb[2 * u + 1][0] = t4[2]; pb[2 * u + 1][1] = t4[3];
            }
        }
        mbar_wait(bar_full + 8 * slot, ph);
        {
            const uint32_t vb = sbase + slot * SLOT + voff;
#pragma unroll
            for (int ks = 0; ks < 8; ks++) {
                uint32_t a[4];
                ldsm4t(a, vb + ks * 2048);
                mma16816(oacc[ks & 1], a, pb[ks][0], pb[ks][1]);
            }
        }
        __syncwarp();
        if (lane == 0) mbar_arrive(bar_empty + 8 * slot);
        if (++slot == NSLOT) { slot = 0; ph ^= 1; }
        if (SEQ_WO == 31 && t == NTILE - 2) { if (++slot == NSLOT) { slot = 0; ph ^= 1; } }
    }

    const int head = cta >> 2;
    float* p_partO = &g_partO[((pair * 4 + 2 * hp) * 4 + split) * 128 + 16 * warp + r8 + 8 * kh];
    float* p_dpart = &g_dpart[(((2 * hp) * 32 + 4 * warp) * NFFN + cta) * 16 + r8 + 8 * kh];
    const float* p_dsrc = &g_dpart[(cta * NFFN + (tid >> 2)) * 16 + (tid & 3) * 4];
    __nv_bfloat16* p_out = out + (cta >> 5) * 512 + (cta & 31) * 16 + (lane >> 1);
    pin(p_partO); pin(p_dpart); pin(p_dsrc); pin(p_out);

    {
        float s0 = l0, s1 = l1;
#pragma unroll
        for (int o = 2; o <= 16; o <<= 1) { s0 += __shfl_xor_sync(0xffffffffu, s0, o); s1 += __shfl_xor_sync(0xffffffffu, s1, o); }
        if (lane < 2) *reinterpret_cast<float2*>(smem + OFF_L + warp * 16 + lane * 8) = make_float2(s0, s1);
        mbar_wait(bar_ready, 0);
        cbar();
        if (warp == 0) {
            const uint32_t other = __shfl_sync(0xffffffffu, M2, lane >> 1);
            float l = 0.f;
#pragma unroll
            for (int ww = 0; ww < 8; ww++) l += *reinterpret_cast<const float*>(smem + OFF_L + ww * 16 + (lane & 3) * 4);
            const float m = (lane & 1) ? bf_hi(other) : bf_lo(other);
            if (lane < 4) st_rel64(&g_ml[(pair * 4 + lane) * 4 + split], __float_as_uint(m), __float_as_uint(l));
        }
        uint32_t pb[8][2];
        {
            uint32_t t4[4];
#pragma unroll
            for (int u = 0; u < 4; u++) {
                ldsm4(t4, poff + u * 64);
                pb[2 * u][0] = t4[0]; pb[2 * u][1] = t4[1]; pb[2 * u + 1][0] = t4[2]; pb[2 * u + 1][1] = t4[3];
            }
        }
        float o2[2][4] = {};
        if (VSPLIT) {
            const uint32_t vb = sbase + slot * SLOT + (warp >> 2) * 4096 + ((lane & 7) + (lane >> 4) * 8) * 128 +
                                ((((2 * warp + ((lane >> 3) & 1)) & 7) ^ (lane & 7)) << 4);
#pragma unroll
            for (int p = 0; p < 4; p++) {
                uint32_t a0[4], a1[4];
                mbar_wait(bar_vl + 8 * p, 0);
                if (p == 3) { TS(30); }
                ldsm4t(a0, vb + p * 8192);
                ldsm4t(a1, vb + p * 8192 + 2048);
                mma16816((p & 1) ? o2[0] : oacc[0], a0, pb[2 * p][0], pb[2 * p][1]);
                mma16816((p & 1) ? o2[1] : oacc[1], a1, pb[2 * p + 1][0], pb[2 * p + 1][1]);
            }
        } else {
            mbar_wait(bar_full + 8 * slot, ph);
            TS(30);
            const uint32_t vb = sbase + slot * SLOT + voff;
            uint32_t a[8][4];
#pragma unroll
            for (int ks = 0; ks < 8; ks++) ldsm4t(a[ks], vb + ks * 2048);
#pragma unroll
            for (int ks = 0; ks < 8; ks++) mma16816((ks & 2) ? o2[ks & 1] : oacc[ks & 1], a[ks], pb[ks][0], pb[ks][1]);
        }
        const float v0 = kh ? (oacc[0][2] + oacc[1][2]) + (o2[0][2] + o2[1][2]) : (oacc[0][0] + oacc[1][0]) + (o2[0][0] + o2[1][0]);
        const float v1 = kh ? (oacc[0][3] + oacc[1][3]) + (o2[0][3] + o2[1][3]) : (oacc[0][1] + oacc[1][1]) + (o2[0][1] + o2[1][1]);
        st_rel32(p_partO, __float_as_uint(v0));
        st_rel32(p_partO + 512, __float_as_uint(v1));
        TS(4);
    }

    float hres = 0.f;
    uint32_t df[4][4];
    if (warp < 4) {
        {
            const int ph_idx = (warp * 8 + (head >> 2)) * 4 + (head & 3);
            const float* po = &g_partO[ph_idx * 512 + lane * 4];
            const float* pm = reinterpret_cast<const float*>(&g_ml[ph_idx * 4]);
            uint4 o0, o1, o2, o3, ma, mb;
            Spin sp;
            while (true) {
                o0 = ld_poll4(po); o1 = ld_poll4(po + 128); o2 = ld_poll4(po + 256); o3 = ld_poll4(po + 384);
                ma = ld_poll4(pm); mb = ld_poll4(pm + 4);
                const uint32_t mxv = max(max(max(umax4(o0), umax4(o1)), max(umax4(o2), umax4(o3))), max(umax4(ma), umax4(mb)));
                if (__all_sync(0xffffffffu, mxv != SENT)) break;
                sp.tick();
            }
            TS(6);
            const float m0 = __uint_as_float(ma.x), m1 = __uint_as_float(ma.z), m2 = __uint_as_float(mb.x), m3 = __uint_as_float(mb.z);
            const float M = fmaxf(fmaxf(m0, m1), fmaxf(m2, m3));
            float w0 = ex2((m0 - M) * LOG2E), w1 = ex2((m1 - M) * LOG2E), w2 = ex2((m2 - M) * LOG2E), w3 = ex2((m3 - M) * LOG2E);
            const float L = w0 * __uint_as_float(ma.y) + w1 * __uint_as_float(ma.w) + w2 * __uint_as_float(mb.y) + w3 * __uint_as_float(mb.w);
            const float inv = __fdividef(1.0f, L);
            const float e0 = (w0 * __uint_as_float(o0.x) + w1 * __uint_as_float(o1.x) + w2 * __uint_as_float(o2.x) + w3 * __uint_as_float(o3.x)) * inv;
            const float e1 = (w0 * __uint_as_float(o0.y) + w1 * __uint_as_float(o1.y) + w2 * __uint_as_float(o2.y) + w3 * __uint_as_float(o3.y)) * inv;
            const float e2 = (w0 * __uint_as_float(o0.z) + w1 * __uint_as_float(o1.z) + w2 * __uint_as_float(o2.z) + w3 * __uint_as_float(o3.z)) * inv;
            const float e3 = (w0 * __uint_as_float(o0.w) + w1 * __uint_as_float(o1.w) + w2 * __uint_as_float(o2.w) + w3 * __uint_as_float(o3.w)) * inv;
            *reinterpret_cast<uint2*>(smem + OFF_QS + warp * QS_PITCH + lane * 8) = make_uint2(pack_bf16(e0, e1), pack_bf16(e2, e3));
            TSD(31, tid == 0, e0 + e1 + e2 + e3);
            bar_arrive(2, 256);
        }
        {
            const float* src = &g_ypart[(cta * 32 + 8 * warp + (lane >> 2)) * 16 + (lane & 3) * 4];
            uint16_t* p_h = &g_h[(cta >> 5) * 512 + (cta & 31) * 16 + (lane >> 1)];
            pin(p_h);
            delay_cycles(DLY2);
            uint4 y;
            Spin sp;
            while (true) {
                y = ld_poll4(src);
                if (__all_sync(0xffffffffu, umax4(y) != SENT)) break;
                sp.tick();
            }
            TS(9);
            const bool up = lane & 16, up2 = lane & 8;
            const float a0 = __uint_as_float(y.x), a1 = __uint_as_float(y.y), a2 = __uint_as_float(y.z), a3 = __uint_as_float(y.w);
            const float v0 = (up ? a2 : a0) + __shfl_xor_sync(0xffffffffu, up ? a0 : a2, 16);
            const float v1 = (up ? a3 : a1) + __shfl_xor_sync(0xffffffffu, up ? a1 : a3, 16);
            float v = (up2 ? v1 : v0) + __shfl_xor_sync(0xffffffffu, up2 ? v0 : v1, 8);
            v += __shfl_xor_sync(0xffffffffu, v, 4);
            float* rc = reinterpret_cast<float*>(smem + OFF_RED2);
            if (!(lane & 4)) rc[warp * 16 + 4 * (lane & 3) + (up ? 2 : 0) + (up2 ? 1 : 0)] = v;
            bar_sync(7, 128);
            if (warp == 0) {
                const float* r2 = rc + (lane & 1) * 32 + (lane >> 1);
                float t = r2[0] + r2[16];
                t += __shfl_xor_sync(0xffffffffu, t, 1);
                hres = bf16r(xres + bf16r(t));
                if (!(lane & 1)) st_rel16(p_h, (uint16_t)(__float_as_uint(hres) >> 16));
                TS(10);
            }
        }
        {
            const uint4* hr = reinterpret_cast<const uint4*>(g_h + warp * 512);
            delay_cycles(DLY3);
            uint4 a, b;
            Spin sp;
            while (true) {
                a = ld_poll4(hr + lane); b = ld_poll4(hr + 32 + lane);
                if (__all_sync(0xffffffffu, valid8h(a) & valid8h(b))) break;
                sp.tick();
            }
            TS(13);
            if (cta < NFFN) {
                unsigned char* row = smem + OFF_XN + warp * XN_PITCH;
                *reinterpret_cast<uint4*>(row + lane * 16) = a;
                *reinterpret_cast<uint4*>(row + 512 + lane * 16) = b;
                bar_arrive(3, 256);
                float v[16];
                const float2 st = ln_stats(a, b, v);
                if (lane == 0) *reinterpret_cast<float2*>(smem + OFF_ST + warp * 8) = st;
                bar_arrive(4, 256);
                TS(14);
                mbar_wait(bar_w + 32, 0); mbar_wait(bar_w + 40, 0);
                const uint32_t wb = sbase + SLOT_WD * SLOT + warp * 2048 + ((lane & 7) + (lane >> 4) * 8) * 128;
#pragma unroll
                for (int i = 0; i < 4; i++) ldsm4t(df[i], wb + (((2 * i + ((lane >> 3) & 1)) ^ (lane & 7)) << 4));
            }
        }
    } else {
        const int m = warp - 4;
        {
            uint32_t af[2][8][4];
            float* p_y = &g_ypart[(((2 * hp) * 32 + (cta & 3) * 8 + 2 * m) * 32 + head) * 16 + r8 + 8 * kh];
            pin(p_y);
            mbar_wait(bar_full + 8 * (SEQ_WO % NSLOT), (SEQ_WO / NSLOT) & 1);
#pragma unroll
            for (int i = 0; i < 2; i++) {
                const int j = 2 * m + i;
                const uint32_t wb = sbase + (SEQ_WO % NSLOT) * SLOT + (j >> 2) * 16384 + ((lane & 7) + (lane >> 4) * 8) * 128 +
                                    ((((2 * j + ((lane >> 3) & 1)) & 7) ^ (lane & 7)) << 4);
#pragma unroll
                for (int ks = 0; ks < 8; ks++) ldsm4t(af[i][ks], wb + ks * 2048);
            }
            TSX(5, tid == 128);
            bar_sync(2, 256);
            TSX(7, tid == 128);
            float acc[2][2][4] = {};
            uint32_t t4[4][4];
#pragma unroll
            for (int u = 0; u < 4; u++) ldsm4(t4[u], sbase + OFF_QS + (lane & 3) * QS_PITCH + (4 * u + (lane >> 3)) * 16);
            TSD(37, tid == 128, __uint_as_float(t4[0][0]));
#pragma unroll
            for (int u = 0; u < 4; u++) {
#pragma unroll
                for (int i = 0; i < 2; i++) {
                    mma16816(acc[i][0], af[i][2 * u], t4[u][0], t4[u][1]);
                    mma16816(acc[i][1], af[i][2 * u + 1], t4[u][2], t4[u][3]);
                }
            }
#pragma unroll
            for (int i = 0; i < 2; i++) {
                const float v0 = kh ? acc[i][0][2] + acc[i][1][2] : acc[i][0][0] + acc[i][1][0];
                const float v1 = kh ? acc[i][0][3] + acc[i][1][3] : acc[i][0][1] + acc[i][1][1];
                st_rel32(p_y + i * 32 * 16, __float_as_uint(v0));
                st_rel32(p_y + i * 32 * 16 + 32 * 32 * 16, __float_as_uint(v1));
            }
            TSX(8, tid == 128);
        }
        if (cta < NFFN) {
            uint32_t gf[8][2][4];
            mbar_wait(bar_w, 0); mbar_wait(bar_w + 8, 0); mbar_wait(bar_w + 16, 0); mbar_wait(bar_w + 24, 0);
#pragma unroll
            for (int ks = 0; ks < 8; ks++) {
                const int k = 128 * m + 16 * ks + (lane & 7) + (lane >> 4) * 8;
                const uint32_t a = sbase + SLOT_WGU * SLOT + k * 32 + ((((lane >> 3) & 1) ^ ((k >> 2) & 1)) << 4);
                ldsm4t(gf[ks][0], a);
                ldsm4t(gf[ks][1], a + 16384);
            }
            TSX(11, tid == 128);
            float sg = 0.f, su = 0.f;
            {
                float cs[2][4] = {};
#pragma unroll
                for (int ks = 0; ks < 8; ks++) { mma16816(cs[0], gf[ks][0], 0x3F803F80u, 0x3F803F80u); mma16816(cs[1], gf[ks][1], 0x3F803F80u, 0x3F803F80u); }
                float* csb = reinterpret_cast<float*>(smem + OFF_CS);
                if (q4 == 0) {
                    csb[(m * 2 + 0) * 16 + r8] = cs[0][0]; csb[(m * 2 + 0) * 16 + r8 + 8] = cs[0][2];
                    csb[(m * 2 + 1) * 16 + r8] = cs[1][0]; csb[(m * 2 + 1) * 16 + r8 + 8] = cs[1][2];
                }
                bar_sync(5, 128);
                const int c = (tid & 63) >> 2;
#pragma unroll
                for (int ww = 0; ww < 4; ww++) { sg += csb[(ww * 2) * 16 + c]; su += csb[(ww * 2 + 1) * 16 + c]; }
            }
            const uint32_t wdb = sbase + SLOT_WD * SLOT + warp * 2048 + ((lane & 7) + (lane >> 4) * 8) * 128;
            const bool have_wd = __all_sync(0xffffffffu, mbar_try(bar_w + 32, 0) && mbar_try(bar_w + 40, 0));
            if (have_wd) {
#pragma unroll
                for (int i = 0; i < 4; i++) ldsm4t(df[i], wdb + (((2 * i + ((lane >> 3) & 1)) ^ (lane & 7)) << 4));
            }
            TSX(12, tid == 128);
            bar_sync(3, 256);
            float acc[2][2][4] = {};
            uint32_t t4[4][4];
#pragma unroll
            for (int u = 0; u < 4; u++) ldsm4(t4[u], sbase + OFF_XN + (lane & 3) * XN_PITCH + (16 * m + 4 * u + (lane >> 3)) * 16);
            TSD(27, tid == 128, __uint_as_float(t4[0][0]));
#pragma unroll
            for (int u = 0; u < 4; u++) {
#pragma unroll
                for (int i = 0; i < 2; i++) {
                    mma16816(acc[i][0], gf[2 * u][i], t4[u][0], t4[u][1]);
                    mma16816(acc[i][1], gf[2 * u + 1][i], t4[u][2], t4[u][3]);
                }
            }
            TSD(28, tid == 128, acc[1][1][0] + acc[0][0][0] + acc[0][1][0] + acc[1][0][0]);
            float* red = reinterpret_cast<float*>(smem + OFF_RED);
#pragma unroll
            for (int i = 0; i < 2; i++) {
                const float2 v = kh ? make_float2(acc[i][0][2] + acc[i][1][2], acc[i][0][3] + acc[i][1][3])
                                    : make_float2(acc[i][0][0] + acc[i][1][0], acc[i][0][1] + acc[i][1][1]);
                *reinterpret_cast<float2*>(red + ((m * 2 + i) * 16 + r8 + 8 * kh) * 4 + 2 * hp) = v;
            }
            bar_sync(4, 256);
            TSX(16, tid == 128);
            if (tid < 192) {
                const int c = (tid & 63) >> 2, b = tid & 3;
                const float2 st = *reinterpret_cast<const float2*>(smem + OFF_ST + b * 8);
                float g = 0.f, u = 0.f;
#pragma unroll
                for (int ww = 0; ww < 4; ww++) { g += red[((ww * 2) * 16 + c) * 4 + b]; u += red[((ww * 2 + 1) * 16 + c) * 4 + b]; }
                TSD(29, tid == 128, g + u + st.x);
                g = bf16r((g - st.x * sg) * st.y); u = bf16r((u - st.x * su) * st.y);
                const float inner = 0.7978845608028654f * (g + 0.044715f * g * g * g);
                const float th = 1.0f - __fdividef(2.0f, __expf(2.0f * inner) + 1.0f);
                const float ge = bf16r(0.5f * g * (1.0f + th));
                *reinterpret_cast<__nv_bfloat16*>(smem + OFF_ACT + b * 32 + c * 2) = __float2bfloat16_rn(ge * u);
                TSD(32, tid == 128, ge * u);
            }
            if (!have_wd) {
                mbar_wait(bar_w + 32, 0); mbar_wait(bar_w + 40, 0);
#pragma unroll
                for (int i = 0; i < 4; i++) ldsm4t(df[i], wdb + (((2 * i + ((lane >> 3) & 1)) ^ (lane & 7)) << 4));
            }
        }
    }
    if (cta < NFFN) {
        bar_sync(6, 256);
        TS(17);
        const uint32_t b0 = *reinterpret_cast<const uint32_t*>(smem + OFF_ACT + (r8 & 3) * 32 + q4 * 4);
        const uint32_t b1 = *reinterpret_cast<const uint32_t*>(smem + OFF_ACT + (r8 & 3) * 32 + 16 + q4 * 4);
        TSD(33, tid == 0, __uint_as_float(b0));
        float c[4][4] = {};
#pragma unroll
        for (int i = 0; i < 4; i++) mma16816(c[i], df[i], b0, b1);
#pragma unroll
        for (int i = 0; i < 4; i++) {
            st_rel32(p_dpart + i * NFFN * 16, __float_as_uint(kh ? c[i][2] : c[i][0]));
            st_rel32(p_dpart + i * NFFN * 16 + 32 * NFFN * 16, __float_as_uint(kh ? c[i][3] : c[i][1]));
        }
        TS(18);
    } else {
        bar_sync(6, 256);
        delay_cycles(DLY4B);
    }

    {
        const int quad = tid & 3;
        const bool two = (tid >> 2) + 64 < NFFN;
        uint4 a, b = make_uint4(0, 0, 0, 0);
        Spin sp;
        delay_cycles(DLY4);
        while (true) {
            a = ld_poll4(p_dsrc);
            if (two) b = ld_poll4(p_dsrc + 64 * 16);
            if (__all_sync(0xffffffffu, max(umax4(a), umax4(b)) != SENT)) break;
            sp.tick();
        }
        TS(19);
        float v[4] = {__uint_as_float(a.x) + __uint_as_float(b.x), __uint_as_float(a.y) + __uint_as_float(b.y),
                      __uint_as_float(a.z) + __uint_as_float(b.z), __uint_as_float(a.w) + __uint_as_float(b.w)};
        {
            const bool up = lane & 16;
            const float s0 = up ? v[0] : v[2], s1 = up ? v[1] : v[3];
            const float k0 = up ? v[2] : v[0], k1 = up ? v[3] : v[1];
            v[0] = k0 + __shfl_xor_sync(0xffffffffu, s0, 16);
            v[1] = k1 + __shfl_xor_sync(0xffffffffu, s1, 16);
            const bool up2 = lane & 8;
            const float s = up2 ? v[0] : v[1], k = up2 ? v[1] : v[0];
            v[0] = k + __shfl_xor_sync(0xffffffffu, s, 8);
            v[0] += __shfl_xor_sync(0xffffffffu, v[0], 4);
            if (!(lane & 4)) reinterpret_cast<float*>(smem + OFF_RED2)[warp * 16 + 4 * quad + ((lane & 16) ? 2 : 0) + ((lane & 8) ? 1 : 0)] = v[0];
        }
        cbar();
        TS(21);
        if (warp == 0) {
            const float* r2 = reinterpret_cast<const float*>(smem + OFF_RED2) + (lane & 1) * 64 + (lane >> 1);
            float s = (r2[0] + r2[16]) + (r2[32] + r2[48]);
            TSD(34, tid == 0, s);
            s += __shfl_xor_sync(0xffffffffu, s, 1);
            if (!(lane & 1)) *p_out = __float2bfloat16_rn(hres + bf16r(s));
            if (cta == 0 && lane == 0) st_rel32(&g_prog, 0u);
        }
    }
    TS(22);
    if (tid == 0) TSG(62);
}

typedef CUresult (*EncodeFn)(CUtensorMap*, CUtensorMapDataType, cuuint32_t, void*, const cuuint64_t*, const cuuint64_t*,
                             const cuuint32_t*, const cuuint32_t*, CUtensorMapInterleave, CUtensorMapSwizzle,
                             CUtensorMapL2promotion, CUtensorMapFloatOOBfill);

void encode(EncodeFn fn, CUtensorMap* m, const void* base, int rank, const cuuint64_t* dims, const cuuint64_t* strides,
            const cuuint32_t* box, CUtensorMapSwizzle sw, CUtensorMapL2promotion promo) {
    cuuint32_t es[3] = {1, 1, 1};
    fn(m, CU_TENSOR_MAP_DATA_TYPE_BFLOAT16, (cuuint32_t)rank, const_cast<void*>(base), dims, strides, box, es,
       CU_TENSOR_MAP_INTERLEAVE_NONE, sw, promo, CU_TENSOR_MAP_FLOAT_OOB_FILL_NONE);
}

}

extern "C" void kernel_launch(void* const* d_in, const int* in_sizes, int n_in, void* d_out, int out_size) {
    (void)in_sizes; (void)n_in; (void)out_size;
    static EncodeFn enc = nullptr;
    if (!enc) {
        void* fn = nullptr;
        cudaDriverEntryPointQueryResult qr;
        cudaGetDriverEntryPoint("cuTensorMapEncodeTiled", &fn, cudaEnableDefault, &qr);
        enc = (EncodeFn)fn;
        cudaFuncSetAttribute(fused_decode_kernel, cudaFuncAttributeMaxDynamicSharedMemorySize, SMEM_BYTES);
    }
    const void* x = d_in[0];
    Maps maps;
    {
        cuuint64_t dims[3] = {64, 262144, 2}; cuuint64_t str[2] = {256, 128}; cuuint32_t box[3] = {64, 128, 2};
        encode(enc, &maps.m[0], d_in[1], 3, dims, str, box, CU_TENSOR_MAP_SWIZZLE_128B, CU_TENSOR_MAP_L2_PROMOTION_L2_256B);
        encode(enc, &maps.m[1], d_in[2], 3, dims, str, box, CU_TENSOR_MAP_SWIZZLE_128B, CU_TENSOR_MAP_L2_PROMOTION_L2_256B);
    }
    {
        cuuint64_t dims[3] = {64, 262144, 2}; cuuint64_t str[2] = {256, 128}; cuuint32_t box[3] = {64, 32, 2};
        encode(enc, &maps.m[7], d_in[2], 3, dims, str, box, CU_TENSOR_MAP_SWIZZLE_128B, CU_TENSOR_MAP_L2_PROMOTION_L2_256B);
    }
    {
        cuuint64_t dims[3] = {4096, 512, 1}; cuuint64_t str[2] = {8192, 8192 * 512}; cuuint32_t box[3] = {32, 256, 1};
        encode(enc, &maps.m[2], d_in[3], 3, dims, str, box, CU_TENSOR_MAP_SWIZZLE_64B, CU_TENSOR_MAP_L2_PROMOTION_L2_128B);
    }
    {
        cuuint64_t dims[3] = {64, 4096, 8}; cuuint64_t str[2] = {1024, 128}; cuuint32_t box[3] = {64, 128, 2};
        encode(enc, &maps.m[3], d_in[4], 3, dims, str, box, CU_TENSOR_MAP_SWIZZLE_128B, CU_TENSOR_MAP_L2_PROMOTION_L2_256B);
    }
    {
        cuuint64_t dims[3] = {1792, 512, 1}; cuuint64_t str[2] = {3584, 3584 * 512}; cuuint32_t box[3] = {16, 256, 1};
        encode(enc, &maps.m[4], d_in[6], 3, dims, str, box, CU_TENSOR_MAP_SWIZZLE_32B, CU_TENSOR_MAP_L2_PROMOTION_L2_128B);
        encode(enc, &maps.m[5], d_in[7], 3, dims, str, box, CU_TENSOR_MAP_SWIZZLE_32B, CU_TENSOR_MAP_L2_PROMOTION_L2_128B);
    }
    {
        cuuint64_t dims[3] = {64, 1792, 8}; cuuint64_t str[2] = {1024, 128}; cuuint32_t box[3] = {64, 16, 4};
        encode(enc, &maps.m[6], d_in[8], 3, dims, str, box, CU_TENSOR_MAP_SWIZZLE_128B, CU_TENSOR_MAP_L2_PROMOTION_L2_256B);
    }
    fused_decode_kernel<<<NCTA, NTHREADS, SMEM_BYTES, cudaStreamPerThread>>>(maps, (const unsigned char*)d_in[1], (const unsigned char*)d_in[2],
        (const __nv_bfloat16*)x, (__nv_bfloat16*)d_out);
}
```

```cpp
#include <cuda_runtime.h>
#include <cuda_bf16.h>
#include <cuda.h>
#include <stdint.h>

namespace {

constexpr int NCTA      = 128;
constexpr int NTHREADS  = 320;
constexpr int SLOT      = 32768;
constexpr int NSLOT     = 6;
constexpr int NTILE     = 16;
constexpr int NFFN      = 112;
constexpr int DEPTH_LO  = 2;
constexpr int DEPTH_HI  = 3;
constexpr int LEAD_THR8 = 4;
constexpr int WDEPTH    = 4;
constexpr int SEQ_WO    = 33;
constexpr int NSEQ      = 34;
constexpr int SLOT_WGU  = 4, SLOT_WD = 5;
constexpr int DLY_F     = 500;
constexpr int DLY_F_IDLE = 1100;
constexpr int RESET_TILE = 8;
constexpr uint32_t SENT = 0xFFFFFFFFu;

constexpr int OFF_XN   = NSLOT * SLOT;
constexpr int XN_PITCH = 1040;
constexpr int OFF_QS   = OFF_XN + 4 * XN_PITCH;
constexpr int QS_PITCH = 272;
constexpr int OFF_P    = OFF_QS + 4 * QS_PITCH;
constexpr int OFF_RED  = OFF_P + 4 * QS_PITCH;
constexpr int OFF_MX   = OFF_RED + 4096;
constexpr int OFF_L    = OFF_MX + 64;
constexpr int OFF_ACT  = OFF_L + 128;
constexpr int OFF_RED2 = OFF_ACT + 128;
constexpr int OFF_CS   = OFF_RED2 + 512;
constexpr int OFF_ST   = OFF_CS + 512;
constexpr int OFF_BAR  = OFF_ST + 32;
constexpr int OFF_VAR  = OFF_BAR + 192;
constexpr int SMEM_USED = OFF_VAR + 64;
constexpr int SMEM_BYTES = SMEM_USED + 1024;
static_assert(OFF_RED % 16 == 0 && OFF_MX % 16 == 0 && OFF_ST % 8 == 0 && OFF_BAR % 8 == 0, "alignment");

__device__ uint2    g_q[4 * 2048];
__device__ float    g_partO[32 * 4 * 4 * 128];
__device__ float2   g_ml[32 * 4 * 4];
__device__ float    g_ypart[4 * 32 * 32 * 16];
__device__ uint16_t g_h[4 * 512];
__device__ float    g_dpart[4 * 32 * NFFN * 16];
__device__ unsigned g_cnt0, g_cnt1, g_prog;
#define TS(i)
#define TSX(i, cond)
#define TSG(i)
#define TSD(i, cond, dep)

__device__ __forceinline__ uint32_t smem_u32(const void* p) { return (uint32_t)__cvta_generic_to_shared(p); }
__device__ __forceinline__ void mbar_init(uint32_t bar, uint32_t cnt) {
    asm volatile("mbarrier.init.shared::cta.b64 [%0], %1;" ::"r"(bar), "r"(cnt) : "memory");
}
__device__ __forceinline__ void mbar_expect_tx(uint32_t bar, uint32_t bytes) {
    asm volatile("mbarrier.arrive.expect_tx.shared::cta.b64 _, [%0], %1;" ::"r"(bar), "r"(bytes) : "memory");
}
__device__ __forceinline__ void mbar_arrive(uint32_t bar) {
    asm volatile("mbarrier.arrive.shared::cta.b64 _, [%0];" ::"r"(bar) : "memory");
}
__device__ __forceinline__ bool mbar_try(uint32_t bar, uint32_t parity) {
    uint32_t ok;
    asm volatile("{\n.reg .pred p;\nmbarrier.try_wait.parity.shared::cta.b64 p, [%1], %2;\nselp.u32 %0, 1, 0, p;\n}"
                 : "=r"(ok) : "r"(bar), "r"(parity) : "memory");
    return ok != 0;
}
constexpr uint32_t SPIN_LIMIT = 1u << 22;
__device__ __forceinline__ void mbar_wait(uint32_t bar, uint32_t parity) {
    uint32_t it = 0;
    while (!mbar_try(bar, parity)) { if (++it > SPIN_LIMIT) __trap(); }
}
__device__ __forceinline__ void tma3d(uint32_t dst, const CUtensorMap* m, int c0, int c1, int c2, uint32_t bar, uint64_t pol) {
    asm volatile("cp.async.bulk.tensor.3d.shared::cluster.global.mbarrier::complete_tx::bytes.L2::cache_hint [%0], [%1, {%3, %4, %5}], [%2], %6;"
                 ::"r"(dst), "l"(m), "r"(bar), "r"(c0), "r"(c1), "r"(c2), "l"(pol) : "memory");
}
__device__ __forceinline__ void ldsm4(uint32_t (&r)[4], uint32_t addr) {
    asm volatile("ldmatrix.sync.aligned.m8n8.x4.shared.b16 {%0,%1,%2,%3}, [%4];"
                 : "=r"(r[0]), "=r"(r[1]), "=r"(r[2]), "=r"(r[3]) : "r"(addr) : "memory");
}
__device__ __forceinline__ void ldsm4t(uint32_t (&r)[4], uint32_t addr) {
    asm volatile("ldmatrix.sync.aligned.m8n8.x4.trans.shared.b16 {%0,%1,%2,%3}, [%4];"
                 : "=r"(r[0]), "=r"(r[1]), "=r"(r[2]), "=r"(r[3]) : "r"(addr) : "memory");
}
__device__ __forceinline__ void mma16816(float (&c)[4], const uint32_t (&a)[4], uint32_t b0, uint32_t b1) {
    asm volatile("mma.sync.aligned.m16n8k16.row.col.f32.bf16.bf16.f32 {%0,%1,%2,%3}, {%4,%5,%6,%7}, {%8,%9}, {%0,%1,%2,%3};"
                 : "+f"(c[0]), "+f"(c[1]), "+f"(c[2]), "+f"(c[3])
                 : "r"(a[0]), "r"(a[1]), "r"(a[2]), "r"(a[3]), "r"(b0), "r"(b1));
}
__device__ __forceinline__ void cbar() { asm volatile("bar.sync 1, 256;" ::: "memory"); }
__device__ __forceinline__ void bar_sync(int id, int n) { asm volatile("bar.sync %0, %1;" ::"r"(id), "r"(n) : "memory"); }
__device__ __forceinline__ void bar_arrive(int id, int n) { asm volatile("bar.arrive %0, %1;" ::"r"(id), "r"(n) : "memory"); }
__device__ __forceinline__ uint4 ld_poll4(const void* p) {
    uint4 v;
    asm volatile("ld.relaxed.gpu.global.v4.u32 {%0,%1,%2,%3}, [%4];" : "=r"(v.x), "=r"(v.y), "=r"(v.z), "=r"(v.w) : "l"(p) : "memory");
    return v;
}
__device__ __forceinline__ uint2 ld_poll2(const void* p) {
    uint2 v;
    asm volatile("ld.relaxed.gpu.global.v2.u32 {%0,%1}, [%2];" : "=r"(v.x), "=r"(v.y) : "l"(p) : "memory");
    return v;
}
__device__ __forceinline__ void st_rel32(void* p, uint32_t v) { asm volatile("st.relaxed.gpu.global.u32 [%0], %1;" ::"l"(p), "r"(v) : "memory"); }
__device__ __forceinline__ void st_rel16(void* p, uint16_t v) { asm volatile("st.relaxed.gpu.global.u16 [%0], %1;" ::"l"(p), "h"(v) : "memory"); }
__device__ __forceinline__ void st_rel64(void* p, uint32_t a, uint32_t b) { asm volatile("st.relaxed.gpu.global.v2.u32 [%0], {%1,%2};" ::"l"(p), "r"(a), "r"(b) : "memory"); }
__device__ __forceinline__ void st_rel128(void* p, uint32_t v) { asm volatile("st.relaxed.gpu.global.v4.u32 [%0], {%1,%1,%1,%1};" ::"l"(p), "r"(v) : "memory"); }
__device__ __forceinline__ uint32_t umax4(const uint4& v) { return max(max(v.x, v.y), max(v.z, v.w)); }
template <class T> __device__ __forceinline__ void pin(T*& p) { asm volatile("" : "+l"(p)); }
__device__ __forceinline__ bool valid8h(const uint4& v) {
    return (__vcmpeq2(v.x, SENT) | __vcmpeq2(v.y, SENT) | __vcmpeq2(v.z, SENT) | __vcmpeq2(v.w, SENT)) == 0;
}
struct Spin {
    uint32_t it = 0;
    __device__ __forceinline__ void tick() { if (++it > SPIN_LIMIT) __trap(); }
};
__device__ __forceinline__ uint32_t pack_bf16(float lo, float hi) {
    uint32_t r; asm("cvt.rn.bf16x2.f32 %0, %1, %2;" : "=r"(r) : "f"(hi), "f"(lo)); return r;
}
__device__ __forceinline__ void delay_cycles(int n) { if (n > 0) { const long long t0 = clock64(); while (clock64() - t0 < n) {} } }
__device__ __forceinline__ float bf16r(float x) { return __uint_as_float(pack_bf16(0.f, x) & 0xFFFF0000u); }
__device__ __forceinline__ float bf_lo(uint32_t v) { return __uint_as_float(v << 16); }
__device__ __forceinline__ float bf_hi(uint32_t v) { return __uint_as_float(v & 0xFFFF0000u); }
__device__ __forceinline__ uint32_t hmax2(uint32_t a, uint32_t b) {
    uint32_t r; asm("max.bf16x2 %0, %1, %2;" : "=r"(r) : "r"(a), "r"(b)); return r;
}
__device__ __forceinline__ float ex2(float x) { float r; asm("ex2.approx.ftz.f32 %0, %1;" : "=f"(r) : "f"(x)); return r; }

__device__ __forceinline__ float2 ln_stats(const uint4& a, const uint4& b, float (&v)[16]) {
    v[0] = bf_lo(a.x); v[1] = bf_hi(a.x); v[2] = bf_lo(a.y); v[3] = bf_hi(a.y);
    v[4] = bf_lo(a.z); v[5] = bf_hi(a.z); v[6] = bf_lo(a.w); v[7] = bf_hi(a.w);
    v[8] = bf_lo(b.x); v[9] = bf_hi(b.x); v[10] = bf_lo(b.y); v[11] = bf_hi(b.y);
    v[12] = bf_lo(b.z); v[13] = bf_hi(b.z); v[14] = bf_lo(b.w); v[15] = bf_hi(b.w);
    const float shift = __shfl_sync(0xffffffffu, v[0], 0);
    float s0 = 0.f, s1 = 0.f, s2 = 0.f, s3 = 0.f, q0 = 0.f, q1 = 0.f, q2 = 0.f, q3 = 0.f;
#pragma unroll
    for (int i = 0; i < 16; i += 4) {
        const float d0 = v[i] - shift, d1 = v[i + 1] - shift, d2 = v[i + 2] - shift, d3 = v[i + 3] - shift;
        s0 += d0; s1 += d1; s2 += d2; s3 += d3;
        q0 = fmaf(d0, d0, q0); q1 = fmaf(d1, d1, q1); q2 = fmaf(d2, d2, q2); q3 = fmaf(d3, d3, q3);
    }
    float s = (s0 + s1) + (s2 + s3), ss = (q0 + q1) + (q2 + q3);
#pragma unroll
    for (int o = 16; o > 0; o >>= 1) { s += __shfl_xor_sync(0xffffffffu, s, o); ss += __shfl_xor_sync(0xffffffffu, ss, o); }
    const float md = s * (1.0f / 512.0f);
    const float var = fmaxf(ss * (1.0f / 512.0f) - md * md, 0.f);
    const float m = bf16r(shift + md);
    float sq; asm("sqrt.approx.f32 %0, %1;" : "=f"(sq) : "f"(bf16r(bf16r(var) + 1e-5f)));
    const float sd = bf16r(sq);
    return make_float2(m, __fdividef(1.0f, sd));
}

struct Maps { CUtensorMap m[7]; };

__global__ void __launch_bounds__(NTHREADS, 1)
fused_decode_kernel(const __grid_constant__ Maps maps, const __nv_bfloat16* __restrict__ x, __nv_bfloat16* __restrict__ out)
{
    extern __shared__ __align__(1024) unsigned char smem_raw[];
    unsigned char* smem = smem_raw + ((1024u - (smem_u32(smem_raw) & 1023u)) & 1023u);
    const uint32_t sbase = smem_u32(smem);
    const uint32_t bar_full = sbase + OFF_BAR, bar_empty = sbase + OFF_BAR + 48, bar_ready = sbase + OFF_BAR + 96, bar_w = sbase + OFF_BAR + 104;
    volatile unsigned* vars = reinterpret_cast<volatile unsigned*>(smem + OFF_VAR);
    const int tid = threadIdx.x, warp = tid >> 5, lane = tid & 31;
    const int cta = blockIdx.x;

    if (tid == 0) TSG(0);
    if (warp == 8) {
        if (lane == 0) {
            for (int i = 0; i < NSLOT; i++) { mbar_init(bar_full + 8 * i, 1); mbar_init(bar_empty + 8 * i, 8); }
            mbar_init(bar_ready, 1);
            for (int i = 0; i < 6; i++) mbar_init(bar_w + 8 * i, 1);
            vars[1] = 0;
            asm volatile("fence.mbarrier_init.release.cluster;" ::: "memory");
        } else if (lane <= 7) {
            asm volatile("prefetch.tensormap [%0];" ::"l"(&maps.m[lane - 1]) : "memory");
        }
    }
    if (warp == 8) { __syncwarp(); bar_arrive(8, NTHREADS); } else bar_sync(8, NTHREADS);

    if (warp == 8) {
        if (lane == 0) {
            uint64_t pol;
            asm volatile("createpolicy.fractional.L2::evict_first.b64 %0, 1.0;" : "=l"(pol));
            const int key0 = cta * (NTILE * 128);
            int arrived = 0;
            unsigned grel = 0;
            int nkv = 0;
            for (int i = 0; i < NSEQ; i++) {
                const int slot = i % NSLOT;
                const bool is_w = (i == 0) || (i == SEQ_WO);
                if (i >= NSLOT) mbar_wait(bar_empty + 8 * slot, ((i / NSLOT) - 1) & 1);
                const int lead8 = (nkv * NCTA - (int)grel) / (NCTA / 8);
                const int d = (i > 2 && lead8 > LEAD_THR8) ? DEPTH_LO : DEPTH_HI;
                while (arrived < i - d + 1) { mbar_wait(bar_full + 8 * (arrived % NSLOT), (arrived / NSLOT) & 1); arrived++; }
                const uint32_t dst = sbase + slot * SLOT, fb = bar_full + 8 * slot;
                int mi, c0 = 0, c1 = 0, c2 = 0, nbox = 1;
                if (i == 0)            { mi = 2; c0 = cta * 32; nbox = 2; }
                else if (i == SEQ_WO)  { mi = 3; c1 = (cta >> 2) * 128; c2 = (cta & 3) * 2; }
                else                   { mi = nkv & 1; c1 = key0 + (nkv >> 1) * 128; }
                mbar_expect_tx(fb, 32768);
                for (int j = 0; j < nbox; j++) tma3d(dst + j * 16384, &maps.m[mi], c0, c1 + j * 256, c2, fb, pol);
                if (!is_w) {
                    if (nkv < 31) {
                        grel = atomicAdd(&g_prog, 1u);
                    } else {
                        asm volatile("red.relaxed.gpu.global.add.u32 [%0], 1;" ::"l"(&g_prog) : "memory");
                    }
                    nkv++;
                }
            }
            if (cta < NFFN) {
                mbar_wait(bar_empty + 8 * SLOT_WGU, (34 / NSLOT - 1) & 1);
                mbar_wait(bar_empty + 8 * SLOT_WD, (35 / NSLOT - 1) & 1);
                {
                    Spin sp; unsigned v;
                    while (true) {
                        asm volatile("ld.relaxed.gpu.global.u32 %0, [%1];" : "=r"(v) : "l"(&g_prog) : "memory");
                        if ((int)v >= NCTA * 32) break;
                        sp.tick(); __nanosleep(64);
                    }
                }
                mbar_wait(bar_full + 8 * (SEQ_WO % NSLOT), (SEQ_WO / NSLOT) & 1);
                TSX(26, true);
                for (int k = 0; k < 6; k++) {
                    if (k >= WDEPTH) mbar_wait(bar_w + 8 * (k - WDEPTH), 0);
                    mbar_expect_tx(bar_w + 8 * k, 8192);
                    const int mi = (k < 4) ? 4 + (k >> 1) : 6;
                    const int c0 = (k < 4) ? cta * 16 : 0, c1 = (k < 4) ? (k & 1) * 256 : cta * 16, c2 = (k < 4) ? 0 : (k - 4) * 4;
                    tma3d(sbase + SLOT_WGU * SLOT + k * 8192, &maps.m[mi], c0, c1, c2, bar_w + 8 * k, pol);
                }
            }
            TSX(20, true);
        }
        return;
    }

    const int pair = cta >> 2, split = cta & 3;

    if (warp == 9) {
        Spin sp;
        while (vars[1] < RESET_TILE) { sp.tick(); __nanosleep(256); }
        const unsigned epoch = vars[0];
#pragma unroll 1
        for (int u = lane; u < 128; u += 32) {
            st_rel128(&g_partO[((pair * 4 + (u >> 5)) * 4 + split) * 128 + (u & 31) * 4], SENT);
            const int seg = u >> 2;
            st_rel128(&g_ypart[(((seg >> 3) * 32 + (cta & 3) * 8 + (seg & 7)) * 32 + (cta >> 2)) * 16 + (u & 3) * 4], SENT);
        }
        if (lane < 4) st_rel64(&g_ml[(pair * 4 + lane) * 4 + split], SENT, SENT);
        if (lane < 2) st_rel128(&g_h[(cta >> 5) * 512 + (cta & 31) * 16 + lane * 8], SENT);
        if (cta < NFFN) {
#pragma unroll 1
            for (int e = lane; e < 512; e += 32) st_rel128(&g_dpart[((e >> 2) * NFFN + cta) * 16 + (e & 3) * 4], SENT);
        }
        __threadfence();
        __syncwarp();
        if (lane == 0) {
            atomicAdd(&g_cnt1, 1u);
            unsigned v; Spin sp2;
            while (true) {
                asm volatile("ld.acquire.gpu.global.u32 %0, [%1];" : "=r"(v) : "l"(&g_cnt1) : "memory");
                if ((int)(v - (epoch + 1) * NCTA) >= 0) break;
                sp2.tick(); __nanosleep(128);
            }
            mbar_arrive(bar_ready);
        }
        TSX(24, lane == 0);
        return;
    }

    const int r8 = lane >> 2, q4 = lane & 3;
    const int hp = q4 & 1, kh = q4 >> 1;
    constexpr float LOG2E = 1.4426950408889634f;
    const int bq = pair >> 3, gq = pair & 7;

    if (tid == 0) vars[0] = atomicAdd(&g_cnt0, 1u) >> 7;
    if (warp == 7) st_rel128(&g_q[(lane >> 3) * 2048 + cta * 16 + (lane & 7) * 2], 0u);
    float xres = 0.f;
    if (warp == 0) xres = __bfloat162float(x[(cta >> 5) * 512 + (cta & 31) * 16 + (lane >> 1)]);

    if (warp < 4) {
        const uint4* xr = reinterpret_cast<const uint4*>(x + warp * 512);
        const uint4 a = __ldg(xr + lane), b = __ldg(xr + 32 + lane);
        float v[16];
        const float2 st = ln_stats(a, b, v);
        uint32_t o[8];
#pragma unroll
        for (int i = 0; i < 8; i++) o[i] = pack_bf16(bf16r(v[2 * i] - st.x) * st.y, bf16r(v[2 * i + 1] - st.x) * st.y);
        unsigned char* row = smem + OFF_XN + warp * XN_PITCH;
        *reinterpret_cast<uint4*>(row + lane * 16) = make_uint4(o[0], o[1], o[2], o[3]);
        *reinterpret_cast<uint4*>(row + 512 + lane * 16) = make_uint4(o[4], o[5], o[6], o[7]);
    }
    cbar();
    const uint32_t tag = vars[0] + 1;

    {
        uint32_t bfr[4][2];
        {
            uint32_t t4[4];
#pragma unroll
            for (int u = 0; u < 2; u++) {
                ldsm4(t4, sbase + OFF_XN + (lane & 3) * XN_PITCH + (8 * warp + 4 * u + (lane >> 3)) * 16);
                bfr[2 * u][0] = t4[0]; bfr[2 * u][1] = t4[1]; bfr[2 * u + 1][0] = t4[2]; bfr[2 * u + 1][1] = t4[3];
            }
        }
        mbar_wait(bar_full + 0, 0);
        TS(2);
        float acc[2][4] = {};
#pragma unroll
        for (int ks = 0; ks < 4; ks++) {
            const int k = 64 * warp + 16 * ks + (lane & 7) + (lane >> 4) * 8;
#pragma unroll
            for (int mt = 0; mt < 2; mt++) {
                uint32_t a[4];
                const int chunk = 2 * mt + ((lane >> 3) & 1);
                ldsm4t(a, sbase + k * 64 + ((chunk ^ ((k >> 1) & 3)) << 4));
                mma16816(acc[mt], a, bfr[ks][0], bfr[ks][1]);
            }
        }
        __syncwarp();
        if (lane == 0) mbar_arrive(bar_empty + 0);
        float* red = reinterpret_cast<float*>(smem + OFF_RED);
#pragma unroll
        for (int mt = 0; mt < 2; mt++) {
            float2 v = kh ? make_float2(acc[mt][2], acc[mt][3]) : make_float2(acc[mt][0], acc[mt][1]);
            *reinterpret_cast<float2*>(red + ((warp * 2 + mt) * 16 + r8 + 8 * kh) * 4 + 2 * hp) = v;
        }
        cbar();
        if (tid < 64) {
            const int b = tid >> 4, c2 = tid & 15;
            float s0 = 0.f, s1 = 0.f;
            const int c0 = 2 * c2, c1 = 2 * c2 + 1;
#pragma unroll
            for (int ww = 0; ww < 8; ww++) {
                s0 += red[((ww * 2 + (c0 >> 4)) * 16 + (c0 & 15)) * 4 + b];
                s1 += red[((ww * 2 + (c1 >> 4)) * 16 + (c1 & 15)) * 4 + b];
            }
            st_rel64(&g_q[b * 2048 + cta * 16 + c2], pack_bf16(s0, s1), tag);
        }
        {
            const uint2* src = &g_q[bq * 2048 + gq * 256 + tid];
            uint2 v;
            Spin sp;
            while (true) { v = ld_poll2(src); if (__all_sync(0xffffffffu, v.y == tag)) break; sp.tick(); }
            *reinterpret_cast<uint32_t*>(smem + OFF_QS + (tid >> 6) * QS_PITCH + (tid & 63) * 4) = v.x;
        }
        cbar();
    }
    TS(3);
    uint32_t qf[8][2];
    {
        uint32_t t4[4];
#pragma unroll
        for (int u = 0; u < 4; u++) {
            ldsm4(t4, sbase + OFF_QS + (lane & 3) * QS_PITCH + (4 * u + (lane >> 3)) * 16);
            qf[2 * u][0] = t4[0]; qf[2 * u][1] = t4[1]; qf[2 * u + 1][0] = t4[2]; qf[2 * u + 1][1] = t4[3];
        }
    }

    const uint32_t voff = (warp >> 2) * 16384 + ((lane & 7) + (lane >> 4) * 8) * 128 +
                          ((((2 * warp + ((lane >> 3) & 1)) & 7) ^ (lane & 7)) << 4);
    const uint32_t poff = sbase + OFF_P + (lane & 3) * QS_PITCH + (lane >> 3) * 16;
    const uint32_t koff = (16 * warp + (lane & 7) + ((lane >> 3) & 1) * 8) * 128;
    const uint32_t kx = lane & 7, kc = lane >> 4;
    constexpr float SCALE = 0.08838834764831845f;
    uint32_t* mxbuf = reinterpret_cast<uint32_t*>(smem + OFF_MX);
    uint32_t M2 = 0xFF80FF80u;
    float l0 = 0.f, l1 = 0.f;
    float oacc[2][4] = {};
    int slot = 1; uint32_t ph = 0;

    for (int t = 0;; t++) {
        mbar_wait(bar_full + 8 * slot, ph);
        float sa[4] = {}, sb[4] = {};
        {
            const uint32_t kb = sbase + slot * SLOT + koff;
#pragma unroll
            for (int ks = 0; ks < 8; ks++) {
                uint32_t a[4];
                ldsm4(a, kb + (ks >> 2) * 16384 + (((2 * (ks & 3) + kc) ^ kx) << 4));
                if (ks & 1) mma16816(sb, a, qf[ks][0], qf[ks][1]); else mma16816(sa, a, qf[ks][0], qf[ks][1]);
            }
        }
        __syncwarp();
        if (lane == 0) mbar_arrive(bar_empty + 8 * slot);
        if (++slot == NSLOT) { slot = 0; ph ^= 1; }

        const float r0 = kh ? sa[2] + sb[2] : sa[0] + sb[0];
        const float r1 = kh ? sa[3] + sb[3] : sa[1] + sb[1];
        uint32_t sp = pack_bf16(r0, r1);
        sp = pack_bf16(bf_lo(sp) * SCALE, bf_hi(sp) * SCALE);
        uint32_t mx = sp;
#pragma unroll
        for (int o = 2; o <= 16; o <<= 1) mx = hmax2(mx, __shfl_xor_sync(0xffffffffu, mx, o));
        if (lane < 2) mxbuf[lane * 8 + warp] = mx;
        if (tid == 0) vars[1] = t + 1;
        TS(40 + t);
        cbar();
        {
            const uint4 m0 = *reinterpret_cast<const uint4*>(mxbuf + hp * 8), m1 = *reinterpret_cast<const uint4*>(mxbuf + hp * 8 + 4);
            uint32_t mt = hmax2(hmax2(hmax2(m0.x, m0.y), hmax2(m0.z, m0.w)), hmax2(hmax2(m1.x, m1.y), hmax2(m1.z, m1.w)));
            const uint32_t Mn = hmax2(M2, mt);
            const float a0 = ex2((bf_lo(M2) - bf_lo(Mn)) * LOG2E), a1 = ex2((bf_hi(M2) - bf_hi(Mn)) * LOG2E);
            const float p0 = ex2((bf_lo(sp) - bf_lo(Mn)) * LOG2E), p1 = ex2((bf_hi(sp) - bf_hi(Mn)) * LOG2E);
            M2 = Mn;
            l0 = fmaf(l0, a0, p0); l1 = fmaf(l1, a1, p1);
            const uint32_t pp = pack_bf16(p0, p1);
            unsigned char* pd = smem + OFF_P + (2 * hp) * QS_PITCH + (16 * warp + r8 + 8 * kh) * 2;
            *reinterpret_cast<uint16_t*>(pd) = (uint16_t)(pp & 0xFFFF);
            *reinterpret_cast<uint16_t*>(pd + QS_PITCH) = (uint16_t)(pp >> 16);
#pragma unroll
            for (int c = 0; c < 2; c++) { oacc[c][0] *= a0; oacc[c][1] *= a1; oacc[c][2] *= a0; oacc[c][3] *= a1; }
        }
        if (t == NTILE - 1) break;
        cbar();
        uint32_t pb[8][2];
        {
            uint32_t t4[4];
#pragma unroll
            for (int u = 0; u < 4; u++) {
                ldsm4(t4, poff + u * 64);
                pb[2 * u][0] = t4[0]; pb[2 * u][1] = t4[1]; pb[2 * u + 1][0] = t4[2]; pb[2 * u + 1][1] = t4[3];
            }
        }
        mbar_wait(bar_full + 8 * slot, ph);
        {
            const uint32_t vb = sbase + slot * SLOT + voff;
#pragma unroll
            for (int ks = 0; ks < 8; ks++) {
                uint32_t a[4];
                ldsm4t(a, vb + ks * 2048);
                mma16816(oacc[ks & 1], a, pb[ks][0], pb[ks][1]);
            }
        }
        __syncwarp();
        if (lane == 0) mbar_arrive(bar_empty + 8 * slot);
        if (++slot == NSLOT) { slot = 0; ph ^= 1; }
    }

    const int head = cta >> 2;
    float* p_partO = &g_partO[((pair * 4 + 2 * hp) * 4 + split) * 128 + 16 * warp + r8 + 8 * kh];
    float* p_dpart = &g_dpart[(((2 * hp) * 32 + 4 * warp) * NFFN + cta) * 16 + r8 + 8 * kh];
    const float* p_dsrc = &g_dpart[(cta * NFFN + (tid >> 2)) * 16 + (tid & 3) * 4];
    __nv_bfloat16* p_out = out + (cta >> 5) * 512 + (cta & 31) * 16 + (lane >> 1);
    pin(p_partO); pin(p_dpart); pin(p_dsrc); pin(p_out);

    {
        float s0 = l0, s1 = l1;
#pragma unroll
        for (int o = 2; o <= 16; o <<= 1) { s0 += __shfl_xor_sync(0xffffffffu, s0, o); s1 += __shfl_xor_sync(0xffffffffu, s1, o); }
        if (lane < 2) *reinterpret_cast<float2*>(smem + OFF_L + warp * 16 + lane * 8) = make_float2(s0, s1);
        mbar_wait(bar_ready, 0);
        cbar();
        if (warp == 0) {
            const uint32_t other = __shfl_sync(0xffffffffu, M2, lane >> 1);
            float l = 0.f;
#pragma unroll
            for (int ww = 0; ww < 8; ww++) l += *reinterpret_cast<const float*>(smem + OFF_L + ww * 16 + (lane & 3) * 4);
            const float m = (lane & 1) ? bf_hi(other) : bf_lo(other);
            if (lane < 4) st_rel64(&g_ml[(pair * 4 + lane) * 4 + split], __float_as_uint(m), __float_as_uint(l));
        }
        uint32_t pb[8][2];
        {
            uint32_t t4[4];
#pragma unroll
            for (int u = 0; u < 4; u++) {
                ldsm4(t4, poff + u * 64);
                pb[2 * u][0] = t4[0]; pb[2 * u][1] = t4[1]; pb[2 * u + 1][0] = t4[2]; pb[2 * u + 1][1] = t4[3];
            }
        }
        float o2[2][4] = {};
        {
            mbar_wait(bar_full + 8 * slot, ph);
            TS(30);
            const uint32_t vb = sbase + slot * SLOT + voff;
            uint32_t a[8][4];
#pragma unroll
            for (int ks = 0; ks < 8; ks++) ldsm4t(a[ks], vb + ks * 2048);
#pragma unroll
            for (int ks = 0; ks < 8; ks++) mma16816((ks & 2) ? o2[ks & 1] : oacc[ks & 1], a[ks], pb[ks][0], pb[ks][1]);
        }
        const float v0 = kh ? (oacc[0][2] + oacc[1][2]) + (o2[0][2] + o2[1][2]) : (oacc[0][0] + oacc[1][0]) + (o2[0][0] + o2[1][0]);
        const float v1 = kh ? (oacc[0][3] + oacc[1][3]) + (o2[0][3] + o2[1][3]) : (oacc[0][1] + oacc[1][1]) + (o2[0][1] + o2[1][1]);
        st_rel32(p_partO, __float_as_uint(v0));
        st_rel32(p_partO + 512, __float_as_uint(v1));
        TS(4);
    }

    float hres = 0.f;
    uint32_t df[4][4];
    if (warp < 4) {
        {
            const int ph_idx = (warp * 8 + (head >> 2)) * 4 + (head & 3);
            const float* po = &g_partO[ph_idx * 512 + lane * 4];
            const float* pm = reinterpret_cast<const float*>(&g_ml[ph_idx * 4]);
            uint4 o0, o1, o2, o3, ma, mb;
            Spin sp;
            while (true) {
                o0 = ld_poll4(po); o1 = ld_poll4(po + 128); o2 = ld_poll4(po + 256); o3 = ld_poll4(po + 384);
                ma = ld_poll4(pm); mb = ld_poll4(pm + 4);
                const uint32_t mxv = max(max(max(umax4(o0), umax4(o1)), max(umax4(o2), umax4(o3))), max(umax4(ma), umax4(mb)));
                if (__all_sync(0xffffffffu, mxv != SENT)) break;
                sp.tick();
            }
            TS(6);
            const float m0 = __uint_as_float(ma.x), m1 = __uint_as_float(ma.z), m2 = __uint_as_float(mb.x), m3 = __uint_as_float(mb.z);
            const float M = fmaxf(fmaxf(m0, m1), fmaxf(m2, m3));
            float w0 = ex2((m0 - M) * LOG2E), w1 = ex2((m1 - M) * LOG2E), w2 = ex2((m2 - M) * LOG2E), w3 = ex2((m3 - M) * LOG2E);
            const float L = w0 * __uint_as_float(ma.y) + w1 * __uint_as_float(ma.w) + w2 * __uint_as_float(mb.y) + w3 * __uint_as_float(mb.w);
            const float inv = __fdividef(1.0f, L);
            const float e0 = (w0 * __uint_as_float(o0.x) + w1 * __uint_as_float(o1.x) + w2 * __uint_as_float(o2.x) + w3 * __uint_as_float(o3.x)) * inv;
            const float e1 = (w0 * __uint_as_float(o0.y) + w1 * __uint_as_float(o1.y) + w2 * __uint_as_float(o2.y) + w3 * __uint_as_float(o3.y)) * inv;
            const float e2 = (w0 * __uint_as_float(o0.z) + w1 * __uint_as_float(o1.z) + w2 * __uint_as_float(o2.z) + w3 * __uint_as_float(o3.z)) * inv;
            const float e3 = (w0 * __uint_as_float(o0.w) + w1 * __uint_as_float(o1.w) + w2 * __uint_as_float(o2.w) + w3 * __uint_as_float(o3.w)) * inv;
            *reinterpret_cast<uint2*>(smem + OFF_QS + warp * QS_PITCH + lane * 8) = make_uint2(pack_bf16(e0, e1), pack_bf16(e2, e3));
            TSD(31, tid == 0, e0 + e1 + e2 + e3);
            bar_arrive(2, 256);
        }
        {
            const float* src = &g_ypart[(cta * 32 + 8 * warp + (lane >> 2)) * 16 + (lane & 3) * 4];
            uint16_t* p_h = &g_h[(cta >> 5) * 512 + (cta & 31) * 16 + (lane >> 1)];
            pin(p_h);
            uint4 y;
            Spin sp;
            while (true) {
                y = ld_poll4(src);
                if (__all_sync(0xffffffffu, umax4(y) != SENT)) break;
                sp.tick();
            }
            TS(9);
            const bool up = lane & 16, up2 = lane & 8;
            const float a0 = __uint_as_float(y.x), a1 = __uint_as_float(y.y), a2 = __uint_as_float(y.z), a3 = __uint_as_float(y.w);
            const float v0 = (up ? a2 : a0) + __shfl_xor_sync(0xffffffffu, up ? a0 : a2, 16);
            const float v1 = (up ? a3 : a1) + __shfl_xor_sync(0xffffffffu, up ? a1 : a3, 16);
            float v = (up2 ? v1 : v0) + __shfl_xor_sync(0xffffffffu, up2 ? v0 : v1, 8);
            v += __shfl_xor_sync(0xffffffffu, v, 4);
            float* rc = reinterpret_cast<float*>(smem + OFF_RED2);
            if (!(lane & 4)) rc[warp * 16 + 4 * (lane & 3) + (up ? 2 : 0) + (up2 ? 1 : 0)] = v;
            bar_sync(7, 128);
            if (warp == 0) {
                const float* r2 = rc + (lane & 1) * 32 + (lane >> 1);
                float t = r2[0] + r2[16];
                t += __shfl_xor_sync(0xffffffffu, t, 1);
                hres = bf16r(xres + bf16r(t));
                if (!(lane & 1)) st_rel16(p_h, (uint16_t)(__float_as_uint(hres) >> 16));
                TS(10);
            }
        }
        {
            const uint4* hr = reinterpret_cast<const uint4*>(g_h + warp * 512);
            uint4 a, b;
            Spin sp;
            while (true) {
                a = ld_poll4(hr + lane); b = ld_poll4(hr + 32 + lane);
                if (__all_sync(0xffffffffu, valid8h(a) & valid8h(b))) break;
                sp.tick();
            }
            TS(13);
            if (cta < NFFN) {
                unsigned char* row = smem + OFF_XN + warp * XN_PITCH;
                *reinterpret_cast<uint4*>(row + lane * 16) = a;
                *reinterpret_cast<uint4*>(row + 512 + lane * 16) = b;
                bar_arrive(3, 256);
                float v[16];
                const float2 st = ln_stats(a, b, v);
                if (lane == 0) *reinterpret_cast<float2*>(smem + OFF_ST + warp * 8) = st;
                bar_arrive(4, 256);
                TS(14);
                mbar_wait(bar_w + 32, 0); mbar_wait(bar_w + 40, 0);
                const uint32_t wb = sbase + SLOT_WD * SLOT + warp * 2048 + ((lane & 7) + (lane >> 4) * 8) * 128;
#pragma unroll
                for (int i = 0; i < 4; i++) ldsm4t(df[i], wb + (((2 * i + ((lane >> 3) & 1)) ^ (lane & 7)) << 4));
            }
        }
    } else {
        const int m = warp - 4;
        {
            uint32_t af[2][8][4];
            float* p_y = &g_ypart[(((2 * hp) * 32 + (cta & 3) * 8 + 2 * m) * 32 + head) * 16 + r8 + 8 * kh];
            pin(p_y);
            mbar_wait(bar_full + 8 * (SEQ_WO % NSLOT), (SEQ_WO / NSLOT) & 1);
#pragma unroll
            for (int i = 0; i < 2; i++) {
                const int j = 2 * m + i;
                const uint32_t wb = sbase + (SEQ_WO % NSLOT) * SLOT + (j >> 2) * 16384 + ((lane & 7) + (lane >> 4) * 8) * 128 +
                                    ((((2 * j + ((lane >> 3) & 1)) & 7) ^ (lane & 7)) << 4);
#pragma unroll
                for (int ks = 0; ks < 8; ks++) ldsm4t(af[i][ks], wb + ks * 2048);
            }
            TSX(5, tid == 128);
            bar_sync(2, 256);
            TSX(7, tid == 128);
            float acc[2][2][4] = {};
            uint32_t t4[4][4];
#pragma unroll
            for (int u = 0; u < 4; u++) ldsm4(t4[u], sbase + OFF_QS + (lane & 3) * QS_PITCH + (4 * u + (lane >> 3)) * 16);
            TSD(37, tid == 128, __uint_as_float(t4[0][0]));
#pragma unroll
            for (int u = 0; u < 4; u++) {
#pragma unroll
                for (int i = 0; i < 2; i++) {
                    mma16816(acc[i][0], af[i][2 * u], t4[u][0], t4[u][1]);
                    mma16816(acc[i][1], af[i][2 * u + 1], t4[u][2], t4[u][3]);
                }
            }
#pragma unroll
            for (int i = 0; i < 2; i++) {
                const float v0 = kh ? acc[i][0][2] + acc[i][1][2] : acc[i][0][0] + acc[i][1][0];
                const float v1 = kh ? acc[i][0][3] + acc[i][1][3] : acc[i][0][1] + acc[i][1][1];
                st_rel32(p_y + i * 32 * 16, __float_as_uint(v0));
                st_rel32(p_y + i * 32 * 16 + 32 * 32 * 16, __float_as_uint(v1));
            }
            TSX(8, tid == 128);
        }
        if (cta < NFFN) {
            uint32_t gf[8][2][4];
            mbar_wait(bar_w, 0); mbar_wait(bar_w + 8, 0); mbar_wait(bar_w + 16, 0); mbar_wait(bar_w + 24, 0);
#pragma unroll
            for (int ks = 0; ks < 8; ks++) {
                const int k = 128 * m + 16 * ks + (lane & 7) + (lane >> 4) * 8;
                const uint32_t a = sbase + SLOT_WGU * SLOT + k * 32 + ((((lane >> 3) & 1) ^ ((k >> 2) & 1)) << 4);
                ldsm4t(gf[ks][0], a);
                ldsm4t(gf[ks][1], a + 16384);
            }
            TSX(11, tid == 128);
            float sg = 0.f, su = 0.f;
            {
                float cs[2][4] = {};
#pragma unroll
                for (int ks = 0; ks < 8; ks++) { mma16816(cs[0], gf[ks][0], 0x3F803F80u, 0x3F803F80u); mma16816(cs[1], gf[ks][1], 0x3F803F80u, 0x3F803F80u); }
                float* csb = reinterpret_cast<float*>(smem + OFF_CS);
                if (q4 == 0) {
                    csb[(m * 2 + 0) * 16 + r8] = cs[0][0]; csb[(m * 2 + 0) * 16 + r8 + 8] = cs[0][2];
                    csb[(m * 2 + 1) * 16 + r8] = cs[1][0]; csb[(m * 2 + 1) * 16 + r8 + 8] = cs[1][2];
                }
                bar_sync(5, 128);
                const int c = (tid & 63) >> 2;
#pragma unroll
                for (int ww = 0; ww < 4; ww++) { sg += csb[(ww * 2) * 16 + c]; su += csb[(ww * 2 + 1) * 16 + c]; }
            }
            const uint32_t wdb = sbase + SLOT_WD * SLOT + warp * 2048 + ((lane & 7) + (lane >> 4) * 8) * 128;
            const bool have_wd = __all_sync(0xffffffffu, mbar_try(bar_w + 32, 0) && mbar_try(bar_w + 40, 0));
            if (have_wd) {
#pragma unroll
                for (int i = 0; i < 4; i++) ldsm4t(df[i], wdb + (((2 * i + ((lane >> 3) & 1)) ^ (lane & 7)) << 4));
            }
            TSX(12, tid == 128);
            bar_sync(3, 256);
            float acc[2][2][4] = {};
            uint32_t t4[4][4];
#pragma unroll
            for (int u = 0; u < 4; u++) ldsm4(t4[u], sbase + OFF_XN + (lane & 3) * XN_PITCH + (16 * m + 4 * u + (lane >> 3)) * 16);
            TSD(27, tid == 128, __uint_as_float(t4[0][0]));
#pragma unroll
            for (int u = 0; u < 4; u++) {
#pragma unroll
                for (int i = 0; i < 2; i++) {
                    mma16816(acc[i][0], gf[2 * u][i], t4[u][0], t4[u][1]);
                    mma16816(acc[i][1], gf[2 * u + 1][i], t4[u][2], t4[u][3]);
                }
            }
            TSD(28, tid == 128, acc[1][1][0] + acc[0][0][0] + acc[0][1][0] + acc[1][0][0]);
            float* red = reinterpret_cast<float*>(smem + OFF_RED);
#pragma unroll
            for (int i = 0; i < 2; i++) {
                const float2 v = kh ? make_float2(acc[i][0][2] + acc[i][1][2], acc[i][0][3] + acc[i][1][3])
                                    : make_float2(acc[i][0][0] + acc[i][1][0], acc[i][0][1] + acc[i][1][1]);
                *reinterpret_cast<float2*>(red + ((m * 2 + i) * 16 + r8 + 8 * kh) * 4 + 2 * hp) = v;
            }
            bar_sync(4, 256);
            TSX(16, tid == 128);
            if (tid < 192) {
                const int c = (tid & 63) >> 2, b = tid & 3;
                const float2 st = *reinterpret_cast<const float2*>(smem + OFF_ST + b * 8);
                float g = 0.f, u = 0.f;
#pragma unroll
                for (int ww = 0; ww < 4; ww++) { g += red[((ww * 2) * 16 + c) * 4 + b]; u += red[((ww * 2 + 1) * 16 + c) * 4 + b]; }
                TSD(29, tid == 128, g + u + st.x);
                g = bf16r((g - st.x * sg) * st.y); u = bf16r((u - st.x * su) * st.y);
                const float inner = 0.7978845608028654f * (g + 0.044715f * g * g * g);
                const float th = 1.0f - __fdividef(2.0f, __expf(2.0f * inner) + 1.0f);
                const float ge = bf16r(0.5f * g * (1.0f + th));
                *reinterpret_cast<__nv_bfloat16*>(smem + OFF_ACT + b * 32 + c * 2) = __float2bfloat16_rn(ge * u);
                TSD(32, tid == 128, ge * u);
            }
            if (!have_wd) {
                mbar_wait(bar_w + 32, 0); mbar_wait(bar_w + 40, 0);
#pragma unroll
                for (int i = 0; i < 4; i++) ldsm4t(df[i], wdb + (((2 * i + ((lane >> 3) & 1)) ^ (lane & 7)) << 4));
            }
        }
    }
    if (cta < NFFN) {
        bar_sync(6, 256);
        TS(17);
        const uint32_t b0 = *reinterpret_cast<const uint32_t*>(smem + OFF_ACT + (r8 & 3) * 32 + q4 * 4);
        const uint32_t b1 = *reinterpret_cast<const uint32_t*>(smem + OFF_ACT + (r8 & 3) * 32 + 16 + q4 * 4);
        TSD(33, tid == 0, __uint_as_float(b0));
        float c[4][4] = {};
#pragma unroll
        for (int i = 0; i < 4; i++) mma16816(c[i], df[i], b0, b1);
#pragma unroll
        for (int i = 0; i < 4; i++) {
            st_rel32(p_dpart + i * NFFN * 16, __float_as_uint(kh ? c[i][2] : c[i][0]));
            st_rel32(p_dpart + i * NFFN * 16 + 32 * NFFN * 16, __float_as_uint(kh ? c[i][3] : c[i][1]));
        }
        TS(18);
    } else {
        bar_sync(6, 256);
        delay_cycles(DLY_F_IDLE);
    }

    {
        const int quad = tid & 3;
        const bool two = (tid >> 2) + 64 < NFFN;
        uint4 a, b = make_uint4(0, 0, 0, 0);
        Spin sp;
        delay_cycles(DLY_F);
        while (true) {
            a = ld_poll4(p_dsrc);
            if (two) b = ld_poll4(p_dsrc + 64 * 16);
            if (__all_sync(0xffffffffu, max(umax4(a), umax4(b)) != SENT)) break;
            sp.tick();
        }
        TS(19);
        float v[4] = {__uint_as_float(a.x) + __uint_as_float(b.x), __uint_as_float(a.y) + __uint_as_float(b.y),
                      __uint_as_float(a.z) + __uint_as_float(b.z), __uint_as_float(a.w) + __uint_as_float(b.w)};
        {
            const bool up = lane & 16;
            const float s0 = up ? v[0] : v[2], s1 = up ? v[1] : v[3];
            const float k0 = up ? v[2] : v[0], k1 = up ? v[3] : v[1];
            v[0] = k0 + __shfl_xor_sync(0xffffffffu, s0, 16);
            v[1] = k1 + __shfl_xor_sync(0xffffffffu, s1, 16);
            const bool up2 = lane & 8;
            const float s = up2 ? v[0] : v[1], k = up2 ? v[1] : v[0];
            v[0] = k + __shfl_xor_sync(0xffffffffu, s, 8);
            v[0] += __shfl_xor_sync(0xffffffffu, v[0], 4);
            if (!(lane & 4)) reinterpret_cast<float*>(smem + OFF_RED2)[warp * 16 + 4 * quad + ((lane & 16) ? 2 : 0) + ((lane & 8) ? 1 : 0)] = v[0];
        }
        cbar();
        TS(21);
        if (warp == 0) {
            const float* r2 = reinterpret_cast<const float*>(smem + OFF_RED2) + (lane & 1) * 64 + (lane >> 1);
            float s = (r2[0] + r2[16]) + (r2[32] + r2[48]);
            TSD(34, tid == 0, s);
            s += __shfl_xor_sync(0xffffffffu, s, 1);
            if (!(lane & 1)) *p_out = __float2bfloat16_rn(hres + bf16r(s));
            if (cta == 0 && lane == 0) st_rel32(&g_prog, 0u);
        }
    }
    TS(22);
    if (tid == 0) TSG(62);
}

typedef CUresult (*EncodeFn)(CUtensorMap*, CUtensorMapDataType, cuuint32_t, void*, const cuuint64_t*, const cuuint64_t*,
                             const cuuint32_t*, const cuuint32_t*, CUtensorMapInterleave, CUtensorMapSwizzle,
                             CUtensorMapL2promotion, CUtensorMapFloatOOBfill);

void encode(EncodeFn fn, CUtensorMap* m, const void* base, int rank, const cuuint64_t* dims, const cuuint64_t* strides,
            const cuuint32_t* box, CUtensorMapSwizzle sw, CUtensorMapL2promotion promo) {
    cuuint32_t es[3] = {1, 1, 1};
    fn(m, CU_TENSOR_MAP_DATA_TYPE_BFLOAT16, (cuuint32_t)rank, const_cast<void*>(base), dims, strides, box, es,
       CU_TENSOR_MAP_INTERLEAVE_NONE, sw, promo, CU_TENSOR_MAP_FLOAT_OOB_FILL_NONE);
}

}

extern "C" void kernel_launch(void* const* d_in, const int* in_sizes, int n_in, void* d_out, int out_size) {
    (void)in_sizes; (void)n_in; (void)out_size;
    static EncodeFn enc = nullptr;
    if (!enc) {
        void* fn = nullptr;
        cudaDriverEntryPointQueryResult qr;
        cudaGetDriverEntryPoint("cuTensorMapEncodeTiled", &fn, cudaEnableDefault, &qr);
        enc = (EncodeFn)fn;
        cudaFuncSetAttribute(fused_decode_kernel, cudaFuncAttributeMaxDynamicSharedMemorySize, SMEM_BYTES);
    }
    const void* x = d_in[0];
    Maps maps;
    {
        cuuint64_t dims[3] = {64, 262144, 2}; cuuint64_t str[2] = {256, 128}; cuuint32_t box[3] = {64, 128, 2};
        encode(enc, &maps.m[0], d_in[1], 3, dims, str, box, CU_TENSOR_MAP_SWIZZLE_128B, CU_TENSOR_MAP_L2_PROMOTION_L2_256B);
        encode(enc, &maps.m[1], d_in[2], 3, dims, str, box, CU_TENSOR_MAP_SWIZZLE_128B, CU_TENSOR_MAP_L2_PROMOTION_L2_256B);
    }
    {
        cuuint64_t dims[3] = {4096, 512, 1}; cuuint64_t str[2] = {8192, 8192 * 512}; cuuint32_t box[3] = {32, 256, 1};
        encode(enc, &maps.m[2], d_in[3], 3, dims, str, box, CU_TENSOR_MAP_SWIZZLE_64B, CU_TENSOR_MAP_L2_PROMOTION_L2_128B);
    }
    {
        cuuint64_t dims[3] = {64, 4096, 8}; cuuint64_t str[2] = {1024, 128}; cuuint32_t box[3] = {64, 128, 2};
        encode(enc, &maps.m[3], d_in[4], 3, dims, str, box, CU_TENSOR_MAP_SWIZZLE_128B, CU_TENSOR_MAP_L2_PROMOTION_L2_256B);
    }
    {
        cuuint64_t dims[3] = {1792, 512, 1}; cuuint64_t str[2] = {3584, 3584 * 512}; cuuint32_t box[3] = {16, 256, 1};
        encode(enc, &maps.m[4], d_in[6], 3, dims, str, box, CU_TENSOR_MAP_SWIZZLE_32B, CU_TENSOR_MAP_L2_PROMOTION_L2_128B);
        encode(enc, &maps.m[5], d_in[7], 3, dims, str, box, CU_TENSOR_MAP_SWIZZLE_32B, CU_TENSOR_MAP_L2_PROMOTION_L2_128B);
    }
    {
        cuuint64_t dims[3] = {64, 1792, 8}; cuuint64_t str[2] = {1024, 128}; cuuint32_t box[3] = {64, 16, 4};
        encode(enc, &maps.m[6], d_in[8], 3, dims, str, box, CU_TENSOR_MAP_SWIZZLE_128B, CU_TENSOR_MAP_L2_PROMOTION_L2_256B);
    }
    fused_decode_kernel<<<NCTA, NTHREADS, SMEM_BYTES, cudaStreamPerThread>>>(maps, (const __nv_bfloat16*)x, (__nv_bfloat16*)d_out);
}
```

```cpp
#include <cuda_runtime.h>
#include <cuda_bf16.h>
#include <cuda.h>
#include <stdint.h>

namespace {

constexpr int NCTA      = 128;
constexpr int NTHREADS  = 320;
constexpr int SLOT      = 32768;
constexpr int NSLOT     = 6;
constexpr int NTILE     = 16;
constexpr int NFFN      = 112;
constexpr int DEPTH_LO  = 2;
constexpr int DEPTH_HI  = 3;
constexpr int LEAD_THR8 = 4;
constexpr int WO_MARGIN = 112;
constexpr int WDEPTH    = 4;
constexpr int SEQ_WO    = 33;
constexpr int NSEQ      = 34;
constexpr int SLOT_WGU  = 4, SLOT_WD = 5;
constexpr int DLY_F     = 500;
constexpr int DLY_F_IDLE = 1100;
constexpr int RESET_TILE = 8;
constexpr uint32_t SENT = 0xFFFFFFFFu;

constexpr int OFF_XN   = NSLOT * SLOT;
constexpr int XN_PITCH = 1040;
constexpr int OFF_QS   = OFF_XN + 4 * XN_PITCH;
constexpr int QS_PITCH = 272;
constexpr int OFF_P    = OFF_QS + 4 * QS_PITCH;
constexpr int OFF_RED  = OFF_P + 4 * QS_PITCH;
constexpr int OFF_MX   = OFF_RED + 4096;
constexpr int OFF_L    = OFF_MX + 64;
constexpr int OFF_ACT  = OFF_L + 128;
constexpr int OFF_RED2 = OFF_ACT + 128;
constexpr int OFF_CS   = OFF_RED2 + 512;
constexpr int OFF_ST   = OFF_CS + 512;
constexpr int OFF_BAR  = OFF_ST + 32;
constexpr int OFF_VAR  = OFF_BAR + 192;
constexpr int SMEM_USED = OFF_VAR + 64;
constexpr int SMEM_BYTES = SMEM_USED + 1024;
static_assert(OFF_RED % 16 == 0 && OFF_MX % 16 == 0 && OFF_ST % 8 == 0 && OFF_BAR % 8 == 0, "alignment");

__device__ uint2    g_q[4 * 2048];
__device__ float    g_partO[32 * 4 * 4 * 128];
__device__ float2   g_ml[32 * 4 * 4];
__device__ float    g_ypart[4 * 32 * 32 * 16];
__device__ uint16_t g_h[4 * 512];
__device__ float    g_dpart[4 * 32 * NFFN * 16];
__device__ unsigned g_cnt0, g_cnt1, g_prog;

__device__ __forceinline__ uint32_t smem_u32(const void* p) { return (uint32_t)__cvta_generic_to_shared(p); }
__device__ __forceinline__ void mbar_init(uint32_t bar, uint32_t cnt) {
    asm volatile("mbarrier.init.shared::cta.b64 [%0], %1;" ::"r"(bar), "r"(cnt) : "memory");
}
__device__ __forceinline__ void mbar_expect_tx(uint32_t bar, uint32_t bytes) {
    asm volatile("mbarrier.arrive.expect_tx.shared::cta.b64 _, [%0], %1;" ::"r"(bar), "r"(bytes) : "memory");
}
__device__ __forceinline__ void mbar_arrive(uint32_t bar) {
    asm volatile("mbarrier.arrive.shared::cta.b64 _, [%0];" ::"r"(bar) : "memory");
}
__device__ __forceinline__ bool mbar_try(uint32_t bar, uint32_t parity) {
    uint32_t ok;
    asm volatile("{\n.reg .pred p;\nmbarrier.try_wait.parity.shared::cta.b64 p, [%1], %2;\nselp.u32 %0, 1, 0, p;\n}"
                 : "=r"(ok) : "r"(bar), "r"(parity) : "memory");
    return ok != 0;
}
constexpr uint32_t SPIN_LIMIT = 1u << 22;
__device__ __forceinline__ void mbar_wait(uint32_t bar, uint32_t parity) {
    uint32_t it = 0;
    while (!mbar_try(bar, parity)) { if (++it > SPIN_LIMIT) __trap(); }
}
__device__ __forceinline__ void tma3d(uint32_t dst, const CUtensorMap* m, int c0, int c1, int c2, uint32_t bar, uint64_t pol) {
    asm volatile("cp.async.bulk.tensor.3d.shared::cluster.global.mbarrier::complete_tx::bytes.L2::cache_hint [%0], [%1, {%3, %4, %5}], [%2], %6;"
                 ::"r"(dst), "l"(m), "r"(bar), "r"(c0), "r"(c1), "r"(c2), "l"(pol) : "memory");
}
__device__ __forceinline__ void ldsm4(uint32_t (&r)[4], uint32_t addr) {
    asm volatile("ldmatrix.sync.aligned.m8n8.x4.shared.b16 {%0,%1,%2,%3}, [%4];"
                 : "=r"(r[0]), "=r"(r[1]), "=r"(r[2]), "=r"(r[3]) : "r"(addr) : "memory");
}
__device__ __forceinline__ void ldsm4t(uint32_t (&r)[4], uint32_t addr) {
    asm volatile("ldmatrix.sync.aligned.m8n8.x4.trans.shared.b16 {%0,%1,%2,%3}, [%4];"
                 : "=r"(r[0]), "=r"(r[1]), "=r"(r[2]), "=r"(r[3]) : "r"(addr) : "memory");
}
__device__ __forceinline__ void mma16816(float (&c)[4], const uint32_t (&a)[4], uint32_t b0, uint32_t b1) {
    asm volatile("mma.sync.aligned.m16n8k16.row.col.f32.bf16.bf16.f32 {%0,%1,%2,%3}, {%4,%5,%6,%7}, {%8,%9}, {%0,%1,%2,%3};"
                 : "+f"(c[0]), "+f"(c[1]), "+f"(c[2]), "+f"(c[3])
                 : "r"(a[0]), "r"(a[1]), "r"(a[2]), "r"(a[3]), "r"(b0), "r"(b1));
}
__device__ __forceinline__ void cbar() { asm volatile("bar.sync 1, 256;" ::: "memory"); }
__device__ __forceinline__ void bar_sync(int id, int n) { asm volatile("bar.sync %0, %1;" ::"r"(id), "r"(n) : "memory"); }
__device__ __forceinline__ void bar_arrive(int id, int n) { asm volatile("bar.arrive %0, %1;" ::"r"(id), "r"(n) : "memory"); }
__device__ __forceinline__ uint4 ld_poll4(const void* p) {
    uint4 v;
    asm volatile("ld.relaxed.gpu.global.v4.u32 {%0,%1,%2,%3}, [%4];" : "=r"(v.x), "=r"(v.y), "=r"(v.z), "=r"(v.w) : "l"(p) : "memory");
    return v;
}
__device__ __forceinline__ uint2 ld_poll2(const void* p) {
    uint2 v;
    asm volatile("ld.relaxed.gpu.global.v2.u32 {%0,%1}, [%2];" : "=r"(v.x), "=r"(v.y) : "l"(p) : "memory");
    return v;
}
__device__ __forceinline__ void st_rel32(void* p, uint32_t v) { asm volatile("st.relaxed.gpu.global.u32 [%0], %1;" ::"l"(p), "r"(v) : "memory"); }
__device__ __forceinline__ void st_rel16(void* p, uint16_t v) { asm volatile("st.relaxed.gpu.global.u16 [%0], %1;" ::"l"(p), "h"(v) : "memory"); }
__device__ __forceinline__ void st_rel64(void* p, uint32_t a, uint32_t b) { asm volatile("st.relaxed.gpu.global.v2.u32 [%0], {%1,%2};" ::"l"(p), "r"(a), "r"(b) : "memory"); }
__device__ __forceinline__ void st_rel128(void* p, uint32_t v) { asm volatile("st.relaxed.gpu.global.v4.u32 [%0], {%1,%1,%1,%1};" ::"l"(p), "r"(v) : "memory"); }
__device__ __forceinline__ uint32_t umax4(const uint4& v) { return max(max(v.x, v.y), max(v.z, v.w)); }
template <class T> __device__ __forceinline__ void pin(T*& p) { asm volatile("" : "+l"(p)); }
__device__ __forceinline__ bool valid8h(const uint4& v) {
    return (__vcmpeq2(v.x, SENT) | __vcmpeq2(v.y, SENT) | __vcmpeq2(v.z, SENT) | __vcmpeq2(v.w, SENT)) == 0;
}
struct Spin {
    uint32_t it = 0;
    __device__ __forceinline__ void tick() { if (++it > SPIN_LIMIT) __trap(); }
};
__device__ __forceinline__ void wait_progress(int n) {
    Spin sp; unsigned v;
    while (true) {
        asm volatile("ld.relaxed.gpu.global.u32 %0, [%1];" : "=r"(v) : "l"(&g_prog) : "memory");
        if ((int)v >= n) break;
        sp.tick(); __nanosleep(64);
    }
}
__device__ __forceinline__ uint32_t pack_bf16(float lo, float hi) {
    uint32_t r; asm("cvt.rn.bf16x2.f32 %0, %1, %2;" : "=r"(r) : "f"(hi), "f"(lo)); return r;
}
__device__ __forceinline__ void delay_cycles(int n) { if (n > 0) { const long long t0 = clock64(); while (clock64() - t0 < n) {} } }
__device__ __forceinline__ float bf16r(float x) { return __uint_as_float(pack_bf16(0.f, x) & 0xFFFF0000u); }
__device__ __forceinline__ float bf_lo(uint32_t v) { return __uint_as_float(v << 16); }
__device__ __forceinline__ float bf_hi(uint32_t v) { return __uint_as_float(v & 0xFFFF0000u); }
__device__ __forceinline__ uint32_t hmax2(uint32_t a, uint32_t b) {
    uint32_t r; asm("max.bf16x2 %0, %1, %2;" : "=r"(r) : "r"(a), "r"(b)); return r;
}
__device__ __forceinline__ float ex2(float x) { float r; asm("ex2.approx.ftz.f32 %0, %1;" : "=f"(r) : "f"(x)); return r; }

__device__ __forceinline__ float2 ln_stats(const uint4& a, const uint4& b, float (&v)[16]) {
    v[0] = bf_lo(a.x); v[1] = bf_hi(a.x); v[2] = bf_lo(a.y); v[3] = bf_hi(a.y);
    v[4] = bf_lo(a.z); v[5] = bf_hi(a.z); v[6] = bf_lo(a.w); v[7] = bf_hi(a.w);
    v[8] = bf_lo(b.x); v[9] = bf_hi(b.x); v[10] = bf_lo(b.y); v[11] = bf_hi(b.y);
    v[12] = bf_lo(b.z); v[13] = bf_hi(b.z); v[14] = bf_lo(b.w); v[15] = bf_hi(b.w);
    const float shift = __shfl_sync(0xffffffffu, v[0], 0);
    float s0 = 0.f, s1 = 0.f, s2 = 0.f, s3 = 0.f, q0 = 0.f, q1 = 0.f, q2 = 0.f, q3 = 0.f;
#pragma unroll
    for (int i = 0; i < 16; i += 4) {
        const float d0 = v[i] - shift, d1 = v[i + 1] - shift, d2 = v[i + 2] - shift, d3 = v[i + 3] - shift;
        s0 += d0; s1 += d1; s2 += d2; s3 += d3;
        q0 = fmaf(d0, d0, q0); q1 = fmaf(d1, d1, q1); q2 = fmaf(d2, d2, q2); q3 = fmaf(d3, d3, q3);
    }
    float s = (s0 + s1) + (s2 + s3), ss = (q0 + q1) + (q2 + q3);
#pragma unroll
    for (int o = 16; o > 0; o >>= 1) { s += __shfl_xor_sync(0xffffffffu, s, o); ss += __shfl_xor_sync(0xffffffffu, ss, o); }
    const float md = s * (1.0f / 512.0f);
    const float var = fmaxf(ss * (1.0f / 512.0f) - md * md, 0.f);
    const float m = bf16r(shift + md);
    float sq; asm("sqrt.approx.f32 %0, %1;" : "=f"(sq) : "f"(bf16r(bf16r(var) + 1e-5f)));
    const float sd = bf16r(sq);
    return make_float2(m, __fdividef(1.0f, sd));
}

struct Maps { CUtensorMap m[7]; };

__global__ void __launch_bounds__(NTHREADS, 1)
fused_decode_kernel(const __grid_constant__ Maps maps, const __nv_bfloat16* __restrict__ x, __nv_bfloat16* __restrict__ out)
{
    extern __shared__ __align__(1024) unsigned char smem_raw[];
    unsigned char* smem = smem_raw + ((1024u - (smem_u32(smem_raw) & 1023u)) & 1023u);
    const uint32_t sbase = smem_u32(smem);
    const uint32_t bar_full = sbase + OFF_BAR, bar_empty = sbase + OFF_BAR + 48, bar_ready = sbase + OFF_BAR + 96, bar_w = sbase + OFF_BAR + 104;
    volatile unsigned* vars = reinterpret_cast<volatile unsigned*>(smem + OFF_VAR);
    const int tid = threadIdx.x, warp = tid >> 5, lane = tid & 31;
    const int cta = blockIdx.x;

    if (warp == 8) {
        if (lane == 0) {
            for (int i = 0; i < NSLOT; i++) { mbar_init(bar_full + 8 * i, 1); mbar_init(bar_empty + 8 * i, 8); }
            mbar_init(bar_ready, 1);
            for (int i = 0; i < 6; i++) mbar_init(bar_w + 8 * i, 1);
            vars[1] = 0;
            asm volatile("fence.mbarrier_init.release.cluster;" ::: "memory");
        } else if (lane <= 7) {
            asm volatile("prefetch.tensormap [%0];" ::"l"(&maps.m[lane - 1]) : "memory");
        }
    }
    if (warp == 8) { __syncwarp(); bar_arrive(8, NTHREADS); } else bar_sync(8, NTHREADS);

    if (warp == 8) {
        if (lane == 0) {
            uint64_t pol;
            asm volatile("createpolicy.fractional.L2::evict_first.b64 %0, 1.0;" : "=l"(pol));
            const int key0 = cta * (NTILE * 128);
            int arrived = 0;
            unsigned grel = 0;
            int nkv = 0;
            for (int i = 0; i < NSEQ; i++) {
                const int slot = i % NSLOT;
                const bool is_w = (i == 0) || (i == SEQ_WO);
                if (i >= NSLOT) mbar_wait(bar_empty + 8 * slot, ((i / NSLOT) - 1) & 1);
                const int lead8 = (nkv * NCTA - (int)grel) / (NCTA / 8);
                const int d = (i > 2 && lead8 > LEAD_THR8) ? DEPTH_LO : DEPTH_HI;
                while (arrived < i - d + 1) { mbar_wait(bar_full + 8 * (arrived % NSLOT), (arrived / NSLOT) & 1); arrived++; }
                if (i == SEQ_WO && (int)grel < NCTA * 32 - WO_MARGIN) wait_progress(NCTA * 32 - WO_MARGIN);
                const uint32_t dst = sbase + slot * SLOT, fb = bar_full + 8 * slot;
                int mi, c0 = 0, c1 = 0, c2 = 0, nbox = 1;
                if (i == 0)            { mi = 2; c0 = cta * 32; nbox = 2; }
                else if (i == SEQ_WO)  { mi = 3; c1 = (cta >> 2) * 128; c2 = (cta & 3) * 2; }
                else                   { mi = nkv & 1; c1 = key0 + (nkv >> 1) * 128; }
                mbar_expect_tx(fb, 32768);
                for (int j = 0; j < nbox; j++) tma3d(dst + j * 16384, &maps.m[mi], c0, c1 + j * 256, c2, fb, pol);
                if (!is_w) {
                    if (nkv < 31) {
                        grel = atomicAdd(&g_prog, 1u);
                    } else {
                        asm volatile("red.relaxed.gpu.global.add.u32 [%0], 1;" ::"l"(&g_prog) : "memory");
                    }
                    nkv++;
                }
            }
            if (cta < NFFN) {
                mbar_wait(bar_empty + 8 * SLOT_WGU, (34 / NSLOT - 1) & 1);
                mbar_wait(bar_empty + 8 * SLOT_WD, (35 / NSLOT - 1) & 1);
                wait_progress(NCTA * 32);
                mbar_wait(bar_full + 8 * (SEQ_WO % NSLOT), (SEQ_WO / NSLOT) & 1);
                for (int k = 0; k < 6; k++) {
                    if (k >= WDEPTH) mbar_wait(bar_w + 8 * (k - WDEPTH), 0);
                    mbar_expect_tx(bar_w + 8 * k, 8192);
                    const int mi = (k < 4) ? 4 + (k >> 1) : 6;
                    const int c0 = (k < 4) ? cta * 16 : 0, c1 = (k < 4) ? (k & 1) * 256 : cta * 16, c2 = (k < 4) ? 0 : (k - 4) * 4;
                    tma3d(sbase + SLOT_WGU * SLOT + k * 8192, &maps.m[mi], c0, c1, c2, bar_w + 8 * k, pol);
                }
            }
        }
        return;
    }

    const int pair = cta >> 2, split = cta & 3;

    if (warp == 9) {
        Spin sp;
        while (vars[1] < RESET_TILE) { sp.tick(); __nanosleep(256); }
        const unsigned epoch = vars[0];
#pragma unroll 1
        for (int u = lane; u < 128; u += 32) {
            st_rel128(&g_partO[((pair * 4 + (u >> 5)) * 4 + split) * 128 + (u & 31) * 4], SENT);
            const int seg = u >> 2;
            st_rel128(&g_ypart[(((seg >> 3) * 32 + (cta & 3) * 8 + (seg & 7)) * 32 + (cta >> 2)) * 16 + (u & 3) * 4], SENT);
        }
        if (lane < 4) st_rel64(&g_ml[(pair * 4 + lane) * 4 + split], SENT, SENT);
        if (lane < 2) st_rel128(&g_h[(cta >> 5) * 512 + (cta & 31) * 16 + lane * 8], SENT);
        if (cta < NFFN) {
#pragma unroll 1
            for (int e = lane; e < 512; e += 32) st_rel128(&g_dpart[((e >> 2) * NFFN + cta) * 16 + (e & 3) * 4], SENT);
        }
        __threadfence();
        __syncwarp();
        if (lane == 0) {
            atomicAdd(&g_cnt1, 1u);
            unsigned v; Spin sp2;
            while (true) {
                asm volatile("ld.acquire.gpu.global.u32 %0, [%1];" : "=r"(v) : "l"(&g_cnt1) : "memory");
                if ((int)(v - (epoch + 1) * NCTA) >= 0) break;
                sp2.tick(); __nanosleep(128);
            }
            mbar_arrive(bar_ready);
        }
        return;
    }

    const int r8 = lane >> 2, q4 = lane & 3;
    const int hp = q4 & 1, kh = q4 >> 1;
    constexpr float LOG2E = 1.4426950408889634f;
    const int bq = pair >> 3, gq = pair & 7;

    if (tid == 0) vars[0] = atomicAdd(&g_cnt0, 1u) >> 7;
    if (warp == 7) st_rel128(&g_q[(lane >> 3) * 2048 + cta * 16 + (lane & 7) * 2], 0u);
    float xres = 0.f;
    if (warp == 0) xres = __bfloat162float(x[(cta >> 5) * 512 + (cta & 31) * 16 + (lane >> 1)]);

    if (warp < 4) {
        const uint4* xr = reinterpret_cast<const uint4*>(x + warp * 512);
        const uint4 a = __ldg(xr + lane), b = __ldg(xr + 32 + lane);
        float v[16];
        const float2 st = ln_stats(a, b, v);
        uint32_t o[8];
#pragma unroll
        for (int i = 0; i < 8; i++) o[i] = pack_bf16(bf16r(v[2 * i] - st.x) * st.y, bf16r(v[2 * i + 1] - st.x) * st.y);
        unsigned char* row = smem + OFF_XN + warp * XN_PITCH;
        *reinterpret_cast<uint4*>(row + lane * 16) = make_uint4(o[0], o[1], o[2], o[3]);
        *reinterpret_cast<uint4*>(row + 512 + lane * 16) = make_uint4(o[4], o[5], o[6], o[7]);
    }
    cbar();
    const uint32_t tag = vars[0] + 1;

    {
        uint32_t bfr[4][2];
        {
            uint32_t t4[4];
#pragma unroll
            for (int u = 0; u < 2; u++) {
                ldsm4(t4, sbase + OFF_XN + (lane & 3) * XN_PITCH + (8 * warp + 4 * u + (lane >> 3)) * 16);
                bfr[2 * u][0] = t4[0]; bfr[2 * u][1] = t4[1]; bfr[2 * u + 1][0] = t4[2]; bfr[2 * u + 1][1] = t4[3];
            }
        }
        mbar_wait(bar_full + 0, 0);
        float acc[2][4] = {};
#pragma unroll
        for (int ks = 0; ks < 4; ks++) {
            const int k = 64 * warp + 16 * ks + (lane & 7) + (lane >> 4) * 8;
#pragma unroll
            for (int mt = 0; mt < 2; mt++) {
                uint32_t a[4];
                const int chunk = 2 * mt + ((lane >> 3) & 1);
                ldsm4t(a, sbase + k * 64 + ((chunk ^ ((k >> 1) & 3)) << 4));
                mma16816(acc[mt], a, bfr[ks][0], bfr[ks][1]);
            }
        }
        __syncwarp();
        if (lane == 0) mbar_arrive(bar_empty + 0);
        float* red = reinterpret_cast<float*>(smem + OFF_RED);
#pragma unroll
        for (int mt = 0; mt < 2; mt++) {
            float2 v = kh ? make_float2(acc[mt][2], acc[mt][3]) : make_float2(acc[mt][0], acc[mt][1]);
            *reinterpret_cast<float2*>(red + ((warp * 2 + mt) * 16 + r8 + 8 * kh) * 4 + 2 * hp) = v;
        }
        cbar();
        if (tid < 64) {
            const int b = tid >> 4, c2 = tid & 15;
            float s0 = 0.f, s1 = 0.f;
            const int c0 = 2 * c2, c1 = 2 * c2 + 1;
#pragma unroll
            for (int ww = 0; ww < 8; ww++) {
                s0 += red[((ww * 2 + (c0 >> 4)) * 16 + (c0 & 15)) * 4 + b];
                s1 += red[((ww * 2 + (c1 >> 4)) * 16 + (c1 & 15)) * 4 + b];
            }
            st_rel64(&g_q[b * 2048 + cta * 16 + c2], pack_bf16(s0, s1), tag);
        }
        {
            const uint2* src = &g_q[bq * 2048 + gq * 256 + tid];
            uint2 v;
            Spin sp;
            while (true) { v = ld_poll2(src); if (__all_sync(0xffffffffu, v.y == tag)) break; sp.tick(); }
            *reinterpret_cast<uint32_t*>(smem + OFF_QS + (tid >> 6) * QS_PITCH + (tid & 63) * 4) = v.x;
        }
        cbar();
    }
    uint32_t qf[8][2];
    {
        uint32_t t4[4];
#pragma unroll
        for (int u = 0; u < 4; u++) {
            ldsm4(t4, sbase + OFF_QS + (lane & 3) * QS_PITCH + (4 * u + (lane >> 3)) * 16);
            qf[2 * u][0] = t4[0]; qf[2 * u][1] = t4[1]; qf[2 * u + 1][0] = t4[2]; qf[2 * u + 1][1] = t4[3];
        }
    }

    const uint32_t voff = (warp >> 2) * 16384 + ((lane & 7) + (lane >> 4) * 8) * 128 +
                          ((((2 * warp + ((lane >> 3) & 1)) & 7) ^ (lane & 7)) << 4);
    const uint32_t poff = sbase + OFF_P + (lane & 3) * QS_PITCH + (lane >> 3) * 16;
    const uint32_t koff = (16 * warp + (lane & 7) + ((lane >> 3) & 1) * 8) * 128;
    const uint32_t kx = lane & 7, kc = lane >> 4;
    constexpr float SCALE = 0.08838834764831845f;
    uint32_t* mxbuf = reinterpret_cast<uint32_t*>(smem + OFF_MX);
    uint32_t M2 = 0xFF80FF80u;
    float l0 = 0.f, l1 = 0.f;
    float oacc[2][4] = {};
    int slot = 1; uint32_t ph = 0;

    for (int t = 0;; t++) {
        mbar_wait(bar_full + 8 * slot, ph);
        float sa[4] = {}, sb[4] = {};
        {
            const uint32_t kb = sbase + slot * SLOT + koff;
#pragma unroll
            for (int ks = 0; ks < 8; ks++) {
                uint32_t a[4];
                ldsm4(a, kb + (ks >> 2) * 16384 + (((2 * (ks & 3) + kc) ^ kx) << 4));
                if (ks & 1) mma16816(sb, a, qf[ks][0], qf[ks][1]); else mma16816(sa, a, qf[ks][0], qf[ks][1]);
            }
        }
        __syncwarp();
        if (lane == 0) mbar_arrive(bar_empty + 8 * slot);
        if (++slot == NSLOT) { slot = 0; ph ^= 1; }

        const float r0 = kh ? sa[2] + sb[2] : sa[0] + sb[0];
        const float r1 = kh ? sa[3] + sb[3] : sa[1] + sb[1];
        uint32_t sp = pack_bf16(r0, r1);
        sp = pack_bf16(bf_lo(sp) * SCALE, bf_hi(sp) * SCALE);
        uint32_t mx = sp;
#pragma unroll
        for (int o = 2; o <= 16; o <<= 1) mx = hmax2(mx, __shfl_xor_sync(0xffffffffu, mx, o));
        if (lane < 2) mxbuf[lane * 8 + warp] = mx;
        if (tid == 0) vars[1] = t + 1;
        cbar();
        {
            const uint4 m0 = *reinterpret_cast<const uint4*>(mxbuf + hp * 8), m1 = *reinterpret_cast<const uint4*>(mxbuf + hp * 8 + 4);
            uint32_t mt = hmax2(hmax2(hmax2(m0.x, m0.y), hmax2(m0.z, m0.w)), hmax2(hmax2(m1.x, m1.y), hmax2(m1.z, m1.w)));
            const uint32_t Mn = hmax2(M2, mt);
            const float a0 = ex2((bf_lo(M2) - bf_lo(Mn)) * LOG2E), a1 = ex2((bf_hi(M2) - bf_hi(Mn)) * LOG2E);
            const float p0 = ex2((bf_lo(sp) - bf_lo(Mn)) * LOG2E), p1 = ex2((bf_hi(sp) - bf_hi(Mn)) * LOG2E);
            M2 = Mn;
            l0 = fmaf(l0, a0, p0); l1 = fmaf(l1, a1, p1);
            const uint32_t pp = pack_bf16(p0, p1);
            unsigned char* pd = smem + OFF_P + (2 * hp) * QS_PITCH + (16 * warp + r8 + 8 * kh) * 2;
            *reinterpret_cast<uint16_t*>(pd) = (uint16_t)(pp & 0xFFFF);
            *reinterpret_cast<uint16_t*>(pd + QS_PITCH) = (uint16_t)(pp >> 16);
#pragma unroll
            for (int c = 0; c < 2; c++) { oacc[c][0] *= a0; oacc[c][1] *= a1; oacc[c][2] *= a0; oacc[c][3] *= a1; }
        }
        if (t == NTILE - 1) break;
        cbar();
        uint32_t pb[8][2];
        {
            uint32_t t4[4];
#pragma unroll
            for (int u = 0; u < 4; u++) {
                ldsm4(t4, poff + u * 64);
                pb[2 * u][0] = t4[0]; pb[2 * u][1] = t4[1]; pb[2 * u + 1][0] = t4[2]; pb[2 * u + 1][1] = t4[3];
            }
        }
        mbar_wait(bar_full + 8 * slot, ph);
        {
            const uint32_t vb = sbase + slot * SLOT + voff;
#pragma unroll
            for (int ks = 0; ks < 8; ks++) {
                uint32_t a[4];
                ldsm4t(a, vb + ks * 2048);
                mma16816(oacc[ks & 1], a, pb[ks][0], pb[ks][1]);
            }
        }
        __syncwarp();
        if (lane == 0) mbar_arrive(bar_empty + 8 * slot);
        if (++slot == NSLOT) { slot = 0; ph ^= 1; }
    }

    const int head = cta >> 2;
    float* p_partO = &g_partO[((pair * 4 + 2 * hp) * 4 + split) * 128 + 16 * warp + r8 + 8 * kh];
    float* p_dpart = &g_dpart[(((2 * hp) * 32 + 4 * warp) * NFFN + cta) * 16 + r8 + 8 * kh];
    const float* p_dsrc = &g_dpart[(cta * NFFN + (tid >> 2)) * 16 + (tid & 3) * 4];
    __nv_bfloat16* p_out = out + (cta >> 5) * 512 + (cta & 31) * 16 + (lane >> 1);
    pin(p_partO); pin(p_dpart); pin(p_dsrc); pin(p_out);

    {
        float s0 = l0, s1 = l1;
#pragma unroll
        for (int o = 2; o <= 16; o <<= 1) { s0 += __shfl_xor_sync(0xffffffffu, s0, o); s1 += __shfl_xor_sync(0xffffffffu, s1, o); }
        if (lane < 2) *reinterpret_cast<float2*>(smem + OFF_L + warp * 16 + lane * 8) = make_float2(s0, s1);
        mbar_wait(bar_ready, 0);
        cbar();
        if (warp == 0) {
            const uint32_t other = __shfl_sync(0xffffffffu, M2, lane >> 1);
            float l = 0.f;
#pragma unroll
            for (int ww = 0; ww < 8; ww++) l += *reinterpret_cast<const float*>(smem + OFF_L + ww * 16 + (lane & 3) * 4);
            const float m = (lane & 1) ? bf_hi(other) : bf_lo(other);
            if (lane < 4) st_rel64(&g_ml[(pair * 4 + lane) * 4 + split], __float_as_uint(m), __float_as_uint(l));
        }
        uint32_t pb[8][2];
        {
            uint32_t t4[4];
#pragma unroll
            for (int u = 0; u < 4; u++) {
                ldsm4(t4, poff + u * 64);
                pb[2 * u][0] = t4[0]; pb[2 * u][1] = t4[1]; pb[2 * u + 1][0] = t4[2]; pb[2 * u + 1][1] = t4[3];
            }
        }
        float o2[2][4] = {};
        {
            mbar_wait(bar_full + 8 * slot, ph);
            const uint32_t vb = sbase + slot * SLOT + voff;
            uint32_t a[8][4];
#pragma unroll
            for (int ks = 0; ks < 8; ks++) ldsm4t(a[ks], vb + ks * 2048);
#pragma unroll
            for (int ks = 0; ks < 8; ks++) mma16816((ks & 2) ? o2[ks & 1] : oacc[ks & 1], a[ks], pb[ks][0], pb[ks][1]);
        }
        const float v0 = kh ? (oacc[0][2] + oacc[1][2]) + (o2[0][2] + o2[1][2]) : (oacc[0][0] + oacc[1][0]) + (o2[0][0] + o2[1][0]);
        const float v1 = kh ? (oacc[0][3] + oacc[1][3]) + (o2[0][3] + o2[1][3]) : (oacc[0][1] + oacc[1][1]) + (o2[0][1] + o2[1][1]);
        st_rel32(p_partO, __float_as_uint(v0));
        st_rel32(p_partO + 512, __float_as_uint(v1));
    }

    float hres = 0.f;
    uint32_t df[4][4];
    if (warp < 4) {
        {
            const int ph_idx = (warp * 8 + (head >> 2)) * 4 + (head & 3);
            const float* po = &g_partO[ph_idx * 512 + lane * 4];
            const float* pm = reinterpret_cast<const float*>(&g_ml[ph_idx * 4]);
            uint4 o0, o1, o2, o3, ma, mb;
            Spin sp;
            while (true) {
                o0 = ld_poll4(po); o1 = ld_poll4(po + 128); o2 = ld_poll4(po + 256); o3 = ld_poll4(po + 384);
                ma = ld_poll4(pm); mb = ld_poll4(pm + 4);
                const uint32_t mxv = max(max(max(umax4(o0), umax4(o1)), max(umax4(o2), umax4(o3))), max(umax4(ma), umax4(mb)));
                if (__all_sync(0xffffffffu, mxv != SENT)) break;
                sp.tick();
            }
            const float m0 = __uint_as_float(ma.x), m1 = __uint_as_float(ma.z), m2 = __uint_as_float(mb.x), m3 = __uint_as_float(mb.z);
            const float M = fmaxf(fmaxf(m0, m1), fmaxf(m2, m3));
            float w0 = ex2((m0 - M) * LOG2E), w1 = ex2((m1 - M) * LOG2E), w2 = ex2((m2 - M) * LOG2E), w3 = ex2((m3 - M) * LOG2E);
            const float L = w0 * __uint_as_float(ma.y) + w1 * __uint_as_float(ma.w) + w2 * __uint_as_float(mb.y) + w3 * __uint_as_float(mb.w);
            const float inv = __fdividef(1.0f, L);
            const float e0 = (w0 * __uint_as_float(o0.x) + w1 * __uint_as_float(o1.x) + w2 * __uint_as_float(o2.x) + w3 * __uint_as_float(o3.x)) * inv;
            const float e1 = (w0 * __uint_as_float(o0.y) + w1 * __uint_as_float(o1.y) + w2 * __uint_as_float(o2.y) + w3 * __uint_as_float(o3.y)) * inv;
            const float e2 = (w0 * __uint_as_float(o0.z) + w1 * __uint_as_float(o1.z) + w2 * __uint_as_float(o2.z) + w3 * __uint_as_float(o3.z)) * inv;
            const float e3 = (w0 * __uint_as_float(o0.w) + w1 * __uint_as_float(o1.w) + w2 * __uint_as_float(o2.w) + w3 * __uint_as_float(o3.w)) * inv;
            *reinterpret_cast<uint2*>(smem + OFF_QS + warp * QS_PITCH + lane * 8) = make_uint2(pack_bf16(e0, e1), pack_bf16(e2, e3));
            bar_arrive(2, 256);
        }
        {
            const float* src = &g_ypart[(cta * 32 + 8 * warp + (lane >> 2)) * 16 + (lane & 3) * 4];
            uint16_t* p_h = &g_h[(cta >> 5) * 512 + (cta & 31) * 16 + (lane >> 1)];
            pin(p_h);
            uint4 y;
            Spin sp;
            while (true) {
                y = ld_poll4(src);
                if (__all_sync(0xffffffffu, umax4(y) != SENT)) break;
                sp.tick();
            }
            const bool up = lane & 16, up2 = lane & 8;
            const float a0 = __uint_as_float(y.x), a1 = __uint_as_float(y.y), a2 = __uint_as_float(y.z), a3 = __uint_as_float(y.w);
            const float v0 = (up ? a2 : a0) + __shfl_xor_sync(0xffffffffu, up ? a0 : a2, 16);
            const float v1 = (up ? a3 : a1) + __shfl_xor_sync(0xffffffffu, up ? a1 : a3, 16);
            float v = (up2 ? v1 : v0) + __shfl_xor_sync(0xffffffffu, up2 ? v0 : v1, 8);
            v += __shfl_xor_sync(0xffffffffu, v, 4);
            float* rc = reinterpret_cast<float*>(smem + OFF_RED2);
            if (!(lane & 4)) rc[warp * 16 + 4 * (lane & 3) + (up ? 2 : 0) + (up2 ? 1 : 0)] = v;
            bar_sync(7, 128);
            if (warp == 0) {
                const float* r2 = rc + (lane & 1) * 32 + (lane >> 1);
                float t = r2[0] + r2[16];
                t += __shfl_xor_sync(0xffffffffu, t, 1);
                hres = bf16r(xres + bf16r(t));
                if (!(lane & 1)) st_rel16(p_h, (uint16_t)(__float_as_uint(hres) >> 16));
            }
        }
        {
            const uint4* hr = reinterpret_cast<const uint4*>(g_h + warp * 512);
            uint4 a, b;
            Spin sp;
            while (true) {
                a = ld_poll4(hr + lane); b = ld_poll4(hr + 32 + lane);
                if (__all_sync(0xffffffffu, valid8h(a) & valid8h(b))) break;
                sp.tick();
            }
            if (cta < NFFN) {
                unsigned char* row = smem + OFF_XN + warp * XN_PITCH;
                *reinterpret_cast<uint4*>(row + lane * 16) = a;
                *reinterpret_cast<uint4*>(row + 512 + lane * 16) = b;
                bar_arrive(3, 256);
                float v[16];
                const float2 st = ln_stats(a, b, v);
                if (lane == 0) *reinterpret_cast<float2*>(smem + OFF_ST + warp * 8) = st;
                bar_arrive(4, 256);
                mbar_wait(bar_w + 32, 0); mbar_wait(bar_w + 40, 0);
                const uint32_t wb = sbase + SLOT_WD * SLOT + warp * 2048 + ((lane & 7) + (lane >> 4) * 8) * 128;
#pragma unroll
                for (int i = 0; i < 4; i++) ldsm4t(df[i], wb + (((2 * i + ((lane >> 3) & 1)) ^ (lane & 7)) << 4));
            }
        }
    } else {
        const int m = warp - 4;
        {
            uint32_t af[2][8][4];
            float* p_y = &g_ypart[(((2 * hp) * 32 + (cta & 3) * 8 + 2 * m) * 32 + head) * 16 + r8 + 8 * kh];
            pin(p_y);
            mbar_wait(bar_full + 8 * (SEQ_WO % NSLOT), (SEQ_WO / NSLOT) & 1);
#pragma unroll
            for (int i = 0; i < 2; i++) {
                const int j = 2 * m + i;
                const uint32_t wb = sbase + (SEQ_WO % NSLOT) * SLOT + (j >> 2) * 16384 + ((lane & 7) + (lane >> 4) * 8) * 128 +
                                    ((((2 * j + ((lane >> 3) & 1)) & 7) ^ (lane & 7)) << 4);
#pragma unroll
                for (int ks = 0; ks < 8; ks++) ldsm4t(af[i][ks], wb + ks * 2048);
            }
            bar_sync(2, 256);
            float acc[2][2][4] = {};
            uint32_t t4[4][4];
#pragma unroll
            for (int u = 0; u < 4; u++) ldsm4(t4[u], sbase + OFF_QS + (lane & 3) * QS_PITCH + (4 * u + (lane >> 3)) * 16);
#pragma unroll
            for (int u = 0; u < 4; u++) {
#pragma unroll
                for (int i = 0; i < 2; i++) {
                    mma16816(acc[i][0], af[i][2 * u], t4[u][0], t4[u][1]);
                    mma16816(acc[i][1], af[i][2 * u + 1], t4[u][2], t4[u][3]);
                }
            }
#pragma unroll
            for (int i = 0; i < 2; i++) {
                const float v0 = kh ? acc[i][0][2] + acc[i][1][2] : acc[i][0][0] + acc[i][1][0];
                const float v1 = kh ? acc[i][0][3] + acc[i][1][3] : acc[i][0][1] + acc[i][1][1];
                st_rel32(p_y + i * 32 * 16, __float_as_uint(v0));
                st_rel32(p_y + i * 32 * 16 + 32 * 32 * 16, __float_as_uint(v1));
            }
        }
        if (cta < NFFN) {
            uint32_t gf[8][2][4];
            mbar_wait(bar_w, 0); mbar_wait(bar_w + 8, 0); mbar_wait(bar_w + 16, 0); mbar_wait(bar_w + 24, 0);
#pragma unroll
            for (int ks = 0; ks < 8; ks++) {
                const int k = 128 * m + 16 * ks + (lane & 7) + (lane >> 4) * 8;
                const uint32_t a = sbase + SLOT_WGU * SLOT + k * 32 + ((((lane >> 3) & 1) ^ ((k >> 2) & 1)) << 4);
                ldsm4t(gf[ks][0], a);
                ldsm4t(gf[ks][1], a + 16384);
            }
            float sg = 0.f, su = 0.f;
            {
                float cs[2][4] = {};
#pragma unroll
                for (int ks = 0; ks < 8; ks++) { mma16816(cs[0], gf[ks][0], 0x3F803F80u, 0x3F803F80u); mma16816(cs[1], gf[ks][1], 0x3F803F80u, 0x3F803F80u); }
                float* csb = reinterpret_cast<float*>(smem + OFF_CS);
                if (q4 == 0) {
                    csb[(m * 2 + 0) * 16 + r8] = cs[0][0]; csb[(m * 2 + 0) * 16 + r8 + 8] = cs[0][2];
                    csb[(m * 2 + 1) * 16 + r8] = cs[1][0]; csb[(m * 2 + 1) * 16 + r8 + 8] = cs[1][2];
                }
                bar_sync(5, 128);
                const int c = (tid & 63) >> 2;
#pragma unroll
                for (int ww = 0; ww < 4; ww++) { sg += csb[(ww * 2) * 16 + c]; su += csb[(ww * 2 + 1) * 16 + c]; }
            }
            const uint32_t wdb = sbase + SLOT_WD * SLOT + warp * 2048 + ((lane & 7) + (lane >> 4) * 8) * 128;
            const bool have_wd = __all_sync(0xffffffffu, mbar_try(bar_w + 32, 0) && mbar_try(bar_w + 40, 0));
            if (have_wd) {
#pragma unroll
                for (int i = 0; i < 4; i++) ldsm4t(df[i], wdb + (((2 * i + ((lane >> 3) & 1)) ^ (lane & 7)) << 4));
            }
            bar_sync(3, 256);
            float acc[2][2][4] = {};
            uint32_t t4[4][4];
#pragma unroll
            for (int u = 0; u < 4; u++) ldsm4(t4[u], sbase + OFF_XN + (lane & 3) * XN_PITCH + (16 * m + 4 * u + (lane >> 3)) * 16);
#pragma unroll
            for (int u = 0; u < 4; u++) {
#pragma unroll
                for (int i = 0; i < 2; i++) {
                    mma16816(acc[i][0], gf[2 * u][i], t4[u][0], t4[u][1]);
                    mma16816(acc[i][1], gf[2 * u + 1][i], t4[u][2], t4[u][3]);
                }
            }
            float* red = reinterpret_cast<float*>(smem + OFF_RED);
#pragma unroll
            for (int i = 0; i < 2; i++) {
                const float2 v = kh ? make_float2(acc[i][0][2] + acc[i][1][2], acc[i][0][3] + acc[i][1][3])
                                    : make_float2(acc[i][0][0] + acc[i][1][0], acc[i][0][1] + acc[i][1][1]);
                *reinterpret_cast<float2*>(red + ((m * 2 + i) * 16 + r8 + 8 * kh) * 4 + 2 * hp) = v;
            }
            bar_sync(4, 256);
            if (tid < 192) {
                const int c = (tid & 63) >> 2, b = tid & 3;
                const float2 st = *reinterpret_cast<const float2*>(smem + OFF_ST + b * 8);
                float g = 0.f, u = 0.f;
#pragma unroll
                for (int ww = 0; ww < 4; ww++) { g += red[((ww * 2) * 16 + c) * 4 + b]; u += red[((ww * 2 + 1) * 16 + c) * 4 + b]; }
                g = bf16r((g - st.x * sg) * st.y); u = bf16r((u - st.x * su) * st.y);
                const float inner = 0.7978845608028654f * (g + 0.044715f * g * g * g);
                const float th = 1.0f - __fdividef(2.0f, __expf(2.0f * inner) + 1.0f);
                const float ge = bf16r(0.5f * g * (1.0f + th));
                *reinterpret_cast<__nv_bfloat16*>(smem + OFF_ACT + b * 32 + c * 2) = __float2bfloat16_rn(ge * u);
            }
            if (!have_wd) {
                mbar_wait(bar_w + 32, 0); mbar_wait(bar_w + 40, 0);
#pragma unroll
                for (int i = 0; i < 4; i++) ldsm4t(df[i], wdb + (((2 * i + ((lane >> 3) & 1)) ^ (lane & 7)) << 4));
            }
        }
    }
    if (cta < NFFN) {
        bar_sync(6, 256);
        const uint32_t b0 = *reinterpret_cast<const uint32_t*>(smem + OFF_ACT + (r8 & 3) * 32 + q4 * 4);
        const uint32_t b1 = *reinterpret_cast<const uint32_t*>(smem + OFF_ACT + (r8 & 3) * 32 + 16 + q4 * 4);
        float c[4][4] = {};
#pragma unroll
        for (int i = 0; i < 4; i++) mma16816(c[i], df[i], b0, b1);
#pragma unroll
        for (int i = 0; i < 4; i++) {
            st_rel32(p_dpart + i * NFFN * 16, __float_as_uint(kh ? c[i][2] : c[i][0]));
            st_rel32(p_dpart + i * NFFN * 16 + 32 * NFFN * 16, __float_as_uint(kh ? c[i][3] : c[i][1]));
        }
    } else {
        bar_sync(6, 256);
        delay_cycles(DLY_F_IDLE);
    }

    {
        const int quad = tid & 3;
        const bool two = (tid >> 2) + 64 < NFFN;
        uint4 a, b = make_uint4(0, 0, 0, 0);
        Spin sp;
        delay_cycles(DLY_F);
        while (true) {
            a = ld_poll4(p_dsrc);
            if (two) b = ld_poll4(p_dsrc + 64 * 16);
            if (__all_sync(0xffffffffu, max(umax4(a), umax4(b)) != SENT)) break;
            sp.tick();
        }
        float v[4] = {__uint_as_float(a.x) + __uint_as_float(b.x), __uint_as_float(a.y) + __uint_as_float(b.y),
                      __uint_as_float(a.z) + __uint_as_float(b.z), __uint_as_float(a.w) + __uint_as_float(b.w)};
        {
            const bool up = lane & 16;
            const float s0 = up ? v[0] : v[2], s1 = up ? v[1] : v[3];
            const float k0 = up ? v[2] : v[0], k1 = up ? v[3] : v[1];
            v[0] = k0 + __shfl_xor_sync(0xffffffffu, s0, 16);
            v[1] = k1 + __shfl_xor_sync(0xffffffffu, s1, 16);
            const bool up2 = lane & 8;
            const float s = up2 ? v[0] : v[1], k = up2 ? v[1] : v[0];
            v[0] = k + __shfl_xor_sync(0xffffffffu, s, 8);
            v[0] += __shfl_xor_sync(0xffffffffu, v[0], 4);
            if (!(lane & 4)) reinterpret_cast<float*>(smem + OFF_RED2)[warp * 16 + 4 * quad + ((lane & 16) ? 2 : 0) + ((lane & 8) ? 1 : 0)] = v[0];
        }
        cbar();
        if (warp == 0) {
            const float* r2 = reinterpret_cast<const float*>(smem + OFF_RED2) + (lane & 1) * 64 + (lane >> 1);
            float s = (r2[0] + r2[16]) + (r2[32] + r2[48]);
            s += __shfl_xor_sync(0xffffffffu, s, 1);
            if (!(lane & 1)) *p_out = __float2bfloat16_rn(hres + bf16r(s));
            if (cta == 0 && lane == 0) st_rel32(&g_prog, 0u);
        }
    }
}

typedef CUresult (*EncodeFn)(CUtensorMap*, CUtensorMapDataType, cuuint32_t, void*, const cuuint64_t*, const cuuint64_t*,
                             const cuuint32_t*, const cuuint32_t*, CUtensorMapInterleave, CUtensorMapSwizzle,
                             CUtensorMapL2promotion, CUtensorMapFloatOOBfill);

void encode(EncodeFn fn, CUtensorMap* m, const void* base, int rank, const cuuint64_t* dims, const cuuint64_t* strides,
            const cuuint32_t* box, CUtensorMapSwizzle sw, CUtensorMapL2promotion promo) {
    cuuint32_t es[3] = {1, 1, 1};
    fn(m, CU_TENSOR_MAP_DATA_TYPE_BFLOAT16, (cuuint32_t)rank, const_cast<void*>(base), dims, strides, box, es,
       CU_TENSOR_MAP_INTERLEAVE_NONE, sw, promo, CU_TENSOR_MAP_FLOAT_OOB_FILL_NONE);
}

}

extern "C" void kernel_launch(void* const* d_in, const int* in_sizes, int n_in, void* d_out, int out_size) {
    (void)in_sizes; (void)n_in; (void)out_size;
    static EncodeFn enc = nullptr;
    if (!enc) {
        void* fn = nullptr;
        cudaDriverEntryPointQueryResult qr;
        cudaGetDriverEntryPoint("cuTensorMapEncodeTiled", &fn, cudaEnableDefault, &qr);
        enc = (EncodeFn)fn;
        cudaFuncSetAttribute(fused_decode_kernel, cudaFuncAttributeMaxDynamicSharedMemorySize, SMEM_BYTES);
    }
    const void* x = d_in[0];
    Maps maps;
    {
        cuuint64_t dims[3] = {64, 262144, 2}; cuuint64_t str[2] = {256, 128}; cuuint32_t box[3] = {64, 128, 2};
        encode(enc, &maps.m[0], d_in[1], 3, dims, str, box, CU_TENSOR_MAP_SWIZZLE_128B, CU_TENSOR_MAP_L2_PROMOTION_L2_256B);
        encode(enc, &maps.m[1], d_in[2], 3, dims, str, box, CU_TENSOR_MAP_SWIZZLE_128B, CU_TENSOR_MAP_L2_PROMOTION_L2_256B);
    }
    {
        cuuint64_t dims[3] = {4096, 512, 1}; cuuint64_t str[2] = {8192, 8192 * 512}; cuuint32_t box[3] = {32, 256, 1};
        encode(enc, &maps.m[2], d_in[3], 3, dims, str, box, CU_TENSOR_MAP_SWIZZLE_64B, CU_TENSOR_MAP_L2_PROMOTION_L2_128B);
    }
    {
        cuuint64_t dims[3] = {64, 4096, 8}; cuuint64_t str[2] = {1024, 128}; cuuint32_t box[3] = {64, 128, 2};
        encode(enc, &maps.m[3], d_in[4], 3, dims, str, box, CU_TENSOR_MAP_SWIZZLE_128B, CU_TENSOR_MAP_L2_PROMOTION_L2_256B);
    }
    {
        cuuint64_t dims[3] = {1792, 512, 1}; cuuint64_t str[2] = {3584, 3584 * 512}; cuuint32_t box[3] = {16, 256, 1};
        encode(enc, &maps.m[4], d_in[6], 3, dims, str, box, CU_TENSOR_MAP_SWIZZLE_32B, CU_TENSOR_MAP_L2_PROMOTION_L2_128B);
        encode(enc, &maps.m[5], d_in[7], 3, dims, str, box, CU_TENSOR_MAP_SWIZZLE_32B, CU_TENSOR_MAP_L2_PROMOTION_L2_128B);
    }
    {
        cuuint64_t dims[3] = {64, 1792, 8}; cuuint64_t str[2] = {1024, 128}; cuuint32_t box[3] = {64, 16, 4};
        encode(enc, &maps.m[6], d_in[8], 3, dims, str, box, CU_TENSOR_MAP_SWIZZLE_128B, CU_TENSOR_MAP_L2_PROMOTION_L2_256B);
    }
    fused_decode_kernel<<<NCTA, NTHREADS, SMEM_BYTES, cudaStreamPerThread>>>(maps, (const __nv_bfloat16*)x, (__nv_bfloat16*)d_out);
}
```

```cpp
#include <cuda_runtime.h>
#include <cuda_bf16.h>
#include <cuda.h>
#include <stdint.h>

namespace {

constexpr int NCTA      = 128;
constexpr int NTHREADS  = 320;
constexpr int SLOT      = 32768;
constexpr int NSLOT     = 6;
constexpr int NTILE     = 16;
constexpr int NFFN      = 112;
constexpr int DEPTH_LO  = 2;
constexpr int DEPTH_HI  = 3;
constexpr int LEAD_THR8 = 4;
constexpr int WO_MARGIN = 112;
constexpr int WDEPTH    = 4;
constexpr int SEQ_WO    = 33;
constexpr int NSEQ      = 34;
constexpr int SLOT_WGU  = 4, SLOT_WD = 5;
constexpr int DLY_F     = 500;
constexpr int DLY_F_IDLE = 1100;
constexpr int RESET_TILE = 8;
constexpr uint32_t SENT = 0xFFFFFFFFu;

constexpr int OFF_XN   = NSLOT * SLOT;
constexpr int XN_PITCH = 1040;
constexpr int OFF_QS   = OFF_XN + 4 * XN_PITCH;
constexpr int QS_PITCH = 272;
constexpr int OFF_P    = OFF_QS + 4 * QS_PITCH;
constexpr int OFF_RED  = OFF_P + 4 * QS_PITCH;
constexpr int OFF_MX   = OFF_RED + 4096;
constexpr int OFF_L    = OFF_MX + 64;
constexpr int OFF_ACT  = OFF_L + 128;
constexpr int OFF_RED2 = OFF_ACT + 128;
constexpr int OFF_CS   = OFF_RED2 + 512;
constexpr int OFF_ST   = OFF_CS + 512;
constexpr int OFF_BAR  = OFF_ST + 128;
constexpr int OFF_VAR  = OFF_BAR + 192;
constexpr int SMEM_USED = OFF_VAR + 64;
constexpr int SMEM_BYTES = SMEM_USED + 1024;
static_assert(OFF_RED % 16 == 0 && OFF_MX % 16 == 0 && OFF_ST % 8 == 0 && OFF_BAR % 8 == 0, "alignment");

__device__ uint2    g_q[4 * 2048];
__device__ float    g_partO[32 * 4 * 4 * 128];
__device__ float2   g_ml[32 * 4 * 4];
__device__ float    g_ypart[4 * 32 * 32 * 16];
__device__ uint16_t g_h[4 * 512];
__device__ float    g_dpart[4 * 32 * NFFN * 16];
__device__ unsigned g_cnt0, g_cnt1, g_prog;
#define TS(i)
#define TSX(i, cond)
#define TSG(i)
#define TSD(i, cond, dep)

__device__ __forceinline__ uint32_t smem_u32(const void* p) { return (uint32_t)__cvta_generic_to_shared(p); }
__device__ __forceinline__ void mbar_init(uint32_t bar, uint32_t cnt) {
    asm volatile("mbarrier.init.shared::cta.b64 [%0], %1;" ::"r"(bar), "r"(cnt) : "memory");
}
__device__ __forceinline__ void mbar_expect_tx(uint32_t bar, uint32_t bytes) {
    asm volatile("mbarrier.arrive.expect_tx.shared::cta.b64 _, [%0], %1;" ::"r"(bar), "r"(bytes) : "memory");
}
__device__ __forceinline__ void mbar_arrive(uint32_t bar) {
    asm volatile("mbarrier.arrive.shared::cta.b64 _, [%0];" ::"r"(bar) : "memory");
}
__device__ __forceinline__ bool mbar_try(uint32_t bar, uint32_t parity) {
    uint32_t ok;
    asm volatile("{\n.reg .pred p;\nmbarrier.try_wait.parity.shared::cta.b64 p, [%1], %2;\nselp.u32 %0, 1, 0, p;\n}"
                 : "=r"(ok) : "r"(bar), "r"(parity) : "memory");
    return ok != 0;
}
constexpr uint32_t SPIN_LIMIT = 1u << 22;
__device__ __forceinline__ void mbar_wait(uint32_t bar, uint32_t parity) {
    uint32_t it = 0;
    while (!mbar_try(bar, parity)) { if (++it > SPIN_LIMIT) __trap(); }
}
__device__ __forceinline__ void tma3d(uint32_t dst, const CUtensorMap* m, int c0, int c1, int c2, uint32_t bar, uint64_t pol) {
    asm volatile("cp.async.bulk.tensor.3d.shared::cluster.global.mbarrier::complete_tx::bytes.L2::cache_hint [%0], [%1, {%3, %4, %5}], [%2], %6;"
                 ::"r"(dst), "l"(m), "r"(bar), "r"(c0), "r"(c1), "r"(c2), "l"(pol) : "memory");
}
__device__ __forceinline__ void ldsm4(uint32_t (&r)[4], uint32_t addr) {
    asm volatile("ldmatrix.sync.aligned.m8n8.x4.shared.b16 {%0,%1,%2,%3}, [%4];"
                 : "=r"(r[0]), "=r"(r[1]), "=r"(r[2]), "=r"(r[3]) : "r"(addr) : "memory");
}
__device__ __forceinline__ void ldsm4t(uint32_t (&r)[4], uint32_t addr) {
    asm volatile("ldmatrix.sync.aligned.m8n8.x4.trans.shared.b16 {%0,%1,%2,%3}, [%4];"
                 : "=r"(r[0]), "=r"(r[1]), "=r"(r[2]), "=r"(r[3]) : "r"(addr) : "memory");
}
__device__ __forceinline__ void mma16816(float (&c)[4], const uint32_t (&a)[4], uint32_t b0, uint32_t b1) {
    asm volatile("mma.sync.aligned.m16n8k16.row.col.f32.bf16.bf16.f32 {%0,%1,%2,%3}, {%4,%5,%6,%7}, {%8,%9}, {%0,%1,%2,%3};"
                 : "+f"(c[0]), "+f"(c[1]), "+f"(c[2]), "+f"(c[3])
                 : "r"(a[0]), "r"(a[1]), "r"(a[2]), "r"(a[3]), "r"(b0), "r"(b1));
}
__device__ __forceinline__ void cbar() { asm volatile("bar.sync 1, 256;" ::: "memory"); }
__device__ __forceinline__ void bar_sync(int id, int n) { asm volatile("bar.sync %0, %1;" ::"r"(id), "r"(n) : "memory"); }
__device__ __forceinline__ void bar_arrive(int id, int n) { asm volatile("bar.arrive %0, %1;" ::"r"(id), "r"(n) : "memory"); }
__device__ __forceinline__ uint4 ld_poll4(const void* p) {
    uint4 v;
    asm volatile("ld.relaxed.gpu.global.v4.u32 {%0,%1,%2,%3}, [%4];" : "=r"(v.x), "=r"(v.y), "=r"(v.z), "=r"(v.w) : "l"(p) : "memory");
    return v;
}
__device__ __forceinline__ uint2 ld_poll2(const void* p) {
    uint2 v;
    asm volatile("ld.relaxed.gpu.global.v2.u32 {%0,%1}, [%2];" : "=r"(v.x), "=r"(v.y) : "l"(p) : "memory");
    return v;
}
__device__ __forceinline__ void st_rel32(void* p, uint32_t v) { asm volatile("st.relaxed.gpu.global.u32 [%0], %1;" ::"l"(p), "r"(v) : "memory"); }
__device__ __forceinline__ void st_rel16(void* p, uint16_t v) { asm volatile("st.relaxed.gpu.global.u16 [%0], %1;" ::"l"(p), "h"(v) : "memory"); }
__device__ __forceinline__ void st_rel64(void* p, uint32_t a, uint32_t b) { asm volatile("st.relaxed.gpu.global.v2.u32 [%0], {%1,%2};" ::"l"(p), "r"(a), "r"(b) : "memory"); }
__device__ __forceinline__ void st_rel128(void* p, uint32_t v) { asm volatile("st.relaxed.gpu.global.v4.u32 [%0], {%1,%1,%1,%1};" ::"l"(p), "r"(v) : "memory"); }
__device__ __forceinline__ uint32_t umax4(const uint4& v) { return max(max(v.x, v.y), max(v.z, v.w)); }
template <class T> __device__ __forceinline__ void pin(T*& p) { asm volatile("" : "+l"(p)); }
__device__ __forceinline__ bool valid8h(const uint4& v) {
    return (__vcmpeq2(v.x, SENT) | __vcmpeq2(v.y, SENT) | __vcmpeq2(v.z, SENT) | __vcmpeq2(v.w, SENT)) == 0;
}
struct Spin {
    uint32_t it = 0;
    __device__ __forceinline__ void tick() { if (++it > SPIN_LIMIT) __trap(); }
};
__device__ __forceinline__ void wait_progress(int n) {
    Spin sp; unsigned v;
    while (true) {
        asm volatile("ld.relaxed.gpu.global.u32 %0, [%1];" : "=r"(v) : "l"(&g_prog) : "memory");
        if ((int)v >= n) break;
        sp.tick(); __nanosleep(64);
    }
}
__device__ __forceinline__ uint32_t pack_bf16(float lo, float hi) {
    uint32_t r; asm("cvt.rn.bf16x2.f32 %0, %1, %2;" : "=r"(r) : "f"(hi), "f"(lo)); return r;
}
__device__ __forceinline__ void delay_cycles(int n) { if (n > 0) { const long long t0 = clock64(); while (clock64() - t0 < n) {} } }
__device__ __forceinline__ float bf16r(float x) { return __uint_as_float(pack_bf16(0.f, x) & 0xFFFF0000u); }
__device__ __forceinline__ float bf_lo(uint32_t v) { return __uint_as_float(v << 16); }
__device__ __forceinline__ float bf_hi(uint32_t v) { return __uint_as_float(v & 0xFFFF0000u); }
__device__ __forceinline__ uint32_t hmax2(uint32_t a, uint32_t b) {
    uint32_t r; asm("max.bf16x2 %0, %1, %2;" : "=r"(r) : "r"(a), "r"(b)); return r;
}
__device__ __forceinline__ float ex2(float x) { float r; asm("ex2.approx.ftz.f32 %0, %1;" : "=f"(r) : "f"(x)); return r; }

__device__ __forceinline__ float2 ln_stats(const uint4& a, const uint4& b, float (&v)[16]) {
    v[0] = bf_lo(a.x); v[1] = bf_hi(a.x); v[2] = bf_lo(a.y); v[3] = bf_hi(a.y);
    v[4] = bf_lo(a.z); v[5] = bf_hi(a.z); v[6] = bf_lo(a.w); v[7] = bf_hi(a.w);
    v[8] = bf_lo(b.x); v[9] = bf_hi(b.x); v[10] = bf_lo(b.y); v[11] = bf_hi(b.y);
    v[12] = bf_lo(b.z); v[13] = bf_hi(b.z); v[14] = bf_lo(b.w); v[15] = bf_hi(b.w);
    const float shift = __shfl_sync(0xffffffffu, v[0], 0);
    float s0 = 0.f, s1 = 0.f, s2 = 0.f, s3 = 0.f, q0 = 0.f, q1 = 0.f, q2 = 0.f, q3 = 0.f;
#pragma unroll
    for (int i = 0; i < 16; i += 4) {
        const float d0 = v[i] - shift, d1 = v[i + 1] - shift, d2 = v[i + 2] - shift, d3 = v[i + 3] - shift;
        s0 += d0; s1 += d1; s2 += d2; s3 += d3;
        q0 = fmaf(d0, d0, q0); q1 = fmaf(d1, d1, q1); q2 = fmaf(d2, d2, q2); q3 = fmaf(d3, d3, q3);
    }
    float s = (s0 + s1) + (s2 + s3), ss = (q0 + q1) + (q2 + q3);
#pragma unroll
    for (int o = 16; o > 0; o >>= 1) { s += __shfl_xor_sync(0xffffffffu, s, o); ss += __shfl_xor_sync(0xffffffffu, ss, o); }
    const float md = s * (1.0f / 512.0f);
    const float var = fmaxf(ss * (1.0f / 512.0f) - md * md, 0.f);
    const float m = bf16r(shift + md);
    float sq; asm("sqrt.approx.f32 %0, %1;" : "=f"(sq) : "f"(bf16r(bf16r(var) + 1e-5f)));
    const float sd = bf16r(sq);
    return make_float2(m, __fdividef(1.0f, sd));
}

struct Maps { CUtensorMap m[7]; };

__global__ void __launch_bounds__(NTHREADS, 1)
fused_decode_kernel(const __grid_constant__ Maps maps, const __nv_bfloat16* __restrict__ x, __nv_bfloat16* __restrict__ out)
{
    extern __shared__ __align__(1024) unsigned char smem_raw[];
    unsigned char* smem = smem_raw + ((1024u - (smem_u32(smem_raw) & 1023u)) & 1023u);
    const uint32_t sbase = smem_u32(smem);
    const uint32_t bar_full = sbase + OFF_BAR, bar_empty = sbase + OFF_BAR + 48, bar_ready = sbase + OFF_BAR + 96, bar_w = sbase + OFF_BAR + 104;
    volatile unsigned* vars = reinterpret_cast<volatile unsigned*>(smem + OFF_VAR);
    const int tid = threadIdx.x, warp = tid >> 5, lane = tid & 31;
    const int cta = blockIdx.x;

    if (tid == 0) TSG(0);
    if (warp == 8) {
        if (lane == 0) {
            for (int i = 0; i < NSLOT; i++) { mbar_init(bar_full + 8 * i, 1); mbar_init(bar_empty + 8 * i, 8); }
            mbar_init(bar_ready, 1);
            for (int i = 0; i < 6; i++) mbar_init(bar_w + 8 * i, 1);
            vars[1] = 0;
            asm volatile("fence.mbarrier_init.release.cluster;" ::: "memory");
        } else if (lane <= 7) {
            asm volatile("prefetch.tensormap [%0];" ::"l"(&maps.m[lane - 1]) : "memory");
        }
    }
    if (warp == 8) { __syncwarp(); bar_arrive(8, NTHREADS); } else bar_sync(8, NTHREADS);

    if (warp == 8) {
        if (lane == 0) {
            uint64_t pol;
            asm volatile("createpolicy.fractional.L2::evict_first.b64 %0, 1.0;" : "=l"(pol));
            const int key0 = cta * (NTILE * 128);
            int arrived = 0;
            unsigned grel = 0;
            int nkv = 0;
            for (int i = 0; i < NSEQ; i++) {
                const int slot = i % NSLOT;
                const bool is_w = (i == 0) || (i == SEQ_WO);
                if (i >= NSLOT) mbar_wait(bar_empty + 8 * slot, ((i / NSLOT) - 1) & 1);
                const int lead8 = (nkv * NCTA - (int)grel) / (NCTA / 8);
                const int d = (i > 2 && lead8 > LEAD_THR8) ? DEPTH_LO : DEPTH_HI;
                while (arrived < i - d + 1) { mbar_wait(bar_full + 8 * (arrived % NSLOT), (arrived / NSLOT) & 1); arrived++; }
                if (i == SEQ_WO && (int)grel < NCTA * 32 - WO_MARGIN) wait_progress(NCTA * 32 - WO_MARGIN);
                const uint32_t dst = sbase + slot * SLOT, fb = bar_full + 8 * slot;
                int mi, c0 = 0, c1 = 0, c2 = 0, nbox = 1;
                if (i == 0)            { mi = 2; c0 = cta * 32; nbox = 2; }
                else if (i == SEQ_WO)  { mi = 3; c1 = (cta >> 2) * 128; c2 = (cta & 3) * 2; }
                else                   { mi = nkv & 1; c1 = key0 + (nkv >> 1) * 128; }
                mbar_expect_tx(fb, 32768);
                for (int j = 0; j < nbox; j++) tma3d(dst + j * 16384, &maps.m[mi], c0, c1 + j * 256, c2, fb, pol);
                if (!is_w) {
                    if (nkv < 31) {
                        grel = atomicAdd(&g_prog, 1u);
                    } else {
                        asm volatile("red.relaxed.gpu.global.add.u32 [%0], 1;" ::"l"(&g_prog) : "memory");
                    }
                    nkv++;
                }
            }
            if (cta < NFFN) {
                mbar_wait(bar_empty + 8 * SLOT_WGU, (34 / NSLOT - 1) & 1);
                mbar_wait(bar_empty + 8 * SLOT_WD, (35 / NSLOT - 1) & 1);
                wait_progress(NCTA * 32);
                mbar_wait(bar_full + 8 * (SEQ_WO % NSLOT), (SEQ_WO / NSLOT) & 1);
                TSX(26, true);
                for (int k = 0; k < 6; k++) {
                    if (k >= WDEPTH) mbar_wait(bar_w + 8 * (k - WDEPTH), 0);
                    mbar_expect_tx(bar_w + 8 * k, 8192);
                    const int mi = (k < 4) ? 4 + (k >> 1) : 6;
                    const int c0 = (k < 4) ? cta * 16 : 0, c1 = (k < 4) ? (k & 1) * 256 : cta * 16, c2 = (k < 4) ? 0 : (k - 4) * 4;
                    tma3d(sbase + SLOT_WGU * SLOT + k * 8192, &maps.m[mi], c0, c1, c2, bar_w + 8 * k, pol);
                }
            }
            TSX(20, true);
        }
        return;
    }

    const int pair = cta >> 2, split = cta & 3;

    if (warp == 9) {
        Spin sp;
        while (vars[1] < RESET_TILE) { sp.tick(); __nanosleep(256); }
        const unsigned epoch = vars[0];
#pragma unroll 1
        for (int u = lane; u < 128; u += 32) {
            st_rel128(&g_partO[((pair * 4 + (u >> 5)) * 4 + split) * 128 + (u & 31) * 4], SENT);
            const int seg = u >> 2;
            st_rel128(&g_ypart[(((seg >> 3) * 32 + (cta & 3) * 8 + (seg & 7)) * 32 + (cta >> 2)) * 16 + (u & 3) * 4], SENT);
        }
        if (lane < 4) st_rel64(&g_ml[(pair * 4 + lane) * 4 + split], SENT, SENT);
        if (lane < 2) st_rel128(&g_h[(cta >> 5) * 512 + (cta & 31) * 16 + lane * 8], SENT);
        if (cta < NFFN) {
#pragma unroll 1
            for (int e = lane; e < 512; e += 32) st_rel128(&g_dpart[((e >> 2) * NFFN + cta) * 16 + (e & 3) * 4], SENT);
        }
        __threadfence();
        __syncwarp();
        if (lane == 0) {
            atomicAdd(&g_cnt1, 1u);
            unsigned v; Spin sp2;
            while (true) {
                asm volatile("ld.acquire.gpu.global.u32 %0, [%1];" : "=r"(v) : "l"(&g_cnt1) : "memory");
                if ((int)(v - (epoch + 1) * NCTA) >= 0) break;
                sp2.tick(); __nanosleep(128);
            }
            mbar_arrive(bar_ready);
        }
        TSX(24, lane == 0);
        return;
    }

    const int r8 = lane >> 2, q4 = lane & 3;
    const int hp = q4 & 1, kh = q4 >> 1;
    constexpr float LOG2E = 1.4426950408889634f;
    const int bq = pair >> 3, gq = pair & 7;

    if (tid == 0) vars[0] = atomicAdd(&g_cnt0, 1u) >> 7;
    if (warp == 7) st_rel128(&g_q[(lane >> 3) * 2048 + cta * 16 + (lane & 7) * 2], 0u);
    float xres = 0.f;
    if (warp == 0) xres = __bfloat162float(x[(cta >> 5) * 512 + (cta & 31) * 16 + (lane >> 1)]);

    if (warp < 4) {
        const uint4* xr = reinterpret_cast<const uint4*>(x + warp * 512);
        const uint4 a = __ldg(xr + lane), b = __ldg(xr + 32 + lane);
        float v[16];
        const float2 st = ln_stats(a, b, v);
        uint32_t o[8];
#pragma unroll
        for (int i = 0; i < 8; i++) o[i] = pack_bf16(bf16r(v[2 * i] - st.x) * st.y, bf16r(v[2 * i + 1] - st.x) * st.y);
        unsigned char* row = smem + OFF_XN + warp * XN_PITCH;
        *reinterpret_cast<uint4*>(row + lane * 16) = make_uint4(o[0], o[1], o[2], o[3]);
        *reinterpret_cast<uint4*>(row + 512 + lane * 16) = make_uint4(o[4], o[5], o[6], o[7]);
    }
    cbar();
    const uint32_t tag = vars[0] + 1;

    {
        uint32_t bfr[4][2];
        {
            uint32_t t4[4];
#pragma unroll
            for (int u = 0; u < 2; u++) {
                ldsm4(t4, sbase + OFF_XN + (lane & 3) * XN_PITCH + (8 * warp + 4 * u + (lane >> 3)) * 16);
                bfr[2 * u][0] = t4[0]; bfr[2 * u][1] = t4[1]; bfr[2 * u + 1][0] = t4[2]; bfr[2 * u + 1][1] = t4[3];
            }
        }
        mbar_wait(bar_full + 0, 0);
        TS(2);
        float acc[2][4] = {};
#pragma unroll
        for (int ks = 0; ks < 4; ks++) {
            const int k = 64 * warp + 16 * ks + (lane & 7) + (lane >> 4) * 8;
#pragma unroll
            for (int mt = 0; mt < 2; mt++) {
                uint32_t a[4];
                const int chunk = 2 * mt + ((lane >> 3) & 1);
                ldsm4t(a, sbase + k * 64 + ((chunk ^ ((k >> 1) & 3)) << 4));
                mma16816(acc[mt], a, bfr[ks][0], bfr[ks][1]);
            }
        }
        __syncwarp();
        if (lane == 0) mbar_arrive(bar_empty + 0);
        float* red = reinterpret_cast<float*>(smem + OFF_RED);
#pragma unroll
        for (int mt = 0; mt < 2; mt++) {
            float2 v = kh ? make_float2(acc[mt][2], acc[mt][3]) : make_float2(acc[mt][0], acc[mt][1]);
            *reinterpret_cast<float2*>(red + ((warp * 2 + mt) * 16 + r8 + 8 * kh) * 4 + 2 * hp) = v;
        }
        cbar();
        if (tid < 64) {
            const int b = tid >> 4, c2 = tid & 15;
            float s0 = 0.f, s1 = 0.f;
            const int c0 = 2 * c2, c1 = 2 * c2 + 1;
#pragma unroll
            for (int ww = 0; ww < 8; ww++) {
                s0 += red[((ww * 2 + (c0 >> 4)) * 16 + (c0 & 15)) * 4 + b];
                s1 += red[((ww * 2 + (c1 >> 4)) * 16 + (c1 & 15)) * 4 + b];
            }
            st_rel64(&g_q[b * 2048 + cta * 16 + c2], pack_bf16(s0, s1), tag);
        }
        {
            const uint2* src = &g_q[bq * 2048 + gq * 256 + tid];
            uint2 v;
            Spin sp;
            while (true) { v = ld_poll2(src); if (__all_sync(0xffffffffu, v.y == tag)) break; sp.tick(); }
            *reinterpret_cast<uint32_t*>(smem + OFF_QS + (tid >> 6) * QS_PITCH + (tid & 63) * 4) = v.x;
        }
        cbar();
    }
    TS(3);
    uint32_t qf[8][2];
    {
        uint32_t t4[4];
#pragma unroll
        for (int u = 0; u < 4; u++) {
            ldsm4(t4, sbase + OFF_QS + (lane & 3) * QS_PITCH + (4 * u + (lane >> 3)) * 16);
            qf[2 * u][0] = t4[0]; qf[2 * u][1] = t4[1]; qf[2 * u + 1][0] = t4[2]; qf[2 * u + 1][1] = t4[3];
        }
    }

    const uint32_t voff = (warp >> 2) * 16384 + ((lane & 7) + (lane >> 4) * 8) * 128 +
                          ((((2 * warp + ((lane >> 3) & 1)) & 7) ^ (lane & 7)) << 4);
    const uint32_t poff = sbase + OFF_P + (lane & 3) * QS_PITCH + (lane >> 3) * 16;
    const uint32_t koff = (16 * warp + (lane & 7) + ((lane >> 3) & 1) * 8) * 128;
    const uint32_t kx = lane & 7, kc = lane >> 4;
    constexpr float SCALE = 0.08838834764831845f;
    uint32_t* mxbuf = reinterpret_cast<uint32_t*>(smem + OFF_MX);
    uint32_t M2 = 0xFF80FF80u;
    float l0 = 0.f, l1 = 0.f;
    float oacc[2][4] = {};
    int slot = 1; uint32_t ph = 0;

    for (int t = 0;; t++) {
        mbar_wait(bar_full + 8 * slot, ph);
        float sa[4] = {}, sb[4] = {};
        {
            const uint32_t kb = sbase + slot * SLOT + koff;
#pragma unroll
            for (int ks = 0; ks < 8; ks++) {
                uint32_t a[4];
                ldsm4(a, kb + (ks >> 2) * 16384 + (((2 * (ks & 3) + kc) ^ kx) << 4));
                if (ks & 1) mma16816(sb, a, qf[ks][0], qf[ks][1]); else mma16816(sa, a, qf[ks][0], qf[ks][1]);
            }
        }
        __syncwarp();
        if (lane == 0) mbar_arrive(bar_empty + 8 * slot);
        if (++slot == NSLOT) { slot = 0; ph ^= 1; }

        const float r0 = kh ? sa[2] + sb[2] : sa[0] + sb[0];
        const float r1 = kh ? sa[3] + sb[3] : sa[1] + sb[1];
        uint32_t sp = pack_bf16(r0, r1);
        sp = pack_bf16(bf_lo(sp) * SCALE, bf_hi(sp) * SCALE);
        uint32_t mx = sp;
#pragma unroll
        for (int o = 2; o <= 16; o <<= 1) mx = hmax2(mx, __shfl_xor_sync(0xffffffffu, mx, o));
        if (lane < 2) mxbuf[lane * 8 + warp] = mx;
        if (tid == 0) vars[1] = t + 1;
        TS(40 + t);
        cbar();
        {
            const uint4 m0 = *reinterpret_cast<const uint4*>(mxbuf + hp * 8), m1 = *reinterpret_cast<const uint4*>(mxbuf + hp * 8 + 4);
            uint32_t mt = hmax2(hmax2(hmax2(m0.x, m0.y), hmax2(m0.z, m0.w)), hmax2(hmax2(m1.x, m1.y), hmax2(m1.z, m1.w)));
            const uint32_t Mn = hmax2(M2, mt);
            const float a0 = ex2((bf_lo(M2) - bf_lo(Mn)) * LOG2E), a1 = ex2((bf_hi(M2) - bf_hi(Mn)) * LOG2E);
            const float p0 = ex2((bf_lo(sp) - bf_lo(Mn)) * LOG2E), p1 = ex2((bf_hi(sp) - bf_hi(Mn)) * LOG2E);
            M2 = Mn;
            l0 = fmaf(l0, a0, p0); l1 = fmaf(l1, a1, p1);
            const uint32_t pp = pack_bf16(p0, p1);
            unsigned char* pd = smem + OFF_P + (2 * hp) * QS_PITCH + (16 * warp + r8 + 8 * kh) * 2;
            *reinterpret_cast<uint16_t*>(pd) = (uint16_t)(pp & 0xFFFF);
            *reinterpret_cast<uint16_t*>(pd + QS_PITCH) = (uint16_t)(pp >> 16);
#pragma unroll
            for (int c = 0; c < 2; c++) { oacc[c][0] *= a0; oacc[c][1] *= a1; oacc[c][2] *= a0; oacc[c][3] *= a1; }
        }
        if (t == NTILE - 1) break;
        cbar();
        uint32_t pb[8][2];
        {
            uint32_t t4[4];
#pragma unroll
            for (int u = 0; u < 4; u++) {
                ldsm4(t4, poff + u * 64);
                pb[2 * u][0] = t4[0]; pb[2 * u][1] = t4[1]; pb[2 * u + 1][0] = t4[2]; pb[2 * u + 1][1] = t4[3];
            }
        }
        mbar_wait(bar_full + 8 * slot, ph);
        {
            const uint32_t vb = sbase + slot * SLOT + voff;
#pragma unroll
            for (int ks = 0; ks < 8; ks++) {
                uint32_t a[4];
                ldsm4t(a, vb + ks * 2048);
                mma16816(oacc[ks & 1], a, pb[ks][0], pb[ks][1]);
            }
        }
        __syncwarp();
        if (lane == 0) mbar_arrive(bar_empty + 8 * slot);
        if (++slot == NSLOT) { slot = 0; ph ^= 1; }
    }

    const int head = cta >> 2;
    float* p_partO = &g_partO[((pair * 4 + 2 * hp) * 4 + split) * 128 + 16 * warp + r8 + 8 * kh];
    float* p_dpart = &g_dpart[(((2 * hp) * 32 + 4 * warp) * NFFN + cta) * 16 + r8 + 8 * kh];
    const float* p_dsrc = &g_dpart[(cta * NFFN + (tid >> 2)) * 16 + (tid & 3) * 4];
    __nv_bfloat16* p_out = out + (cta >> 5) * 512 + (cta & 31) * 16 + (lane >> 1);
    pin(p_partO); pin(p_dpart); pin(p_dsrc); pin(p_out);

    {
        float s0 = l0, s1 = l1;
#pragma unroll
        for (int o = 2; o <= 16; o <<= 1) { s0 += __shfl_xor_sync(0xffffffffu, s0, o); s1 += __shfl_xor_sync(0xffffffffu, s1, o); }
        if (lane < 2) *reinterpret_cast<float2*>(smem + OFF_L + warp * 16 + lane * 8) = make_float2(s0, s1);
        mbar_wait(bar_ready, 0);
        cbar();
        if (warp == 0) {
            const uint32_t other = __shfl_sync(0xffffffffu, M2, lane >> 1);
            float l = 0.f;
#pragma unroll
            for (int ww = 0; ww < 8; ww++) l += *reinterpret_cast<const float*>(smem + OFF_L + ww * 16 + (lane & 3) * 4);
            const float m = (lane & 1) ? bf_hi(other) : bf_lo(other);
            if (lane < 4) st_rel64(&g_ml[(pair * 4 + lane) * 4 + split], __float_as_uint(m), __float_as_uint(l));
        }
        uint32_t pb[8][2];
        {
            uint32_t t4[4];
#pragma unroll
            for (int u = 0; u < 4; u++) {
                ldsm4(t4, poff + u * 64);
                pb[2 * u][0] = t4[0]; pb[2 * u][1] = t4[1]; pb[2 * u + 1][0] = t4[2]; pb[2 * u + 1][1] = t4[3];
            }
        }
        float o2[2][4] = {};
        {
            mbar_wait(bar_full + 8 * slot, ph);
            TS(30);
            const uint32_t vb = sbase + slot * SLOT + voff;
            uint32_t a[8][4];
#pragma unroll
            for (int ks = 0; ks < 8; ks++) ldsm4t(a[ks], vb + ks * 2048);
#pragma unroll
            for (int ks = 0; ks < 8; ks++) mma16816((ks & 2) ? o2[ks & 1] : oacc[ks & 1], a[ks], pb[ks][0], pb[ks][1]);
        }
        const float v0 = kh ? (oacc[0][2] + oacc[1][2]) + (o2[0][2] + o2[1][2]) : (oacc[0][0] + oacc[1][0]) + (o2[0][0] + o2[1][0]);
        const float v1 = kh ? (oacc[0][3] + oacc[1][3]) + (o2[0][3] + o2[1][3]) : (oacc[0][1] + oacc[1][1]) + (o2[0][1] + o2[1][1]);
        st_rel32(p_partO, __float_as_uint(v0));
        st_rel32(p_partO + 512, __float_as_uint(v1));
        TS(4);
    }

    float hres = 0.f;
    uint32_t df[4][4];
    if (warp < 4) {
        {
            const int ph_idx = (warp * 8 + (head >> 2)) * 4 + (head & 3);
            const float* po = &g_partO[ph_idx * 512 + lane * 4];
            const float* pm = reinterpret_cast<const float*>(&g_ml[ph_idx * 4]);
            uint4 o0, o1, o2, o3, ma, mb;
            Spin sp;
            while (true) {
                o0 = ld_poll4(po); o1 = ld_poll4(po + 128); o2 = ld_poll4(po + 256); o3 = ld_poll4(po + 384);
                ma = ld_poll4(pm); mb = ld_poll4(pm + 4);
                const uint32_t mxv = max(max(max(umax4(o0), umax4(o1)), max(umax4(o2), umax4(o3))), max(umax4(ma), umax4(mb)));
                if (__all_sync(0xffffffffu, mxv != SENT)) break;
                sp.tick();
            }
            TS(6);
            const float m0 = __uint_as_float(ma.x), m1 = __uint_as_float(ma.z), m2 = __uint_as_float(mb.x), m3 = __uint_as_float(mb.z);
            const float M = fmaxf(fmaxf(m0, m1), fmaxf(m2, m3));
            float w0 = ex2((m0 - M) * LOG2E), w1 = ex2((m1 - M) * LOG2E), w2 = ex2((m2 - M) * LOG2E), w3 = ex2((m3 - M) * LOG2E);
            const float L = w0 * __uint_as_float(ma.y) + w1 * __uint_as_float(ma.w) + w2 * __uint_as_float(mb.y) + w3 * __uint_as_float(mb.w);
            const float inv = __fdividef(1.0f, L);
            const float e0 = (w0 * __uint_as_float(o0.x) + w1 * __uint_as_float(o1.x) + w2 * __uint_as_float(o2.x) + w3 * __uint_as_float(o3.x)) * inv;
            const float e1 = (w0 * __uint_as_float(o0.y) + w1 * __uint_as_float(o1.y) + w2 * __uint_as_float(o2.y) + w3 * __uint_as_float(o3.y)) * inv;
            const float e2 = (w0 * __uint_as_float(o0.z) + w1 * __uint_as_float(o1.z) + w2 * __uint_as_float(o2.z) + w3 * __uint_as_float(o3.z)) * inv;
            const float e3 = (w0 * __uint_as_float(o0.w) + w1 * __uint_as_float(o1.w) + w2 * __uint_as_float(o2.w) + w3 * __uint_as_float(o3.w)) * inv;
            *reinterpret_cast<uint2*>(smem + OFF_QS + warp * QS_PITCH + lane * 8) = make_uint2(pack_bf16(e0, e1), pack_bf16(e2, e3));
            TSD(31, tid == 0, e0 + e1 + e2 + e3);
            bar_arrive(2, 256);
        }
        {
            const float* src = &g_ypart[(cta * 32 + 8 * warp + (lane >> 2)) * 16 + (lane & 3) * 4];
            uint16_t* p_h = &g_h[(cta >> 5) * 512 + (cta & 31) * 16 + (lane >> 1)];
            pin(p_h);
            uint4 y;
            Spin sp;
            while (true) {
                y = ld_poll4(src);
                if (__all_sync(0xffffffffu, umax4(y) != SENT)) break;
                sp.tick();
            }
            TS(9);
            const bool up = lane & 16, up2 = lane & 8;
            const float a0 = __uint_as_float(y.x), a1 = __uint_as_float(y.y), a2 = __uint_as_float(y.z), a3 = __uint_as_float(y.w);
            const float v0 = (up ? a2 : a0) + __shfl_xor_sync(0xffffffffu, up ? a0 : a2, 16);
            const float v1 = (up ? a3 : a1) + __shfl_xor_sync(0xffffffffu, up ? a1 : a3, 16);
            float v = (up2 ? v1 : v0) + __shfl_xor_sync(0xffffffffu, up2 ? v0 : v1, 8);
            v += __shfl_xor_sync(0xffffffffu, v, 4);
            float* rc = reinterpret_cast<float*>(smem + OFF_RED2);
            if (!(lane & 4)) rc[warp * 16 + 4 * (lane & 3) + (up ? 2 : 0) + (up2 ? 1 : 0)] = v;
            bar_sync(7, 128);
            if (warp == 0) {
                const float* r2 = rc + (lane & 1) * 32 + (lane >> 1);
                float t = r2[0] + r2[16];
                t += __shfl_xor_sync(0xffffffffu, t, 1);
                hres = bf16r(xres + bf16r(t));
                if (!(lane & 1)) st_rel16(p_h, (uint16_t)(__float_as_uint(hres) >> 16));
                bar_arrive(3, 160);
                TS(10);
            }
        }
        if (cta < NFFN) {
            mbar_wait(bar_w + 32, 0); mbar_wait(bar_w + 40, 0);
            const uint32_t wb = sbase + SLOT_WD * SLOT + warp * 2048 + ((lane & 7) + (lane >> 4) * 8) * 128;
#pragma unroll
            for (int i = 0; i < 4; i++) ldsm4t(df[i], wb + (((2 * i + ((lane >> 3) & 1)) ^ (lane & 7)) << 4));
        }
    } else {
        const int m = warp - 4;
        {
            uint32_t af[2][8][4];
            float* p_y = &g_ypart[(((2 * hp) * 32 + (cta & 3) * 8 + 2 * m) * 32 + head) * 16 + r8 + 8 * kh];
            pin(p_y);
            mbar_wait(bar_full + 8 * (SEQ_WO % NSLOT), (SEQ_WO / NSLOT) & 1);
#pragma unroll
            for (int i = 0; i < 2; i++) {
                const int j = 2 * m + i;
                const uint32_t wb = sbase + (SEQ_WO % NSLOT) * SLOT + (j >> 2) * 16384 + ((lane & 7) + (lane >> 4) * 8) * 128 +
                                    ((((2 * j + ((lane >> 3) & 1)) & 7) ^ (lane & 7)) << 4);
#pragma unroll
                for (int ks = 0; ks < 8; ks++) ldsm4t(af[i][ks], wb + ks * 2048);
            }
            TSX(5, tid == 128);
            bar_sync(2, 256);
            TSX(7, tid == 128);
            float acc[2][2][4] = {};
            uint32_t t4[4][4];
#pragma unroll
            for (int u = 0; u < 4; u++) ldsm4(t4[u], sbase + OFF_QS + (lane & 3) * QS_PITCH + (4 * u + (lane >> 3)) * 16);
            TSD(37, tid == 128, __uint_as_float(t4[0][0]));
#pragma unroll
            for (int u = 0; u < 4; u++) {
#pragma unroll
                for (int i = 0; i < 2; i++) {
                    mma16816(acc[i][0], af[i][2 * u], t4[u][0], t4[u][1]);
                    mma16816(acc[i][1], af[i][2 * u + 1], t4[u][2], t4[u][3]);
                }
            }
#pragma unroll
            for (int i = 0; i < 2; i++) {
                const float v0 = kh ? acc[i][0][2] + acc[i][1][2] : acc[i][0][0] + acc[i][1][0];
                const float v1 = kh ? acc[i][0][3] + acc[i][1][3] : acc[i][0][1] + acc[i][1][1];
                st_rel32(p_y + i * 32 * 16, __float_as_uint(v0));
                st_rel32(p_y + i * 32 * 16 + 32 * 32 * 16, __float_as_uint(v1));
            }
            TSX(8, tid == 128);
        }
        const uint16_t* hsrc = g_h + (r8 & 3) * 512 + 128 * m + 8 * q4;
        if (cta >= NFFN) {
            bar_sync(3, 160);
            uint4 hb0, hb1; Spin sp;
            while (true) { hb0 = ld_poll4(hsrc); hb1 = ld_poll4(hsrc + 64); if (__all_sync(0xffffffffu, valid8h(hb0) & valid8h(hb1))) break; sp.tick(); }
        } else {
            uint32_t gf[4][2][2][4];
            mbar_wait(bar_w, 0); mbar_wait(bar_w + 8, 0); mbar_wait(bar_w + 16, 0); mbar_wait(bar_w + 24, 0);
#pragma unroll
            for (int u = 0; u < 4; u++) {
#pragma unroll
                for (int ss = 0; ss < 2; ss++) {
                    const int k = 128 * m + 32 * u + 8 * ((lane & 7) >> 1) + 4 * ss + 2 * (lane >> 4) + (lane & 1);
                    const uint32_t a = sbase + SLOT_WGU * SLOT + k * 32 + ((((lane >> 3) & 1) ^ ((k >> 2) & 1)) << 4);
                    ldsm4t(gf[u][ss][0], a);
                    ldsm4t(gf[u][ss][1], a + 16384);
                }
            }
            TSX(11, tid == 128);
            constexpr uint32_t ONES = 0x3F803F80u;
            float sg = 0.f, su = 0.f;
            {
                float cs[2][4] = {};
#pragma unroll
                for (int u = 0; u < 4; u++) {
#pragma unroll
                    for (int ss = 0; ss < 2; ss++) { mma16816(cs[0], gf[u][ss][0], ONES, ONES); mma16816(cs[1], gf[u][ss][1], ONES, ONES); }
                }
                float* csb = reinterpret_cast<float*>(smem + OFF_CS);
                if (q4 == 0) {
                    csb[(m * 2 + 0) * 16 + r8] = cs[0][0]; csb[(m * 2 + 0) * 16 + r8 + 8] = cs[0][2];
                    csb[(m * 2 + 1) * 16 + r8] = cs[1][0]; csb[(m * 2 + 1) * 16 + r8 + 8] = cs[1][2];
                }
                bar_sync(5, 128);
                const int c = (tid & 63) >> 2;
#pragma unroll
                for (int ww = 0; ww < 4; ww++) { sg += csb[(ww * 2) * 16 + c]; su += csb[(ww * 2 + 1) * 16 + c]; }
            }
            const uint32_t wdb = sbase + SLOT_WD * SLOT + warp * 2048 + ((lane & 7) + (lane >> 4) * 8) * 128;
            const bool have_wd = __all_sync(0xffffffffu, mbar_try(bar_w + 32, 0) && mbar_try(bar_w + 40, 0));
            if (have_wd) {
#pragma unroll
                for (int i = 0; i < 4; i++) ldsm4t(df[i], wdb + (((2 * i + ((lane >> 3) & 1)) ^ (lane & 7)) << 4));
            }
            TSX(12, tid == 128);
            bar_sync(3, 160);
            uint4 hb[4];
            {
                Spin sp;
                while (true) {
                    hb[0] = ld_poll4(hsrc); hb[1] = ld_poll4(hsrc + 32); hb[2] = ld_poll4(hsrc + 64); hb[3] = ld_poll4(hsrc + 96);
                    if (__all_sync(0xffffffffu, valid8h(hb[0]) & valid8h(hb[1]) & valid8h(hb[2]) & valid8h(hb[3]))) break;
                    sp.tick();
                }
            }
            TSX(13, tid == 128);
            float acc[2][2][4] = {};
            float hs[2][4] = {}, hq[2][4] = {};
            {
                const uint32_t ones_a[4] = {ONES, 0u, ONES, 0u};
#pragma unroll
                for (int u = 0; u < 4; u++) {
                    mma16816(acc[0][0], gf[u][0][0], hb[u].x, hb[u].y);
                    mma16816(acc[1][0], gf[u][0][1], hb[u].x, hb[u].y);
                    mma16816(acc[0][1], gf[u][1][0], hb[u].z, hb[u].w);
                    mma16816(acc[1][1], gf[u][1][1], hb[u].z, hb[u].w);
                    const uint32_t ha0[4] = {hb[u].x, 0u, hb[u].y, 0u}, ha1[4] = {hb[u].z, 0u, hb[u].w, 0u};
                    mma16816(hq[0], ha0, hb[u].x, hb[u].y);
                    mma16816(hq[1], ha1, hb[u].z, hb[u].w);
                    mma16816(hs[0], ones_a, hb[u].x, hb[u].y);
                    mma16816(hs[1], ones_a, hb[u].z, hb[u].w);
                }
            }
            TSD(28, tid == 128, acc[1][1][0] + acc[0][0][0] + acc[0][1][0] + acc[1][0][0]);
            {
                float* stp = reinterpret_cast<float*>(smem + OFF_ST);
                if (lane < 2) *reinterpret_cast<float2*>(stp + m * 8 + 2 * lane) = make_float2(hs[0][0] + hs[1][0], hs[0][1] + hs[1][1]);
                if (r8 < 4 && q4 == (r8 >> 1)) stp[m * 8 + 4 + r8] = (r8 & 1) ? hq[0][1] + hq[1][1] : hq[0][0] + hq[1][0];
            }
            float* red = reinterpret_cast<float*>(smem + OFF_RED);
#pragma unroll
            for (int i = 0; i < 2; i++) {
                const float2 v = kh ? make_float2(acc[i][0][2] + acc[i][1][2], acc[i][0][3] + acc[i][1][3])
                                    : make_float2(acc[i][0][0] + acc[i][1][0], acc[i][0][1] + acc[i][1][1]);
                *reinterpret_cast<float2*>(red + ((m * 2 + i) * 16 + r8 + 8 * kh) * 4 + 2 * hp) = v;
            }
            bar_sync(4, 128);
            TSX(16, tid == 128);
            if (tid < 192) {
                const int c = (tid & 63) >> 2, b = tid & 3;
                const float* stp = reinterpret_cast<const float*>(smem + OFF_ST) + b;
                const float mean = ((stp[0] + stp[8]) + (stp[16] + stp[24])) * (1.0f / 512.0f);
                const float var = fmaxf(((stp[4] + stp[12]) + (stp[20] + stp[28])) * (1.0f / 512.0f) - mean * mean, 0.f);
                const float mb = bf16r(mean);
                float sq; asm("sqrt.approx.f32 %0, %1;" : "=f"(sq) : "f"(bf16r(bf16r(var) + 1e-5f)));
                const float rs = __fdividef(1.0f, bf16r(sq));
                float g = 0.f, u = 0.f;
#pragma unroll
                for (int ww = 0; ww < 4; ww++) { g += red[((ww * 2) * 16 + c) * 4 + b]; u += red[((ww * 2 + 1) * 16 + c) * 4 + b]; }
                TSD(29, tid == 128, g + u + rs);
                g = bf16r((g - mb * sg) * rs); u = bf16r((u - mb * su) * rs);
                const float inner = 0.7978845608028654f * (g + 0.044715f * g * g * g);
                const float th = 1.0f - __fdividef(2.0f, __expf(2.0f * inner) + 1.0f);
                const float ge = bf16r(0.5f * g * (1.0f + th));
                *reinterpret_cast<__nv_bfloat16*>(smem + OFF_ACT + b * 32 + c * 2) = __float2bfloat16_rn(ge * u);
                TSD(32, tid == 128, ge * u);
            }
            if (!have_wd) {
                mbar_wait(bar_w + 32, 0); mbar_wait(bar_w + 40, 0);
#pragma unroll
                for (int i = 0; i < 4; i++) ldsm4t(df[i], wdb + (((2 * i + ((lane >> 3) & 1)) ^ (lane & 7)) << 4));
            }
        }
    }
    if (cta < NFFN) {
        bar_sync(6, 256);
        TS(17);
        const uint32_t b0 = *reinterpret_cast<const uint32_t*>(smem + OFF_ACT + (r8 & 3) * 32 + q4 * 4);
        const uint32_t b1 = *reinterpret_cast<const uint32_t*>(smem + OFF_ACT + (r8 & 3) * 32 + 16 + q4 * 4);
        TSD(33, tid == 0, __uint_as_float(b0));
        float c[4][4] = {};
#pragma unroll
        for (int i = 0; i < 4; i++) mma16816(c[i], df[i], b0, b1);
#pragma unroll
        for (int i = 0; i < 4; i++) {
            st_rel32(p_dpart + i * NFFN * 16, __float_as_uint(kh ? c[i][2] : c[i][0]));
            st_rel32(p_dpart + i * NFFN * 16 + 32 * NFFN * 16, __float_as_uint(kh ? c[i][3] : c[i][1]));
        }
        TS(18);
    } else {
        bar_sync(6, 256);
        delay_cycles(DLY_F_IDLE);
    }

    {
        const int quad = tid & 3;
        const bool two = (tid >> 2) + 64 < NFFN;
        uint4 a, b = make_uint4(0, 0, 0, 0);
        Spin sp;
        delay_cycles(DLY_F);
        while (true) {
            a = ld_poll4(p_dsrc);
            if (two) b = ld_poll4(p_dsrc + 64 * 16);
            if (__all_sync(0xffffffffu, max(umax4(a), umax4(b)) != SENT)) break;
            sp.tick();
        }
        TS(19);
        float v[4] = {__uint_as_float(a.x) + __uint_as_float(b.x), __uint_as_float(a.y) + __uint_as_float(b.y),
                      __uint_as_float(a.z) + __uint_as_float(b.z), __uint_as_float(a.w) + __uint_as_float(b.w)};
        {
            const bool up = lane & 16;
            const float s0 = up ? v[0] : v[2], s1 = up ? v[1] : v[3];
            const float k0 = up ? v[2] : v[0], k1 = up ? v[3] : v[1];
            v[0] = k0 + __shfl_xor_sync(0xffffffffu, s0, 16);
            v[1] = k1 + __shfl_xor_sync(0xffffffffu, s1, 16);
            const bool up2 = lane & 8;
            const float s = up2 ? v[0] : v[1], k = up2 ? v[1] : v[0];
            v[0] = k + __shfl_xor_sync(0xffffffffu, s, 8);
            v[0] += __shfl_xor_sync(0xffffffffu, v[0], 4);
            if (!(lane & 4)) reinterpret_cast<float*>(smem + OFF_RED2)[warp * 16 + 4 * quad + ((lane & 16) ? 2 : 0) + ((lane & 8) ? 1 : 0)] = v[0];
        }
        cbar();
        TS(21);
        if (warp == 0) {
            const float* r2 = reinterpret_cast<const float*>(smem + OFF_RED2) + (lane & 1) * 64 + (lane >> 1);
            float s = (r2[0] + r2[16]) + (r2[32] + r2[48]);
            TSD(34, tid == 0, s);
            s += __shfl_xor_sync(0xffffffffu, s, 1);
            if (!(lane & 1)) *p_out = __float2bfloat16_rn(hres + bf16r(s));
            if (cta == 0 && lane == 0) st_rel32(&g_prog, 0u);
        }
    }
    TS(22);
    if (tid == 0) TSG(62);
}

typedef CUresult (*EncodeFn)(CUtensorMap*, CUtensorMapDataType, cuuint32_t, void*, const cuuint64_t*, const cuuint64_t*,
                             const cuuint32_t*, const cuuint32_t*, CUtensorMapInterleave, CUtensorMapSwizzle,
                             CUtensorMapL2promotion, CUtensorMapFloatOOBfill);

void encode(EncodeFn fn, CUtensorMap* m, const void* base, int rank, const cuuint64_t* dims, const cuuint64_t* strides,
            const cuuint32_t* box, CUtensorMapSwizzle sw, CUtensorMapL2promotion promo) {
    cuuint32_t es[3] = {1, 1, 1};
    fn(m, CU_TENSOR_MAP_DATA_TYPE_BFLOAT16, (cuuint32_t)rank, const_cast<void*>(base), dims, strides, box, es,
       CU_TENSOR_MAP_INTERLEAVE_NONE, sw, promo, CU_TENSOR_MAP_FLOAT_OOB_FILL_NONE);
}

}

extern "C" void kernel_launch(void* const* d_in, const int* in_sizes, int n_in, void* d_out, int out_size) {
    (void)in_sizes; (void)n_in; (void)out_size;
    static EncodeFn enc = nullptr;
    if (!enc) {
        void* fn = nullptr;
        cudaDriverEntryPointQueryResult qr;
        cudaGetDriverEntryPoint("cuTensorMapEncodeTiled", &fn, cudaEnableDefault, &qr);
        enc = (EncodeFn)fn;
        cudaFuncSetAttribute(fused_decode_kernel, cudaFuncAttributeMaxDynamicSharedMemorySize, SMEM_BYTES);
    }
    const void* x = d_in[0];
    Maps maps;
    {
        cuuint64_t dims[3] = {64, 262144, 2}; cuuint64_t str[2] = {256, 128}; cuuint32_t box[3] = {64, 128, 2};
        encode(enc, &maps.m[0], d_in[1], 3, dims, str, box, CU_TENSOR_MAP_SWIZZLE_128B, CU_TENSOR_MAP_L2_PROMOTION_L2_256B);
        encode(enc, &maps.m[1], d_in[2], 3, dims, str, box, CU_TENSOR_MAP_SWIZZLE_128B, CU_TENSOR_MAP_L2_PROMOTION_L2_256B);
    }
    {
        cuuint64_t dims[3] = {4096, 512, 1}; cuuint64_t str[2] = {8192, 8192 * 512}; cuuint32_t box[3] = {32, 256, 1};
        encode(enc, &maps.m[2], d_in[3], 3, dims, str, box, CU_TENSOR_MAP_SWIZZLE_64B, CU_TENSOR_MAP_L2_PROMOTION_L2_128B);
    }
    {
        cuuint64_t dims[3] = {64, 4096, 8}; cuuint64_t str[2] = {1024, 128}; cuuint32_t box[3] = {64, 128, 2};
        encode(enc, &maps.m[3], d_in[4], 3, dims, str, box, CU_TENSOR_MAP_SWIZZLE_128B, CU_TENSOR_MAP_L2_PROMOTION_L2_256B);
    }
    {
        cuuint64_t dims[3] = {1792, 512, 1}; cuuint64_t str[2] = {3584, 3584 * 512}; cuuint32_t box[3] = {16, 256, 1};
        encode(enc, &maps.m[4], d_in[6], 3, dims, str, box, CU_TENSOR_MAP_SWIZZLE_32B, CU_TENSOR_MAP_L2_PROMOTION_L2_128B);
        encode(enc, &maps.m[5], d_in[7], 3, dims, str, box, CU_TENSOR_MAP_SWIZZLE_32B, CU_TENSOR_MAP_L2_PROMOTION_L2_128B);
    }
    {
        cuuint64_t dims[3] = {64, 1792, 8}; cuuint64_t str[2] = {1024, 128}; cuuint32_t box[3] = {64, 16, 4};
        encode(enc, &maps.m[6], d_in[8], 3, dims, str, box, CU_TENSOR_MAP_SWIZZLE_128B, CU_TENSOR_MAP_L2_PROMOTION_L2_256B);
    }
    fused_decode_kernel<<<NCTA, NTHREADS, SMEM_BYTES, cudaStreamPerThread>>>(maps, (const __nv_bfloat16*)x, (__nv_bfloat16*)d_out);
}
```

```cpp
#include <cuda_runtime.h>
#include <cuda_bf16.h>
#include <cuda.h>
#include <stdint.h>

namespace {

constexpr int NCTA      = 128;
constexpr int NTHREADS  = 320;
constexpr int SLOT      = 32768;
constexpr int NSLOT     = 6;
constexpr int NTILE     = 16;
constexpr int NFFN      = 112;
constexpr int DEPTH_LO  = 2;
constexpr int DEPTH_HI  = 3;
constexpr int LEAD_THR8 = 4;
constexpr int WO_MARGIN = 112;
constexpr int WDEPTH    = 4;
constexpr int SEQ_WO    = 33;
constexpr int NSEQ      = 34;
constexpr int SLOT_WGU  = 4, SLOT_WD = 5;
constexpr int DLY_F     = 500;
constexpr int DLY_F_IDLE = 1100;
constexpr int RESET_TILE = 8;
#define SAMPLE_NS 100
constexpr uint32_t SENT = 0xFFFFFFFFu;

constexpr int OFF_XN   = NSLOT * SLOT;
constexpr int XN_PITCH = 1040;
constexpr int OFF_QS   = OFF_XN + 4 * XN_PITCH;
constexpr int QS_PITCH = 272;
constexpr int OFF_P    = OFF_QS + 4 * QS_PITCH;
constexpr int OFF_RED  = OFF_P + 4 * QS_PITCH;
constexpr int OFF_MX   = OFF_RED + 4096;
constexpr int OFF_L    = OFF_MX + 64;
constexpr int OFF_ACT  = OFF_L + 128;
constexpr int OFF_RED2 = OFF_ACT + 128;
constexpr int OFF_CS   = OFF_RED2 + 512;
constexpr int OFF_ST   = OFF_CS + 512;
constexpr int OFF_BAR  = OFF_ST + 32;
constexpr int OFF_VAR  = OFF_BAR + 192;
constexpr int SMEM_USED = OFF_VAR + 64;
constexpr int SMEM_BYTES = SMEM_USED + 1024;
static_assert(OFF_RED % 16 == 0 && OFF_MX % 16 == 0 && OFF_ST % 8 == 0 && OFF_BAR % 8 == 0, "alignment");

__device__ uint2    g_q[4 * 2048];
__device__ float    g_partO[32 * 4 * 4 * 128];
__device__ float2   g_ml[32 * 4 * 4];
__device__ float    g_ypart[4 * 32 * 32 * 16];
__device__ uint16_t g_h[4 * 512];
__device__ float    g_dpart[4 * 32 * NFFN * 16];
__device__ unsigned g_cnt0, g_cnt1, g_prog;

__device__ __forceinline__ uint32_t smem_u32(const void* p) { return (uint32_t)__cvta_generic_to_shared(p); }
__device__ __forceinline__ void mbar_init(uint32_t bar, uint32_t cnt) {
    asm volatile("mbarrier.init.shared::cta.b64 [%0], %1;" ::"r"(bar), "r"(cnt) : "memory");
}
__device__ __forceinline__ void mbar_expect_tx(uint32_t bar, uint32_t bytes) {
    asm volatile("mbarrier.arrive.expect_tx.shared::cta.b64 _, [%0], %1;" ::"r"(bar), "r"(bytes) : "memory");
}
__device__ __forceinline__ void mbar_arrive(uint32_t bar) {
    asm volatile("mbarrier.arrive.shared::cta.b64 _, [%0];" ::"r"(bar) : "memory");
}
__device__ __forceinline__ bool mbar_try(uint32_t bar, uint32_t parity) {
    uint32_t ok;
    asm volatile("{\n.reg .pred p;\nmbarrier.try_wait.parity.shared::cta.b64 p, [%1], %2;\nselp.u32 %0, 1, 0, p;\n}"
                 : "=r"(ok) : "r"(bar), "r"(parity) : "memory");
    return ok != 0;
}
constexpr uint32_t SPIN_LIMIT = 1u << 22;
__device__ __forceinline__ void mbar_wait(uint32_t bar, uint32_t parity) {
    uint32_t it = 0;
    while (!mbar_try(bar, parity)) { if (++it > SPIN_LIMIT) __trap(); }
}
__device__ __forceinline__ void tma3d(uint32_t dst, const CUtensorMap* m, int c0, int c1, int c2, uint32_t bar, uint64_t pol) {
    asm volatile("cp.async.bulk.tensor.3d.shared::cluster.global.mbarrier::complete_tx::bytes.L2::cache_hint [%0], [%1, {%3, %4, %5}], [%2], %6;"
                 ::"r"(dst), "l"(m), "r"(bar), "r"(c0), "r"(c1), "r"(c2), "l"(pol) : "memory");
}
__device__ __forceinline__ void ldsm4(uint32_t (&r)[4], uint32_t addr) {
    asm volatile("ldmatrix.sync.aligned.m8n8.x4.shared.b16 {%0,%1,%2,%3}, [%4];"
                 : "=r"(r[0]), "=r"(r[1]), "=r"(r[2]), "=r"(r[3]) : "r"(addr) : "memory");
}
__device__ __forceinline__ void ldsm4t(uint32_t (&r)[4], uint32_t addr) {
    asm volatile("ldmatrix.sync.aligned.m8n8.x4.trans.shared.b16 {%0,%1,%2,%3}, [%4];"
                 : "=r"(r[0]), "=r"(r[1]), "=r"(r[2]), "=r"(r[3]) : "r"(addr) : "memory");
}
__device__ __forceinline__ void mma16816(float (&c)[4], const uint32_t (&a)[4], uint32_t b0, uint32_t b1) {
    asm volatile("mma.sync.aligned.m16n8k16.row.col.f32.bf16.bf16.f32 {%0,%1,%2,%3}, {%4,%5,%6,%7}, {%8,%9}, {%0,%1,%2,%3};"
                 : "+f"(c[0]), "+f"(c[1]), "+f"(c[2]), "+f"(c[3])
                 : "r"(a[0]), "r"(a[1]), "r"(a[2]), "r"(a[3]), "r"(b0), "r"(b1));
}
__device__ __forceinline__ void cbar() { asm volatile("bar.sync 1, 256;" ::: "memory"); }
__device__ __forceinline__ void bar_sync(int id, int n) { asm volatile("bar.sync %0, %1;" ::"r"(id), "r"(n) : "memory"); }
__device__ __forceinline__ void bar_arrive(int id, int n) { asm volatile("bar.arrive %0, %1;" ::"r"(id), "r"(n) : "memory"); }
__device__ __forceinline__ uint4 ld_poll4(const void* p) {
    uint4 v;
    asm volatile("ld.relaxed.gpu.global.v4.u32 {%0,%1,%2,%3}, [%4];" : "=r"(v.x), "=r"(v.y), "=r"(v.z), "=r"(v.w) : "l"(p) : "memory");
    return v;
}
__device__ __forceinline__ uint2 ld_poll2(const void* p) {
    uint2 v;
    asm volatile("ld.relaxed.gpu.global.v2.u32 {%0,%1}, [%2];" : "=r"(v.x), "=r"(v.y) : "l"(p) : "memory");
    return v;
}
__device__ __forceinline__ void st_rel32(void* p, uint32_t v) { asm volatile("st.relaxed.gpu.global.u32 [%0], %1;" ::"l"(p), "r"(v) : "memory"); }
__device__ __forceinline__ void st_rel16(void* p, uint16_t v) { asm volatile("st.relaxed.gpu.global.u16 [%0], %1;" ::"l"(p), "h"(v) : "memory"); }
__device__ __forceinline__ void st_rel64(void* p, uint32_t a, uint32_t b) { asm volatile("st.relaxed.gpu.global.v2.u32 [%0], {%1,%2};" ::"l"(p), "r"(a), "r"(b) : "memory"); }
__device__ __forceinline__ void st_rel128(void* p, uint32_t v) { asm volatile("st.relaxed.gpu.global.v4.u32 [%0], {%1,%1,%1,%1};" ::"l"(p), "r"(v) : "memory"); }
__device__ __forceinline__ uint32_t umax4(const uint4& v) { return max(max(v.x, v.y), max(v.z, v.w)); }
template <class T> __device__ __forceinline__ void pin(T*& p) { asm volatile("" : "+l"(p)); }
__device__ __forceinline__ bool valid8h(const uint4& v) {
    return (__vcmpeq2(v.x, SENT) | __vcmpeq2(v.y, SENT) | __vcmpeq2(v.z, SENT) | __vcmpeq2(v.w, SENT)) == 0;
}
struct Spin {
    uint32_t it = 0;
    __device__ __forceinline__ void tick() { if (++it > SPIN_LIMIT) __trap(); }
};
__device__ __forceinline__ void wait_progress(int n) {
    Spin sp; unsigned v;
    while (true) {
        asm volatile("ld.relaxed.gpu.global.u32 %0, [%1];" : "=r"(v) : "l"(&g_prog) : "memory");
        if ((int)v >= n) break;
        sp.tick(); __nanosleep(64);
    }
}
__device__ __forceinline__ uint32_t pack_bf16(float lo, float hi) {
    uint32_t r; asm("cvt.rn.bf16x2.f32 %0, %1, %2;" : "=r"(r) : "f"(hi), "f"(lo)); return r;
}
__device__ __forceinline__ void delay_cycles(int n) { if (n > 0) { const long long t0 = clock64(); while (clock64() - t0 < n) {} } }
__device__ __forceinline__ float bf16r(float x) { return __uint_as_float(pack_bf16(0.f, x) & 0xFFFF0000u); }
__device__ __forceinline__ float bf_lo(uint32_t v) { return __uint_as_float(v << 16); }
__device__ __forceinline__ float bf_hi(uint32_t v) { return __uint_as_float(v & 0xFFFF0000u); }
__device__ __forceinline__ uint32_t hmax2(uint32_t a, uint32_t b) {
    uint32_t r; asm("max.bf16x2 %0, %1, %2;" : "=r"(r) : "r"(a), "r"(b)); return r;
}
__device__ __forceinline__ float ex2(float x) { float r; asm("ex2.approx.ftz.f32 %0, %1;" : "=f"(r) : "f"(x)); return r; }

__device__ __forceinline__ float2 ln_stats(const uint4& a, const uint4& b, float (&v)[16]) {
    v[0] = bf_lo(a.x); v[1] = bf_hi(a.x); v[2] = bf_lo(a.y); v[3] = bf_hi(a.y);
    v[4] = bf_lo(a.z); v[5] = bf_hi(a.z); v[6] = bf_lo(a.w); v[7] = bf_hi(a.w);
    v[8] = bf_lo(b.x); v[9] = bf_hi(b.x); v[10] = bf_lo(b.y); v[11] = bf_hi(b.y);
    v[12] = bf_lo(b.z); v[13] = bf_hi(b.z); v[14] = bf_lo(b.w); v[15] = bf_hi(b.w);
    const float shift = __shfl_sync(0xffffffffu, v[0], 0);
    float s0 = 0.f, s1 = 0.f, s2 = 0.f, s3 = 0.f, q0 = 0.f, q1 = 0.f, q2 = 0.f, q3 = 0.f;
#pragma unroll
    for (int i = 0; i < 16; i += 4) {
        const float d0 = v[i] - shift, d1 = v[i + 1] - shift, d2 = v[i + 2] - shift, d3 = v[i + 3] - shift;
        s0 += d0; s1 += d1; s2 += d2; s3 += d3;
        q0 = fmaf(d0, d0, q0); q1 = fmaf(d1, d1, q1); q2 = fmaf(d2, d2, q2); q3 = fmaf(d3, d3, q3);
    }
    float s = (s0 + s1) + (s2 + s3), ss = (q0 + q1) + (q2 + q3);
#pragma unroll
    for (int o = 16; o > 0; o >>= 1) { s += __shfl_xor_sync(0xffffffffu, s, o); ss += __shfl_xor_sync(0xffffffffu, ss, o); }
    const float md = s * (1.0f / 512.0f);
    const float var = fmaxf(ss * (1.0f / 512.0f) - md * md, 0.f);
    const float m = bf16r(shift + md);
    float sq; asm("sqrt.approx.f32 %0, %1;" : "=f"(sq) : "f"(bf16r(bf16r(var) + 1e-5f)));
    const float sd = bf16r(sq);
    return make_float2(m, __fdividef(1.0f, sd));
}

struct Maps { CUtensorMap m[7]; };

__global__ void __launch_bounds__(NTHREADS, 1)
fused_decode_kernel(const __grid_constant__ Maps maps, const __nv_bfloat16* __restrict__ x, __nv_bfloat16* __restrict__ out)
{
    extern __shared__ __align__(1024) unsigned char smem_raw[];
    unsigned char* smem = smem_raw + ((1024u - (smem_u32(smem_raw) & 1023u)) & 1023u);
    const uint32_t sbase = smem_u32(smem);
    const uint32_t bar_full = sbase + OFF_BAR, bar_empty = sbase + OFF_BAR + 48, bar_ready = sbase + OFF_BAR + 96, bar_w = sbase + OFF_BAR + 104;
    volatile unsigned* vars = reinterpret_cast<volatile unsigned*>(smem + OFF_VAR);
    const int tid = threadIdx.x, warp = tid >> 5, lane = tid & 31;
    const int cta = blockIdx.x;

    uint64_t pol;
    asm volatile("createpolicy.fractional.L2::evict_first.b64 %0, 1.0;" : "=l"(pol));
    if (__builtin_expect(tid == 256, 1)) {
        for (int i = 0; i < NSLOT; i++) { mbar_init(bar_full + 8 * i, 1); mbar_init(bar_empty + 8 * i, 8); }
        asm volatile("fence.mbarrier_init.release.cluster;" ::: "memory");
        mbar_expect_tx(bar_full, 32768);
        tma3d(sbase, &maps.m[2], cta * 32, 0, 0, bar_full, pol);
        tma3d(sbase + 16384, &maps.m[2], cta * 32, 256, 0, bar_full, pol);
        mbar_expect_tx(bar_full + 8, 32768);
        tma3d(sbase + SLOT, &maps.m[0], 0, cta * (NTILE * 128), 0, bar_full + 8, pol);
        mbar_expect_tx(bar_full + 16, 32768);
        tma3d(sbase + 2 * SLOT, &maps.m[1], 0, cta * (NTILE * 128), 0, bar_full + 16, pol);
        asm volatile("red.relaxed.gpu.global.add.u32 [%0], 2;" ::"l"(&g_prog) : "memory");
        mbar_init(bar_ready, 1);
        for (int i = 0; i < 6; i++) mbar_init(bar_w + 8 * i, 1);
        vars[1] = 0; vars[2] = 0; vars[3] = 0;
        asm volatile("fence.mbarrier_init.release.cluster;" ::: "memory");
    } else if (tid > 256 && tid <= 260) {
        asm volatile("prefetch.tensormap [%0];" ::"l"(&maps.m[tid - 254]) : "memory");
    }
    if (warp == 8) { __syncwarp(); bar_arrive(8, NTHREADS); } else bar_sync(8, NTHREADS);

    if (warp == 8) {
        if (lane == 0) {
            const int key0 = cta * (NTILE * 128);
            int arrived = 0;
            int nkv = 2;
            for (int i = 3; i < NSEQ; i++) {
                const int slot = i % NSLOT;
                const bool is_w = (i == SEQ_WO);
                if (i >= NSLOT) mbar_wait(bar_empty + 8 * slot, ((i / NSLOT) - 1) & 1);
                const int grel = (int)vars[2];
                const int lead8 = (nkv * NCTA - grel) / (NCTA / 8);
                const int d = (lead8 > LEAD_THR8) ? DEPTH_LO : DEPTH_HI;
                while (arrived < i - d + 1) { mbar_wait(bar_full + 8 * (arrived % NSLOT), (arrived / NSLOT) & 1); arrived++; }
                if (i == SEQ_WO && grel < NCTA * 32 - WO_MARGIN) wait_progress(NCTA * 32 - WO_MARGIN);
                const uint32_t dst = sbase + slot * SLOT, fb = bar_full + 8 * slot;
                mbar_expect_tx(fb, 32768);
                if (is_w) tma3d(dst, &maps.m[3], 0, (cta >> 2) * 128, (cta & 3) * 2, fb, pol);
                else      tma3d(dst, &maps.m[nkv & 1], 0, key0 + (nkv >> 1) * 128, 0, fb, pol);
                if (!is_w) {
                    asm volatile("red.relaxed.gpu.global.add.u32 [%0], 1;" ::"l"(&g_prog) : "memory");
                    nkv++;
                }
            }
            vars[3] = 1;
            if (cta < NFFN) {
                mbar_wait(bar_empty + 8 * SLOT_WGU, (34 / NSLOT - 1) & 1);
                mbar_wait(bar_empty + 8 * SLOT_WD, (35 / NSLOT - 1) & 1);
                wait_progress(NCTA * 32);
                mbar_wait(bar_full + 8 * (SEQ_WO % NSLOT), (SEQ_WO / NSLOT) & 1);
                for (int k = 0; k < 6; k++) {
                    if (k >= WDEPTH) mbar_wait(bar_w + 8 * (k - WDEPTH), 0);
                    mbar_expect_tx(bar_w + 8 * k, 8192);
                    const int mi = (k < 4) ? 4 + (k >> 1) : 6;
                    const int c0 = (k < 4) ? cta * 16 : 0, c1 = (k < 4) ? (k & 1) * 256 : cta * 16, c2 = (k < 4) ? 0 : (k - 4) * 4;
                    tma3d(sbase + SLOT_WGU * SLOT + k * 8192, &maps.m[mi], c0, c1, c2, bar_w + 8 * k, pol);
                }
            }
        }
        return;
    }

    const int pair = cta >> 2, split = cta & 3;

    if (warp == 9) {
        Spin sp;
        auto sample = [&]() {
            unsigned v;
            asm volatile("ld.relaxed.gpu.global.u32 %0, [%1];" : "=r"(v) : "l"(&g_prog) : "memory");
            if (lane == 0) vars[2] = v;
        };
        while (vars[1] < RESET_TILE) { sp.tick(); sample(); __nanosleep(SAMPLE_NS); }
        const unsigned epoch = vars[0];
#pragma unroll 1
        for (int u = lane; u < 128; u += 32) {
            st_rel128(&g_partO[((pair * 4 + (u >> 5)) * 4 + split) * 128 + (u & 31) * 4], SENT);
            const int seg = u >> 2;
            st_rel128(&g_ypart[(((seg >> 3) * 32 + (cta & 3) * 8 + (seg & 7)) * 32 + (cta >> 2)) * 16 + (u & 3) * 4], SENT);
        }
        if (lane < 4) st_rel64(&g_ml[(pair * 4 + lane) * 4 + split], SENT, SENT);
        if (lane < 2) st_rel128(&g_h[(cta >> 5) * 512 + (cta & 31) * 16 + lane * 8], SENT);
        if (cta < NFFN) {
#pragma unroll 1
            for (int e = lane; e < 512; e += 32) st_rel128(&g_dpart[((e >> 2) * NFFN + cta) * 16 + (e & 3) * 4], SENT);
        }
        __threadfence();
        __syncwarp();
        if (lane == 0) {
            atomicAdd(&g_cnt1, 1u);
            unsigned v; Spin sp2;
            while (true) {
                asm volatile("ld.acquire.gpu.global.u32 %0, [%1];" : "=r"(v) : "l"(&g_cnt1) : "memory");
                if ((int)(v - (epoch + 1) * NCTA) >= 0) break;
                sp2.tick(); sample(); __nanosleep(128);
            }
            mbar_arrive(bar_ready);
        }
        __syncwarp();
        while (vars[3] == 0) { sp.tick(); sample(); __nanosleep(SAMPLE_NS); }
        return;
    }

    const int r8 = lane >> 2, q4 = lane & 3;
    const int hp = q4 & 1, kh = q4 >> 1;
    constexpr float LOG2E = 1.4426950408889634f;
    const int bq = pair >> 3, gq = pair & 7;

    if (tid == 0) vars[0] = atomicAdd(&g_cnt0, 1u) >> 7;
    if (warp == 7) st_rel128(&g_q[(lane >> 3) * 2048 + cta * 16 + (lane & 7) * 2], 0u);
    float xres = 0.f;
    if (warp == 0) xres = __bfloat162float(x[(cta >> 5) * 512 + (cta & 31) * 16 + (lane >> 1)]);

    if (warp < 4) {
        const uint4* xr = reinterpret_cast<const uint4*>(x + warp * 512);
        const uint4 a = __ldg(xr + lane), b = __ldg(xr + 32 + lane);
        float v[16];
        const float2 st = ln_stats(a, b, v);
        uint32_t o[8];
#pragma unroll
        for (int i = 0; i < 8; i++) o[i] = pack_bf16(bf16r(v[2 * i] - st.x) * st.y, bf16r(v[2 * i + 1] - st.x) * st.y);
        unsigned char* row = smem + OFF_XN + warp * XN_PITCH;
        *reinterpret_cast<uint4*>(row + lane * 16) = make_uint4(o[0], o[1], o[2], o[3]);
        *reinterpret_cast<uint4*>(row + 512 + lane * 16) = make_uint4(o[4], o[5], o[6], o[7]);
    }
    cbar();
    const uint32_t tag = vars[0] + 1;

    {
        uint32_t bfr[4][2];
        {
            uint32_t t4[4];
#pragma unroll
            for (int u = 0; u < 2; u++) {
                ldsm4(t4, sbase + OFF_XN + (lane & 3) * XN_PITCH + (8 * warp + 4 * u + (lane >> 3)) * 16);
                bfr[2 * u][0] = t4[0]; bfr[2 * u][1] = t4[1]; bfr[2 * u + 1][0] = t4[2]; bfr[2 * u + 1][1] = t4[3];
            }
        }
        mbar_wait(bar_full + 0, 0);
        float acc[2][4] = {};
#pragma unroll
        for (int ks = 0; ks < 4; ks++) {
            const int k = 64 * warp + 16 * ks + (lane & 7) + (lane >> 4) * 8;
#pragma unroll
            for (int mt = 0; mt < 2; mt++) {
                uint32_t a[4];
                const int chunk = 2 * mt + ((lane >> 3) & 1);
                ldsm4t(a, sbase + k * 64 + ((chunk ^ ((k >> 1) & 3)) << 4));
                mma16816(acc[mt], a, bfr[ks][0], bfr[ks][1]);
            }
        }
        __syncwarp();
        if (lane == 0) mbar_arrive(bar_empty + 0);
        float* red = reinterpret_cast<float*>(smem + OFF_RED);
#pragma unroll
        for (int mt = 0; mt < 2; mt++) {
            float2 v = kh ? make_float2(acc[mt][2], acc[mt][3]) : make_float2(acc[mt][0], acc[mt][1]);
            *reinterpret_cast<float2*>(red + ((warp * 2 + mt) * 16 + r8 + 8 * kh) * 4 + 2 * hp) = v;
        }
        cbar();
        if (tid < 64) {
            const int b = tid >> 4, c2 = tid & 15;
            float s0 = 0.f, s1 = 0.f;
            const int c0 = 2 * c2, c1 = 2 * c2 + 1;
#pragma unroll
            for (int ww = 0; ww < 8; ww++) {
                s0 += red[((ww * 2 + (c0 >> 4)) * 16 + (c0 & 15)) * 4 + b];
                s1 += red[((ww * 2 + (c1 >> 4)) * 16 + (c1 & 15)) * 4 + b];
            }
            st_rel64(&g_q[b * 2048 + cta * 16 + c2], pack_bf16(s0, s1), tag);
        }
        {
            const uint2* src = &g_q[bq * 2048 + gq * 256 + tid];
            uint2 v;
            Spin sp;
            while (true) { v = ld_poll2(src); if (__all_sync(0xffffffffu, v.y == tag)) break; sp.tick(); }
            *reinterpret_cast<uint32_t*>(smem + OFF_QS + (tid >> 6) * QS_PITCH + (tid & 63) * 4) = v.x;
        }
        cbar();
    }
    uint32_t qf[8][2];
    {
        uint32_t t4[4];
#pragma unroll
        for (int u = 0; u < 4; u++) {
            ldsm4(t4, sbase + OFF_QS + (lane & 3) * QS_PITCH + (4 * u + (lane >> 3)) * 16);
            qf[2 * u][0] = t4[0]; qf[2 * u][1] = t4[1]; qf[2 * u + 1][0] = t4[2]; qf[2 * u + 1][1] = t4[3];
        }
    }

    const uint32_t voff = (warp >> 2) * 16384 + ((lane & 7) + (lane >> 4) * 8) * 128 +
                          ((((2 * warp + ((lane >> 3) & 1)) & 7) ^ (lane & 7)) << 4);
    const uint32_t poff = sbase + OFF_P + (lane & 3) * QS_PITCH + (lane >> 3) * 16;
    const uint32_t koff = (16 * warp + (lane & 7) + ((lane >> 3) & 1) * 8) * 128;
    const uint32_t kx = lane & 7, kc = lane >> 4;
    constexpr float SCALE = 0.08838834764831845f;
    uint32_t* mxbuf = reinterpret_cast<uint32_t*>(smem + OFF_MX);
    uint32_t M2 = 0xFF80FF80u;
    float l0 = 0.f, l1 = 0.f;
    float oacc[2][4] = {};
    int slot = 1; uint32_t ph = 0;

    for (int t = 0;; t++) {
        mbar_wait(bar_full + 8 * slot, ph);
        float sa[4] = {}, sb[4] = {};
        {
            const uint32_t kb = sbase + slot * SLOT + koff;
#pragma unroll
            for (int ks = 0; ks < 8; ks++) {
                uint32_t a[4];
                ldsm4(a, kb + (ks >> 2) * 16384 + (((2 * (ks & 3) + kc) ^ kx) << 4));
                if (ks & 1) mma16816(sb, a, qf[ks][0], qf[ks][1]); else mma16816(sa, a, qf[ks][0], qf[ks][1]);
            }
        }
        __syncwarp();
        if (lane == 0) mbar_arrive(bar_empty + 8 * slot);
        if (++slot == NSLOT) { slot = 0; ph ^= 1; }

        const float r0 = kh ? sa[2] + sb[2] : sa[0] + sb[0];
        const float r1 = kh ? sa[3] + sb[3] : sa[1] + sb[1];
        uint32_t sp = pack_bf16(r0, r1);
        sp = pack_bf16(bf_lo(sp) * SCALE, bf_hi(sp) * SCALE);
        uint32_t mx = sp;
#pragma unroll
        for (int o = 2; o <= 16; o <<= 1) mx = hmax2(mx, __shfl_xor_sync(0xffffffffu, mx, o));
        if (lane < 2) mxbuf[lane * 8 + warp] = mx;
        if (tid == 0) vars[1] = t + 1;
        cbar();
        {
            const uint4 m0 = *reinterpret_cast<const uint4*>(mxbuf + hp * 8), m1 = *reinterpret_cast<const uint4*>(mxbuf + hp * 8 + 4);
            uint32_t mt = hmax2(hmax2(hmax2(m0.x, m0.y), hmax2(m0.z, m0.w)), hmax2(hmax2(m1.x, m1.y), hmax2(m1.z, m1.w)));
            const uint32_t Mn = hmax2(M2, mt);
            const float a0 = ex2((bf_lo(M2) - bf_lo(Mn)) * LOG2E), a1 = ex2((bf_hi(M2) - bf_hi(Mn)) * LOG2E);
            const float p0 = ex2((bf_lo(sp) - bf_lo(Mn)) * LOG2E), p1 = ex2((bf_hi(sp) - bf_hi(Mn)) * LOG2E);
            M2 = Mn;
            l0 = fmaf(l0, a0, p0); l1 = fmaf(l1, a1, p1);
            const uint32_t pp = pack_bf16(p0, p1);
            unsigned char* pd = smem + OFF_P + (2 * hp) * QS_PITCH + (16 * warp + r8 + 8 * kh) * 2;
            *reinterpret_cast<uint16_t*>(pd) = (uint16_t)(pp & 0xFFFF);
            *reinterpret_cast<uint16_t*>(pd + QS_PITCH) = (uint16_t)(pp >> 16);
#pragma unroll
            for (int c = 0; c < 2; c++) { oacc[c][0] *= a0; oacc[c][1] *= a1; oacc[c][2] *= a0; oacc[c][3] *= a1; }
        }
        if (t == NTILE - 1) break;
        cbar();
        uint32_t pb[8][2];
        {
            uint32_t t4[4];
#pragma unroll
            for (int u = 0; u < 4; u++) {
                ldsm4(t4, poff + u * 64);
                pb[2 * u][0] = t4[0]; pb[2 * u][1] = t4[1]; pb[2 * u + 1][0] = t4[2]; pb[2 * u + 1][1] = t4[3];
            }
        }
        mbar_wait(bar_full + 8 * slot, ph);
        {
            const uint32_t vb = sbase + slot * SLOT + voff;
#pragma unroll
            for (int ks = 0; ks < 8; ks++) {
                uint32_t a[4];
                ldsm4t(a, vb + ks * 2048);
                mma16816(oacc[ks & 1], a, pb[ks][0], pb[ks][1]);
            }
        }
        __syncwarp();
        if (lane == 0) mbar_arrive(bar_empty + 8 * slot);
        if (++slot == NSLOT) { slot = 0; ph ^= 1; }
    }

    const int head = cta >> 2;
    float* p_partO = &g_partO[((pair * 4 + 2 * hp) * 4 + split) * 128 + 16 * warp + r8 + 8 * kh];
    float* p_dpart = &g_dpart[(((2 * hp) * 32 + 4 * warp) * NFFN + cta) * 16 + r8 + 8 * kh];
    const float* p_dsrc = &g_dpart[(cta * NFFN + (tid >> 2)) * 16 + (tid & 3) * 4];
    __nv_bfloat16* p_out = out + (cta >> 5) * 512 + (cta & 31) * 16 + (lane >> 1);
    pin(p_partO); pin(p_dpart); pin(p_dsrc); pin(p_out);

    {
        float s0 = l0, s1 = l1;
#pragma unroll
        for (int o = 2; o <= 16; o <<= 1) { s0 += __shfl_xor_sync(0xffffffffu, s0, o); s1 += __shfl_xor_sync(0xffffffffu, s1, o); }
        if (lane < 2) *reinterpret_cast<float2*>(smem + OFF_L + warp * 16 + lane * 8) = make_float2(s0, s1);
        mbar_wait(bar_ready, 0);
        cbar();
        if (warp == 0) {
            const uint32_t other = __shfl_sync(0xffffffffu, M2, lane >> 1);
            float l = 0.f;
#pragma unroll
            for (int ww = 0; ww < 8; ww++) l += *reinterpret_cast<const float*>(smem + OFF_L + ww * 16 + (lane & 3) * 4);
            const float m = (lane & 1) ? bf_hi(other) : bf_lo(other);
            if (lane < 4) st_rel64(&g_ml[(pair * 4 + lane) * 4 + split], __float_as_uint(m), __float_as_uint(l));
        }
        uint32_t pb[8][2];
        {
            uint32_t t4[4];
#pragma unroll
            for (int u = 0; u < 4; u++) {
                ldsm4(t4, poff + u * 64);
                pb[2 * u][0] = t4[0]; pb[2 * u][1] = t4[1]; pb[2 * u + 1][0] = t4[2]; pb[2 * u + 1][1] = t4[3];
            }
        }
        float o2[2][4] = {};
        {
            mbar_wait(bar_full + 8 * slot, ph);
            const uint32_t vb = sbase + slot * SLOT + voff;
            uint32_t a[8][4];
#pragma unroll
            for (int ks = 0; ks < 8; ks++) ldsm4t(a[ks], vb + ks * 2048);
#pragma unroll
            for (int ks = 0; ks < 8; ks++) mma16816((ks & 2) ? o2[ks & 1] : oacc[ks & 1], a[ks], pb[ks][0], pb[ks][1]);
        }
        const float v0 = kh ? (oacc[0][2] + oacc[1][2]) + (o2[0][2] + o2[1][2]) : (oacc[0][0] + oacc[1][0]) + (o2[0][0] + o2[1][0]);
        const float v1 = kh ? (oacc[0][3] + oacc[1][3]) + (o2[0][3] + o2[1][3]) : (oacc[0][1] + oacc[1][1]) + (o2[0][1] + o2[1][1]);
        st_rel32(p_partO, __float_as_uint(v0));
        st_rel32(p_partO + 512, __float_as_uint(v1));
    }

    float hres = 0.f;
    uint32_t df[4][4];
    if (warp < 4) {
        {
            const int ph_idx = (warp * 8 + (head >> 2)) * 4 + (head & 3);
            const float* po = &g_partO[ph_idx * 512 + lane * 4];
            const float* pm = reinterpret_cast<const float*>(&g_ml[ph_idx * 4]);
            uint4 o0, o1, o2, o3, ma, mb;
            Spin sp;
            while (true) {
                o0 = ld_poll4(po); o1 = ld_poll4(po + 128); o2 = ld_poll4(po + 256); o3 = ld_poll4(po + 384);
                ma = ld_poll4(pm); mb = ld_poll4(pm + 4);
                const uint32_t mxv = max(max(max(umax4(o0), umax4(o1)), max(umax4(o2), umax4(o3))), max(umax4(ma), umax4(mb)));
                if (__all_sync(0xffffffffu, mxv != SENT)) break;
                sp.tick();
            }
            const float m0 = __uint_as_float(ma.x), m1 = __uint_as_float(ma.z), m2 = __uint_as_float(mb.x), m3 = __uint_as_float(mb.z);
            const float M = fmaxf(fmaxf(m0, m1), fmaxf(m2, m3));
            float w0 = ex2((m0 - M) * LOG2E), w1 = ex2((m1 - M) * LOG2E), w2 = ex2((m2 - M) * LOG2E), w3 = ex2((m3 - M) * LOG2E);
            const float L = w0 * __uint_as_float(ma.y) + w1 * __uint_as_float(ma.w) + w2 * __uint_as_float(mb.y) + w3 * __uint_as_float(mb.w);
            const float inv = __fdividef(1.0f, L);
            const float e0 = (w0 * __uint_as_float(o0.x) + w1 * __uint_as_float(o1.x) + w2 * __uint_as_float(o2.x) + w3 * __uint_as_float(o3.x)) * inv;
            const float e1 = (w0 * __uint_as_float(o0.y) + w1 * __uint_as_float(o1.y) + w2 * __uint_as_float(o2.y) + w3 * __uint_as_float(o3.y)) * inv;
            const float e2 = (w0 * __uint_as_float(o0.z) + w1 * __uint_as_float(o1.z) + w2 * __uint_as_float(o2.z) + w3 * __uint_as_float(o3.z)) * inv;
            const float e3 = (w0 * __uint_as_float(o0.w) + w1 * __uint_as_float(o1.w) + w2 * __uint_as_float(o2.w) + w3 * __uint_as_float(o3.w)) * inv;
            *reinterpret_cast<uint2*>(smem + OFF_QS + warp * QS_PITCH + lane * 8) = make_uint2(pack_bf16(e0, e1), pack_bf16(e2, e3));
            bar_arrive(2, 256);
        }
        {
            const float* src = &g_ypart[(cta * 32 + 8 * warp + (lane >> 2)) * 16 + (lane & 3) * 4];
            uint16_t* p_h = &g_h[(cta >> 5) * 512 + (cta & 31) * 16 + (lane >> 1)];
            pin(p_h);
            uint4 y;
            Spin sp;
            while (true) {
                y = ld_poll4(src);
                if (__all_sync(0xffffffffu, umax4(y) != SENT)) break;
                sp.tick();
            }
            const bool up = lane & 16, up2 = lane & 8;
            const float a0 = __uint_as_float(y.x), a1 = __uint_as_float(y.y), a2 = __uint_as_float(y.z), a3 = __uint_as_float(y.w);
            const float v0 = (up ? a2 : a0) + __shfl_xor_sync(0xffffffffu, up ? a0 : a2, 16);
            const float v1 = (up ? a3 : a1) + __shfl_xor_sync(0xffffffffu, up ? a1 : a3, 16);
            float v = (up2 ? v1 : v0) + __shfl_xor_sync(0xffffffffu, up2 ? v0 : v1, 8);
            v += __shfl_xor_sync(0xffffffffu, v, 4);
            float* rc = reinterpret_cast<float*>(smem + OFF_RED2);
            if (!(lane & 4)) rc[warp * 16 + 4 * (lane & 3) + (up ? 2 : 0) + (up2 ? 1 : 0)] = v;
            bar_sync(7, 128);
            if (warp == 0) {
                const float* r2 = rc + (lane & 1) * 32 + (lane >> 1);
                float t = r2[0] + r2[16];
                t += __shfl_xor_sync(0xffffffffu, t, 1);
                hres = bf16r(xres + bf16r(t));
                if (!(lane & 1)) st_rel16(p_h, (uint16_t)(__float_as_uint(hres) >> 16));
            }
        }
        {
            const uint4* hr = reinterpret_cast<const uint4*>(g_h + warp * 512);
            uint4 a, b;
            Spin sp;
            while (true) {
                a = ld_poll4(hr + lane); b = ld_poll4(hr + 32 + lane);
                if (__all_sync(0xffffffffu, valid8h(a) & valid8h(b))) break;
                sp.tick();
            }
            if (cta < NFFN) {
                unsigned char* row = smem + OFF_XN + warp * XN_PITCH;
                *reinterpret_cast<uint4*>(row + lane * 16) = a;
                *reinterpret_cast<uint4*>(row + 512 + lane * 16) = b;
                bar_arrive(3, 256);
                float v[16];
                const float2 st = ln_stats(a, b, v);
                if (lane == 0) *reinterpret_cast<float2*>(smem + OFF_ST + warp * 8) = st;
                bar_arrive(4, 256);
                mbar_wait(bar_w + 32, 0); mbar_wait(bar_w + 40, 0);
                const uint32_t wb = sbase + SLOT_WD * SLOT + warp * 2048 + ((lane & 7) + (lane >> 4) * 8) * 128;
#pragma unroll
                for (int i = 0; i < 4; i++) ldsm4t(df[i], wb + (((2 * i + ((lane >> 3) & 1)) ^ (lane & 7)) << 4));
            }
        }
    } else {
        const int m = warp - 4;
        {
            uint32_t af[2][8][4];
            float* p_y = &g_ypart[(((2 * hp) * 32 + (cta & 3) * 8 + 2 * m) * 32 + head) * 16 + r8 + 8 * kh];
            pin(p_y);
            mbar_wait(bar_full + 8 * (SEQ_WO % NSLOT), (SEQ_WO / NSLOT) & 1);
#pragma unroll
            for (int i = 0; i < 2; i++) {
                const int j = 2 * m + i;
                const uint32_t wb = sbase + (SEQ_WO % NSLOT) * SLOT + (j >> 2) * 16384 + ((lane & 7) + (lane >> 4) * 8) * 128 +
                                    ((((2 * j + ((lane >> 3) & 1)) & 7) ^ (lane & 7)) << 4);
#pragma unroll
                for (int ks = 0; ks < 8; ks++) ldsm4t(af[i][ks], wb + ks * 2048);
            }
            bar_sync(2, 256);
            float acc[2][2][4] = {};
            uint32_t t4[4][4];
#pragma unroll
            for (int u = 0; u < 4; u++) ldsm4(t4[u], sbase + OFF_QS + (lane & 3) * QS_PITCH + (4 * u + (lane >> 3)) * 16);
#pragma unroll
            for (int u = 0; u < 4; u++) {
#pragma unroll
                for (int i = 0; i < 2; i++) {
                    mma16816(acc[i][0], af[i][2 * u], t4[u][0], t4[u][1]);
                    mma16816(acc[i][1], af[i][2 * u + 1], t4[u][2], t4[u][3]);
                }
            }
#pragma unroll
            for (int i = 0; i < 2; i++) {
                const float v0 = kh ? acc[i][0][2] + acc[i][1][2] : acc[i][0][0] + acc[i][1][0];
                const float v1 = kh ? acc[i][0][3] + acc[i][1][3] : acc[i][0][1] + acc[i][1][1];
                st_rel32(p_y + i * 32 * 16, __float_as_uint(v0));
                st_rel32(p_y + i * 32 * 16 + 32 * 32 * 16, __float_as_uint(v1));
            }
        }
        if (cta < NFFN) {
            uint32_t gf[8][2][4];
            mbar_wait(bar_w, 0); mbar_wait(bar_w + 8, 0); mbar_wait(bar_w + 16, 0); mbar_wait(bar_w + 24, 0);
#pragma unroll
            for (int ks = 0; ks < 8; ks++) {
                const int k = 128 * m + 16 * ks + (lane & 7) + (lane >> 4) * 8;
                const uint32_t a = sbase + SLOT_WGU * SLOT + k * 32 + ((((lane >> 3) & 1) ^ ((k >> 2) & 1)) << 4);
                ldsm4t(gf[ks][0], a);
                ldsm4t(gf[ks][1], a + 16384);
            }
            float sg = 0.f, su = 0.f;
            {
                float cs[2][4] = {};
#pragma unroll
                for (int ks = 0; ks < 8; ks++) { mma16816(cs[0], gf[ks][0], 0x3F803F80u, 0x3F803F80u); mma16816(cs[1], gf[ks][1], 0x3F803F80u, 0x3F803F80u); }
                float* csb = reinterpret_cast<float*>(smem + OFF_CS);
                if (q4 == 0) {
                    csb[(m * 2 + 0) * 16 + r8] = cs[0][0]; csb[(m * 2 + 0) * 16 + r8 + 8] = cs[0][2];
                    csb[(m * 2 + 1) * 16 + r8] = cs[1][0]; csb[(m * 2 + 1) * 16 + r8 + 8] = cs[1][2];
                }
                bar_sync(5, 128);
                const int c = (tid & 63) >> 2;
#pragma unroll
                for (int ww = 0; ww < 4; ww++) { sg += csb[(ww * 2) * 16 + c]; su += csb[(ww * 2 + 1) * 16 + c]; }
            }
            const uint32_t wdb = sbase + SLOT_WD * SLOT + warp * 2048 + ((lane & 7) + (lane >> 4) * 8) * 128;
            const bool have_wd = __all_sync(0xffffffffu, mbar_try(bar_w + 32, 0) && mbar_try(bar_w + 40, 0));
            if (have_wd) {
#pragma unroll
                for (int i = 0; i < 4; i++) ldsm4t(df[i], wdb + (((2 * i + ((lane >> 3) & 1)) ^ (lane & 7)) << 4));
            }
            bar_sync(3, 256);
            float acc[2][2][4] = {};
            uint32_t t4[4][4];
#pragma unroll
            for (int u = 0; u < 4; u++) ldsm4(t4[u], sbase + OFF_XN + (lane & 3) * XN_PITCH + (16 * m + 4 * u + (lane >> 3)) * 16);
#pragma unroll
            for (int u = 0; u < 4; u++) {
#pragma unroll
                for (int i = 0; i < 2; i++) {
                    mma16816(acc[i][0], gf[2 * u][i], t4[u][0], t4[u][1]);
                    mma16816(acc[i][1], gf[2 * u + 1][i], t4[u][2], t4[u][3]);
                }
            }
            float* red = reinterpret_cast<float*>(smem + OFF_RED);
#pragma unroll
            for (int i = 0; i < 2; i++) {
                const float2 v = kh ? make_float2(acc[i][0][2] + acc[i][1][2], acc[i][0][3] + acc[i][1][3])
                                    : make_float2(acc[i][0][0] + acc[i][1][0], acc[i][0][1] + acc[i][1][1]);
                *reinterpret_cast<float2*>(red + ((m * 2 + i) * 16 + r8 + 8 * kh) * 4 + 2 * hp) = v;
            }
            bar_sync(4, 256);
            if (tid < 192) {
                const int c = (tid & 63) >> 2, b = tid & 3;
                const float2 st = *reinterpret_cast<const float2*>(smem + OFF_ST + b * 8);
                float g = 0.f, u = 0.f;
#pragma unroll
                for (int ww = 0; ww < 4; ww++) { g += red[((ww * 2) * 16 + c) * 4 + b]; u += red[((ww * 2 + 1) * 16 + c) * 4 + b]; }
                g = bf16r((g - st.x * sg) * st.y); u = bf16r((u - st.x * su) * st.y);
                const float inner = 0.7978845608028654f * (g + 0.044715f * g * g * g);
                const float th = 1.0f - __fdividef(2.0f, __expf(2.0f * inner) + 1.0f);
                const float ge = bf16r(0.5f * g * (1.0f + th));
                *reinterpret_cast<__nv_bfloat16*>(smem + OFF_ACT + b * 32 + c * 2) = __float2bfloat16_rn(ge * u);
            }
            if (!have_wd) {
                mbar_wait(bar_w + 32, 0); mbar_wait(bar_w + 40, 0);
#pragma unroll
                for (int i = 0; i < 4; i++) ldsm4t(df[i], wdb + (((2 * i + ((lane >> 3) & 1)) ^ (lane & 7)) << 4));
            }
        }
    }
    if (cta < NFFN) {
        bar_sync(6, 256);
        const uint32_t b0 = *reinterpret_cast<const uint32_t*>(smem + OFF_ACT + (r8 & 3) * 32 + q4 * 4);
        const uint32_t b1 = *reinterpret_cast<const uint32_t*>(smem + OFF_ACT + (r8 & 3) * 32 + 16 + q4 * 4);
        float c[4][4] = {};
#pragma unroll
        for (int i = 0; i < 4; i++) mma16816(c[i], df[i], b0, b1);
#pragma unroll
        for (int i = 0; i < 4; i++) {
            st_rel32(p_dpart + i * NFFN * 16, __float_as_uint(kh ? c[i][2] : c[i][0]));
            st_rel32(p_dpart + i * NFFN * 16 + 32 * NFFN * 16, __float_as_uint(kh ? c[i][3] : c[i][1]));
        }
    } else {
        bar_sync(6, 256);
        delay_cycles(DLY_F_IDLE);
    }

    {
        const int quad = tid & 3;
        const bool two = (tid >> 2) + 64 < NFFN;
        uint4 a, b = make_uint4(0, 0, 0, 0);
        Spin sp;
        delay_cycles(DLY_F);
        while (true) {
            a = ld_poll4(p_dsrc);
            if (two) b = ld_poll4(p_dsrc + 64 * 16);
            if (__all_sync(0xffffffffu, max(umax4(a), umax4(b)) != SENT)) break;
            sp.tick();
        }
        float v[4] = {__uint_as_float(a.x) + __uint_as_float(b.x), __uint_as_float(a.y) + __uint_as_float(b.y),
                      __uint_as_float(a.z) + __uint_as_float(b.z), __uint_as_float(a.w) + __uint_as_float(b.w)};
        {
            const bool up = lane & 16;
            const float s0 = up ? v[0] : v[2], s1 = up ? v[1] : v[3];
            const float k0 = up ? v[2] : v[0], k1 = up ? v[3] : v[1];
            v[0] = k0 + __shfl_xor_sync(0xffffffffu, s0, 16);
            v[1] = k1 + __shfl_xor_sync(0xffffffffu, s1, 16);
            const bool up2 = lane & 8;
            const float s = up2 ? v[0] : v[1], k = up2 ? v[1] : v[0];
            v[0] = k + __shfl_xor_sync(0xffffffffu, s, 8);
            v[0] += __shfl_xor_sync(0xffffffffu, v[0], 4);
            if (!(lane & 4)) reinterpret_cast<float*>(smem + OFF_RED2)[warp * 16 + 4 * quad + ((lane & 16) ? 2 : 0) + ((lane & 8) ? 1 : 0)] = v[0];
        }
        cbar();
        if (warp == 0) {
            const float* r2 = reinterpret_cast<const float*>(smem + OFF_RED2) + (lane & 1) * 64 + (lane >> 1);
            float s = (r2[0] + r2[16]) + (r2[32] + r2[48]);
            s += __shfl_xor_sync(0xffffffffu, s, 1);
            if (!(lane & 1)) *p_out = __float2bfloat16_rn(hres + bf16r(s));
            if (cta == 0 && lane == 0) st_rel32(&g_prog, 0u);
        }
    }
}

typedef CUresult (*EncodeFn)(CUtensorMap*, CUtensorMapDataType, cuuint32_t, void*, const cuuint64_t*, const cuuint64_t*,
                             const cuuint32_t*, const cuuint32_t*, CUtensorMapInterleave, CUtensorMapSwizzle,
                             CUtensorMapL2promotion, CUtensorMapFloatOOBfill);

void encode(EncodeFn fn, CUtensorMap* m, const void* base, int rank, const cuuint64_t* dims, const cuuint64_t* strides,
            const cuuint32_t* box, CUtensorMapSwizzle sw, CUtensorMapL2promotion promo) {
    cuuint32_t es[3] = {1, 1, 1};
    fn(m, CU_TENSOR_MAP_DATA_TYPE_BFLOAT16, (cuuint32_t)rank, const_cast<void*>(base), dims, strides, box, es,
       CU_TENSOR_MAP_INTERLEAVE_NONE, sw, promo, CU_TENSOR_MAP_FLOAT_OOB_FILL_NONE);
}

}

extern "C" void kernel_launch(void* const* d_in, const int* in_sizes, int n_in, void* d_out, int out_size) {
    (void)in_sizes; (void)n_in; (void)out_size;
    static EncodeFn enc = nullptr;
    if (!enc) {
        void* fn = nullptr;
        cudaDriverEntryPointQueryResult qr;
        cudaGetDriverEntryPoint("cuTensorMapEncodeTiled", &fn, cudaEnableDefault, &qr);
        enc = (EncodeFn)fn;
        cudaFuncSetAttribute(fused_decode_kernel, cudaFuncAttributeMaxDynamicSharedMemorySize, SMEM_BYTES);
    }
    const void* x = d_in[0];
    Maps maps;
    {
        cuuint64_t dims[3] = {64, 262144, 2}; cuuint64_t str[2] = {256, 128}; cuuint32_t box[3] = {64, 128, 2};
        encode(enc, &maps.m[0], d_in[1], 3, dims, str, box, CU_TENSOR_MAP_SWIZZLE_128B, CU_TENSOR_MAP_L2_PROMOTION_L2_256B);
        encode(enc, &maps.m[1], d_in[2], 3, dims, str, box, CU_TENSOR_MAP_SWIZZLE_128B, CU_TENSOR_MAP_L2_PROMOTION_L2_256B);
    }
    {
        cuuint64_t dims[3] = {4096, 512, 1}; cuuint64_t str[2] = {8192, 8192 * 512}; cuuint32_t box[3] = {32, 256, 1};
        encode(enc, &maps.m[2], d_in[3], 3, dims, str, box, CU_TENSOR_MAP_SWIZZLE_64B, CU_TENSOR_MAP_L2_PROMOTION_L2_128B);
    }
    {
        cuuint64_t dims[3] = {64, 4096, 8}; cuuint64_t str[2] = {1024, 128}; cuuint32_t box[3] = {64, 128, 2};
        encode(enc, &maps.m[3], d_in[4], 3, dims, str, box, CU_TENSOR_MAP_SWIZZLE_128B, CU_TENSOR_MAP_L2_PROMOTION_L2_256B);
    }
    {
        cuuint64_t dims[3] = {1792, 512, 1}; cuuint64_t str[2] = {3584, 3584 * 512}; cuuint32_t box[3] = {16, 256, 1};
        encode(enc, &maps.m[4], d_in[6], 3, dims, str, box, CU_TENSOR_MAP_SWIZZLE_32B, CU_TENSOR_MAP_L2_PROMOTION_L2_128B);
        encode(enc, &maps.m[5], d_in[7], 3, dims, str, box, CU_TENSOR_MAP_SWIZZLE_32B, CU_TENSOR_MAP_L2_PROMOTION_L2_128B);
    }
    {
        cuuint64_t dims[3] = {64, 1792, 8}; cuuint64_t str[2] = {1024, 128}; cuuint32_t box[3] = {64, 16, 4};
        encode(enc, &maps.m[6], d_in[8], 3, dims, str, box, CU_TENSOR_MAP_SWIZZLE_128B, CU_TENSOR_MAP_L2_PROMOTION_L2_256B);
    }
    fused_decode_kernel<<<NCTA, NTHREADS, SMEM_BYTES, cudaStreamPerThread>>>(maps, (const __nv_bfloat16*)x, (__nv_bfloat16*)d_out);
}
```

```cpp
#include <cuda_runtime.h>
#include <cuda_bf16.h>
#include <cuda.h>
#include <stdint.h>

namespace {

constexpr int NCTA      = 128;
constexpr int NTHREADS  = 320;
constexpr int SLOT      = 32768;
constexpr int NSLOT     = 6;
constexpr int NTILE     = 16;
constexpr int NFFN      = 112;
constexpr int DEPTH_LO  = 2;
#define DHI 3
constexpr int DEPTH_HI  = DHI;
#define THR8 8
constexpr int LEAD_THR8 = THR8;
#define WOM 112
constexpr int WO_MARGIN = WOM;
constexpr int WDEPTH    = 4;
constexpr int SEQ_WO    = 33;
constexpr int NSEQ      = 34;
constexpr int SLOT_WGU  = 4, SLOT_WD = 5;
constexpr int DLY_F     = 500;
constexpr int DLY_F_IDLE = 1100;
constexpr int RESET_TILE = 8;
#define NPRE 1
#define PRE_DLY1 0
#define PRE_DLY2 0
#define SAMPLE_NS 100
constexpr uint32_t SENT = 0xFFFFFFFFu;

constexpr int OFF_XN   = NSLOT * SLOT;
constexpr int XN_PITCH = 1040;
constexpr int OFF_QS   = OFF_XN + 4 * XN_PITCH;
constexpr int QS_PITCH = 272;
constexpr int OFF_P    = OFF_QS + 4 * QS_PITCH;
constexpr int OFF_RED  = OFF_P + 4 * QS_PITCH;
constexpr int OFF_MX   = OFF_RED + 8192;
constexpr int OFF_L    = OFF_MX + 64;
constexpr int OFF_ACT  = OFF_L + 128;
constexpr int OFF_RED2 = OFF_ACT + 128;
constexpr int OFF_CS   = OFF_RED2 + 512;
constexpr int OFF_ST   = OFF_CS + 512;
constexpr int OFF_BAR  = OFF_ST + 32;
constexpr int OFF_VAR  = OFF_BAR + 192;
constexpr int SMEM_USED = OFF_VAR + 64;
constexpr int SMEM_BYTES = SMEM_USED + 1024;
static_assert(OFF_RED % 16 == 0 && OFF_MX % 16 == 0 && OFF_ST % 8 == 0 && OFF_BAR % 8 == 0, "alignment");

__device__ uint2    g_q[2 * 4 * 4096];
__device__ float    g_partO[32 * 4 * 4 * 128];
__device__ float2   g_ml[32 * 4 * 4];
__device__ float    g_ypart[4 * 32 * 32 * 16];
__device__ uint16_t g_h[4 * 512];
__device__ float    g_dpart[4 * 32 * NFFN * 16];
__device__ unsigned g_cnt0, g_cnt1, g_prog;

__device__ __forceinline__ uint32_t smem_u32(const void* p) { return (uint32_t)__cvta_generic_to_shared(p); }
__device__ __forceinline__ void mbar_init(uint32_t bar, uint32_t cnt) {
    asm volatile("mbarrier.init.shared::cta.b64 [%0], %1;" ::"r"(bar), "r"(cnt) : "memory");
}
__device__ __forceinline__ void mbar_expect_tx(uint32_t bar, uint32_t bytes) {
    asm volatile("mbarrier.arrive.expect_tx.shared::cta.b64 _, [%0], %1;" ::"r"(bar), "r"(bytes) : "memory");
}
__device__ __forceinline__ void mbar_arrive(uint32_t bar) {
    asm volatile("mbarrier.arrive.shared::cta.b64 _, [%0];" ::"r"(bar) : "memory");
}
__device__ __forceinline__ bool mbar_try(uint32_t bar, uint32_t parity) {
    uint32_t ok;
    asm volatile("{\n.reg .pred p;\nmbarrier.try_wait.parity.shared::cta.b64 p, [%1], %2;\nselp.u32 %0, 1, 0, p;\n}"
                 : "=r"(ok) : "r"(bar), "r"(parity) : "memory");
    return ok != 0;
}
constexpr uint32_t SPIN_LIMIT = 1u << 22;
__device__ __forceinline__ void mbar_wait(uint32_t bar, uint32_t parity) {
    uint32_t it = 0;
    while (!mbar_try(bar, parity)) { if (++it > SPIN_LIMIT) __trap(); }
}
__device__ __forceinline__ void tma3d(uint32_t dst, const CUtensorMap* m, int c0, int c1, int c2, uint32_t bar, uint64_t pol) {
    asm volatile("cp.async.bulk.tensor.3d.shared::cluster.global.mbarrier::complete_tx::bytes.L2::cache_hint [%0], [%1, {%3, %4, %5}], [%2], %6;"
                 ::"r"(dst), "l"(m), "r"(bar), "r"(c0), "r"(c1), "r"(c2), "l"(pol) : "memory");
}
__device__ __forceinline__ void ldsm4(uint32_t (&r)[4], uint32_t addr) {
    asm volatile("ldmatrix.sync.aligned.m8n8.x4.shared.b16 {%0,%1,%2,%3}, [%4];"
                 : "=r"(r[0]), "=r"(r[1]), "=r"(r[2]), "=r"(r[3]) : "r"(addr) : "memory");
}
__device__ __forceinline__ void ldsm4t(uint32_t (&r)[4], uint32_t addr) {
    asm volatile("ldmatrix.sync.aligned.m8n8.x4.trans.shared.b16 {%0,%1,%2,%3}, [%4];"
                 : "=r"(r[0]), "=r"(r[1]), "=r"(r[2]), "=r"(r[3]) : "r"(addr) : "memory");
}
__device__ __forceinline__ void mma16816(float (&c)[4], const uint32_t (&a)[4], uint32_t b0, uint32_t b1) {
    asm volatile("mma.sync.aligned.m16n8k16.row.col.f32.bf16.bf16.f32 {%0,%1,%2,%3}, {%4,%5,%6,%7}, {%8,%9}, {%0,%1,%2,%3};"
                 : "+f"(c[0]), "+f"(c[1]), "+f"(c[2]), "+f"(c[3])
                 : "r"(a[0]), "r"(a[1]), "r"(a[2]), "r"(a[3]), "r"(b0), "r"(b1));
}
__device__ __forceinline__ void cbar() { asm volatile("bar.sync 1, 256;" ::: "memory"); }
__device__ __forceinline__ void bar_sync(int id, int n) { asm volatile("bar.sync %0, %1;" ::"r"(id), "r"(n) : "memory"); }
__device__ __forceinline__ void bar_arrive(int id, int n) { asm volatile("bar.arrive %0, %1;" ::"r"(id), "r"(n) : "memory"); }
__device__ __forceinline__ uint4 ld_poll4(const void* p) {
    uint4 v;
    asm volatile("ld.relaxed.gpu.global.v4.u32 {%0,%1,%2,%3}, [%4];" : "=r"(v.x), "=r"(v.y), "=r"(v.z), "=r"(v.w) : "l"(p) : "memory");
    return v;
}
__device__ __forceinline__ void st_rel32(void* p, uint32_t v) { asm volatile("st.relaxed.gpu.global.u32 [%0], %1;" ::"l"(p), "r"(v) : "memory"); }
__device__ __forceinline__ void st_rel16(void* p, uint16_t v) { asm volatile("st.relaxed.gpu.global.u16 [%0], %1;" ::"l"(p), "h"(v) : "memory"); }
__device__ __forceinline__ void st_rel64(void* p, uint32_t a, uint32_t b) { asm volatile("st.relaxed.gpu.global.v2.u32 [%0], {%1,%2};" ::"l"(p), "r"(a), "r"(b) : "memory"); }
__device__ __forceinline__ void st_rel128(void* p, uint32_t v) { asm volatile("st.relaxed.gpu.global.v4.u32 [%0], {%1,%1,%1,%1};" ::"l"(p), "r"(v) : "memory"); }
__device__ __forceinline__ uint32_t umax4(const uint4& v) { return max(max(v.x, v.y), max(v.z, v.w)); }
template <class T> __device__ __forceinline__ void pin(T*& p) { asm volatile("" : "+l"(p)); }
__device__ __forceinline__ bool valid8h(const uint4& v) {
    return (__vcmpeq2(v.x, SENT) | __vcmpeq2(v.y, SENT) | __vcmpeq2(v.z, SENT) | __vcmpeq2(v.w, SENT)) == 0;
}
struct Spin {
    uint32_t it = 0;
    __device__ __forceinline__ void tick() { if (++it > SPIN_LIMIT) __trap(); }
};
__device__ __forceinline__ void wait_progress(int n) {
    Spin sp; unsigned v;
    while (true) {
        asm volatile("ld.relaxed.gpu.global.u32 %0, [%1];" : "=r"(v) : "l"(&g_prog) : "memory");
        if ((int)v >= n) break;
        sp.tick(); __nanosleep(64);
    }
}
__device__ __forceinline__ uint32_t pack_bf16(float lo, float hi) {
    uint32_t r; asm("cvt.rn.bf16x2.f32 %0, %1, %2;" : "=r"(r) : "f"(hi), "f"(lo)); return r;
}
__device__ __forceinline__ void delay_cycles(int n) { if (n > 0) { const long long t0 = clock64(); while (clock64() - t0 < n) {} } }
__device__ __forceinline__ float bf16r(float x) { return __uint_as_float(pack_bf16(0.f, x) & 0xFFFF0000u); }
__device__ __forceinline__ float bf_lo(uint32_t v) { return __uint_as_float(v << 16); }
__device__ __forceinline__ float bf_hi(uint32_t v) { return __uint_as_float(v & 0xFFFF0000u); }
__device__ __forceinline__ uint32_t hmax2(uint32_t a, uint32_t b) {
    uint32_t r; asm("max.bf16x2 %0, %1, %2;" : "=r"(r) : "r"(a), "r"(b)); return r;
}
__device__ __forceinline__ float ex2(float x) { float r; asm("ex2.approx.ftz.f32 %0, %1;" : "=f"(r) : "f"(x)); return r; }

__device__ __forceinline__ float2 ln_stats(const uint4& a, const uint4& b, float (&v)[16]) {
    v[0] = bf_lo(a.x); v[1] = bf_hi(a.x); v[2] = bf_lo(a.y); v[3] = bf_hi(a.y);
    v[4] = bf_lo(a.z); v[5] = bf_hi(a.z); v[6] = bf_lo(a.w); v[7] = bf_hi(a.w);
    v[8] = bf_lo(b.x); v[9] = bf_hi(b.x); v[10] = bf_lo(b.y); v[11] = bf_hi(b.y);
    v[12] = bf_lo(b.z); v[13] = bf_hi(b.z); v[14] = bf_lo(b.w); v[15] = bf_hi(b.w);
    const float shift = __shfl_sync(0xffffffffu, v[0], 0);
    float s0 = 0.f, s1 = 0.f, s2 = 0.f, s3 = 0.f, q0 = 0.f, q1 = 0.f, q2 = 0.f, q3 = 0.f;
#pragma unroll
    for (int i = 0; i < 16; i += 4) {
        const float d0 = v[i] - shift, d1 = v[i + 1] - shift, d2 = v[i + 2] - shift, d3 = v[i + 3] - shift;
        s0 += d0; s1 += d1; s2 += d2; s3 += d3;
        q0 = fmaf(d0, d0, q0); q1 = fmaf(d1, d1, q1); q2 = fmaf(d2, d2, q2); q3 = fmaf(d3, d3, q3);
    }
    float s = (s0 + s1) + (s2 + s3), ss = (q0 + q1) + (q2 + q3);
#pragma unroll
    for (int o = 16; o > 0; o >>= 1) { s += __shfl_xor_sync(0xffffffffu, s, o); ss += __shfl_xor_sync(0xffffffffu, ss, o); }
    const float md = s * (1.0f / 512.0f);
    const float var = fmaxf(ss * (1.0f / 512.0f) - md * md, 0.f);
    const float m = bf16r(shift + md);
    float sq; asm("sqrt.approx.f32 %0, %1;" : "=f"(sq) : "f"(bf16r(bf16r(var) + 1e-5f)));
    const float sd = bf16r(sq);
    return make_float2(m, __fdividef(1.0f, sd));
}

struct Maps { CUtensorMap m[7]; };

__global__ void __launch_bounds__(NTHREADS, 1)
fused_decode_kernel(const __grid_constant__ Maps maps, const __nv_bfloat16* __restrict__ x, __nv_bfloat16* __restrict__ out)
{
    extern __shared__ __align__(1024) unsigned char smem_raw[];
    unsigned char* smem = smem_raw + ((1024u - (smem_u32(smem_raw) & 1023u)) & 1023u);
    const uint32_t sbase = smem_u32(smem);
    const uint32_t bar_full = sbase + OFF_BAR, bar_empty = sbase + OFF_BAR + 48, bar_ready = sbase + OFF_BAR + 96, bar_w = sbase + OFF_BAR + 104;
    volatile unsigned* vars = reinterpret_cast<volatile unsigned*>(smem + OFF_VAR);
    const int tid = threadIdx.x, warp = tid >> 5, lane = tid & 31;
    const int cta = blockIdx.x;

    uint64_t pol;
    asm volatile("createpolicy.fractional.L2::evict_first.b64 %0, 1.0;" : "=l"(pol));
    if (__builtin_expect(tid == 256, 1)) {
        for (int i = 0; i < NSLOT; i++) { mbar_init(bar_full + 8 * i, 1); mbar_init(bar_empty + 8 * i, 8); }
        asm volatile("fence.mbarrier_init.release.cluster;" ::: "memory");
        mbar_expect_tx(bar_full, 32768);
        tma3d(sbase, &maps.m[2], (cta >> 1) * 64, (cta & 1) * 256, 0, bar_full, pol);
        delay_cycles(PRE_DLY1);
        mbar_expect_tx(bar_full + 8, 32768);
        tma3d(sbase + SLOT, &maps.m[0], 0, cta * (NTILE * 128), 0, bar_full + 8, pol);
        if (NPRE > 0) asm volatile("red.relaxed.gpu.global.add.u32 [%0], %1;" ::"l"(&g_prog), "r"(NPRE) : "memory");
        mbar_init(bar_ready, 1);
        for (int i = 0; i < 6; i++) mbar_init(bar_w + 8 * i, 1);
        vars[1] = 0; vars[2] = 0; vars[3] = 0;
        asm volatile("fence.mbarrier_init.release.cluster;" ::: "memory");
    } else if (tid > 256 && tid <= 263) {
        asm volatile("prefetch.tensormap [%0];" ::"l"(&maps.m[tid - 257]) : "memory");
    }
    if (warp == 8) { __syncwarp(); bar_arrive(8, NTHREADS); } else bar_sync(8, NTHREADS);

    if (warp == 8) {
        if (lane == 0) {
            const int key0 = cta * (NTILE * 128);
            int arrived = 0;
            int nkv = NPRE;
            for (int i = 1 + NPRE; i < NSEQ; i++) {
                const int slot = i % NSLOT;
                const bool is_w = (i == SEQ_WO);
                if (i >= NSLOT) mbar_wait(bar_empty + 8 * slot, ((i / NSLOT) - 1) & 1);
                const int grel = (int)vars[2];
                const int lead8 = (nkv * NCTA - grel) / (NCTA / 8);
                const int d = (lead8 > LEAD_THR8) ? DEPTH_LO : DEPTH_HI;
                while (arrived < i - d + 1) { mbar_wait(bar_full + 8 * (arrived % NSLOT), (arrived / NSLOT) & 1); arrived++; }
                if (i == SEQ_WO && grel < NCTA * 32 - WO_MARGIN) wait_progress(NCTA * 32 - WO_MARGIN);
                const uint32_t dst = sbase + slot * SLOT, fb = bar_full + 8 * slot;
                mbar_expect_tx(fb, 32768);
                if (is_w) tma3d(dst, &maps.m[3], 0, (cta >> 2) * 128, (cta & 3) * 2, fb, pol);
                else      tma3d(dst, &maps.m[nkv & 1], 0, key0 + (nkv >> 1) * 128, 0, fb, pol);
                if (!is_w) {
                    asm volatile("red.relaxed.gpu.global.add.u32 [%0], 1;" ::"l"(&g_prog) : "memory");
                    nkv++;
                }
            }
            vars[3] = 1;
            if (cta < NFFN) {
                mbar_wait(bar_empty + 8 * SLOT_WGU, (34 / NSLOT - 1) & 1);
                mbar_wait(bar_empty + 8 * SLOT_WD, (35 / NSLOT - 1) & 1);
                wait_progress(NCTA * 32);
                mbar_wait(bar_full + 8 * (SEQ_WO % NSLOT), (SEQ_WO / NSLOT) & 1);
                for (int k = 0; k < 6; k++) {
                    if (k >= WDEPTH) mbar_wait(bar_w + 8 * (k - WDEPTH), 0);
                    mbar_expect_tx(bar_w + 8 * k, 8192);
                    const int mi = (k < 4) ? 4 + (k >> 1) : 6;
                    const int c0 = (k < 4) ? cta * 16 : 0, c1 = (k < 4) ? (k & 1) * 256 : cta * 16, c2 = (k < 4) ? 0 : (k - 4) * 4;
                    tma3d(sbase + SLOT_WGU * SLOT + k * 8192, &maps.m[mi], c0, c1, c2, bar_w + 8 * k, pol);
                }
            }
        }
        return;
    }

    const int pair = cta >> 2, split = cta & 3;

    if (warp == 9) {
        Spin sp;
        auto sample = [&]() {
            unsigned v;
            asm volatile("ld.relaxed.gpu.global.u32 %0, [%1];" : "=r"(v) : "l"(&g_prog) : "memory");
            if (lane == 0) vars[2] = v;
        };
        while (vars[1] < RESET_TILE) { sp.tick(); sample(); __nanosleep(SAMPLE_NS); }
        const unsigned epoch = vars[0];
#pragma unroll 1
        for (int u = lane; u < 128; u += 32) {
            st_rel128(&g_partO[((pair * 4 + (u >> 5)) * 4 + split) * 128 + (u & 31) * 4], SENT);
            const int seg = u >> 2;
            st_rel128(&g_ypart[(((seg >> 3) * 32 + (cta & 3) * 8 + (seg & 7)) * 32 + (cta >> 2)) * 16 + (u & 3) * 4], SENT);
        }
        if (lane < 4) st_rel64(&g_ml[(pair * 4 + lane) * 4 + split], SENT, SENT);
        if (lane < 2) st_rel128(&g_h[(cta >> 5) * 512 + (cta & 31) * 16 + lane * 8], SENT);
        if (cta < NFFN) {
#pragma unroll 1
            for (int e = lane; e < 512; e += 32) st_rel128(&g_dpart[((e >> 2) * NFFN + cta) * 16 + (e & 3) * 4], SENT);
        }
        __threadfence();
        __syncwarp();
        if (lane == 0) {
            atomicAdd(&g_cnt1, 1u);
            unsigned v; Spin sp2;
            while (true) {
                asm volatile("ld.acquire.gpu.global.u32 %0, [%1];" : "=r"(v) : "l"(&g_cnt1) : "memory");
                if ((int)(v - (epoch + 1) * NCTA) >= 0) break;
                sp2.tick(); sample(); __nanosleep(128);
            }
            mbar_arrive(bar_ready);
        }
        __syncwarp();
        while (vars[3] == 0) { sp.tick(); sample(); __nanosleep(SAMPLE_NS); }
        return;
    }

    const int r8 = lane >> 2, q4 = lane & 3;
    const int hp = q4 & 1, kh = q4 >> 1;
    constexpr float LOG2E = 1.4426950408889634f;
    const int bq = pair >> 3, gq = pair & 7;

    if (tid == 0) vars[0] = atomicAdd(&g_cnt0, 1u) >> 7;
    if (warp >= 4) st_rel128(&g_q[((cta & 1) * 4 + (warp - 4)) * 4096 + (cta >> 1) * 64 + lane * 2], 0u);
    float xres = 0.f;
    if (warp == 0) xres = __bfloat162float(x[(cta >> 5) * 512 + (cta & 31) * 16 + (lane >> 1)]);

    if (warp < 4) {
        const uint4* xr = reinterpret_cast<const uint4*>(x + warp * 512);
        const uint4 a = __ldg(xr + lane), b = __ldg(xr + 32 + lane);
        float v[16];
        const float2 st = ln_stats(a, b, v);
        uint32_t o[8];
#pragma unroll
        for (int i = 0; i < 8; i++) o[i] = pack_bf16(bf16r(v[2 * i] - st.x) * st.y, bf16r(v[2 * i + 1] - st.x) * st.y);
        unsigned char* row = smem + OFF_XN + warp * XN_PITCH;
        *reinterpret_cast<uint4*>(row + lane * 16) = make_uint4(o[0], o[1], o[2], o[3]);
        *reinterpret_cast<uint4*>(row + 512 + lane * 16) = make_uint4(o[4], o[5], o[6], o[7]);
    }
    cbar();
    const uint32_t tag = vars[0] + 1;

    {
        uint32_t bq4[4];
        ldsm4(bq4, sbase + OFF_XN + (lane & 3) * XN_PITCH + (32 * (cta & 1) + 4 * warp + (lane >> 3)) * 16);
        mbar_wait(bar_full + 0, 0);
        float acc[4][4] = {};
#pragma unroll
        for (int ks = 0; ks < 2; ks++) {
            const int k = 32 * warp + 16 * ks + (lane & 7) + (lane >> 4) * 8;
#pragma unroll
            for (int mt = 0; mt < 4; mt++) {
                uint32_t a[4];
                ldsm4t(a, sbase + k * 128 + (((2 * mt + ((lane >> 3) & 1)) ^ (lane & 7)) << 4));
                mma16816(acc[mt], a, bq4[2 * ks], bq4[2 * ks + 1]);
            }
        }
        __syncwarp();
        if (lane == 0) mbar_arrive(bar_empty + 0);
        float* red = reinterpret_cast<float*>(smem + OFF_RED);
#pragma unroll
        for (int mt = 0; mt < 4; mt++) {
            float2 v = kh ? make_float2(acc[mt][2], acc[mt][3]) : make_float2(acc[mt][0], acc[mt][1]);
            *reinterpret_cast<float2*>(red + ((warp * 4 + mt) * 16 + r8 + 8 * kh) * 4 + 2 * hp) = v;
        }
        cbar();
        {
            const int col = tid >> 2, b = tid & 3;
            float s0 = 0.f;
#pragma unroll
            for (int ww = 0; ww < 8; ww++) s0 += red[(ww * 64 + col) * 4 + b];
            st_rel64(&g_q[((cta & 1) * 4 + b) * 4096 + (cta >> 1) * 64 + col], __float_as_uint(s0), tag);
        }
        {
            const uint2* src = &g_q[bq * 4096 + gq * 512 + 2 * tid];
            uint4 lo, hi;
            Spin sp;
            while (true) {
                lo = ld_poll4(src); hi = ld_poll4(src + 4 * 4096);
                if (__all_sync(0xffffffffu, (lo.y == tag) & (lo.w == tag) & (hi.y == tag) & (hi.w == tag))) break;
                sp.tick();
            }
            *reinterpret_cast<uint32_t*>(smem + OFF_QS + (tid >> 6) * QS_PITCH + (tid & 63) * 4) =
                pack_bf16(__uint_as_float(lo.x) + __uint_as_float(hi.x), __uint_as_float(lo.z) + __uint_as_float(hi.z));
        }
        cbar();
    }
    uint32_t qf[8][2];
    {
        uint32_t t4[4];
#pragma unroll
        for (int u = 0; u < 4; u++) {
            ldsm4(t4, sbase + OFF_QS + (lane & 3) * QS_PITCH + (4 * u + (lane >> 3)) * 16);
            qf[2 * u][0] = t4[0]; qf[2 * u][1] = t4[1]; qf[2 * u + 1][0] = t4[2]; qf[2 * u + 1][1] = t4[3];
        }
    }

    const uint32_t voff = (warp >> 2) * 16384 + ((lane & 7) + (lane >> 4) * 8) * 128 +
                          ((((2 * warp + ((lane >> 3) & 1)) & 7) ^ (lane & 7)) << 4);
    const uint32_t poff = sbase + OFF_P + (lane & 3) * QS_PITCH + (lane >> 3) * 16;
    const uint32_t koff = (16 * warp + (lane & 7) + ((lane >> 3) & 1) * 8) * 128;
    const uint32_t kx = lane & 7, kc = lane >> 4;
    constexpr float SCALE = 0.08838834764831845f;
    uint32_t* mxbuf = reinterpret_cast<uint32_t*>(smem + OFF_MX);
    uint32_t M2 = 0xFF80FF80u;
    float l0 = 0.f, l1 = 0.f;
    float oacc[2][4] = {};
    int slot = 1; uint32_t ph = 0;

    for (int t = 0;; t++) {
        mbar_wait(bar_full + 8 * slot, ph);
        float sa[4] = {}, sb[4] = {};
        {
            const uint32_t kb = sbase + slot * SLOT + koff;
#pragma unroll
            for (int ks = 0; ks < 8; ks++) {
                uint32_t a[4];
                ldsm4(a, kb + (ks >> 2) * 16384 + (((2 * (ks & 3) + kc) ^ kx) << 4));
                if (ks & 1) mma16816(sb, a, qf[ks][0], qf[ks][1]); else mma16816(sa, a, qf[ks][0], qf[ks][1]);
            }
        }
        __syncwarp();
        if (lane == 0) mbar_arrive(bar_empty + 8 * slot);
        if (++slot == NSLOT) { slot = 0; ph ^= 1; }

        const float r0 = kh ? sa[2] + sb[2] : sa[0] + sb[0];
        const float r1 = kh ? sa[3] + sb[3] : sa[1] + sb[1];
        uint32_t sp = pack_bf16(r0, r1);
        sp = pack_bf16(bf_lo(sp) * SCALE, bf_hi(sp) * SCALE);
        uint32_t mx = sp;
#pragma unroll
        for (int o = 2; o <= 16; o <<= 1) mx = hmax2(mx, __shfl_xor_sync(0xffffffffu, mx, o));
        if (lane < 2) mxbuf[lane * 8 + warp] = mx;
        if (tid == 0) vars[1] = t + 1;
        cbar();
        {
            const uint4 m0 = *reinterpret_cast<const uint4*>(mxbuf + hp * 8), m1 = *reinterpret_cast<const uint4*>(mxbuf + hp * 8 + 4);
            uint32_t mt = hmax2(hmax2(hmax2(m0.x, m0.y), hmax2(m0.z, m0.w)), hmax2(hmax2(m1.x, m1.y), hmax2(m1.z, m1.w)));
            const uint32_t Mn = hmax2(M2, mt);
            const float a0 = ex2((bf_lo(M2) - bf_lo(Mn)) * LOG2E), a1 = ex2((bf_hi(M2) - bf_hi(Mn)) * LOG2E);
            const float p0 = ex2((bf_lo(sp) - bf_lo(Mn)) * LOG2E), p1 = ex2((bf_hi(sp) - bf_hi(Mn)) * LOG2E);
            M2 = Mn;
            l0 = fmaf(l0, a0, p0); l1 = fmaf(l1, a1, p1);
            const uint32_t pp = pack_bf16(p0, p1);
            unsigned char* pd = smem + OFF_P + (2 * hp) * QS_PITCH + (16 * warp + r8 + 8 * kh) * 2;
            *reinterpret_cast<uint16_t*>(pd) = (uint16_t)(pp & 0xFFFF);
            *reinterpret_cast<uint16_t*>(pd + QS_PITCH) = (uint16_t)(pp >> 16);
#pragma unroll
            for (int c = 0; c < 2; c++) { oacc[c][0] *= a0; oacc[c][1] *= a1; oacc[c][2] *= a0; oacc[c][3] *= a1; }
        }
        if (t == NTILE - 1) break;
        cbar();
        uint32_t pb[8][2];
        {
            uint32_t t4[4];
#pragma unroll
            for (int u = 0; u < 4; u++) {
                ldsm4(t4, poff + u * 64);
                pb[2 * u][0] = t4[0]; pb[2 * u][1] = t4[1]; pb[2 * u + 1][0] = t4[2]; pb[2 * u + 1][1] = t4[3];
            }
        }
        mbar_wait(bar_full + 8 * slot, ph);
        {
            const uint32_t vb = sbase + slot * SLOT + voff;
#pragma unroll
            for (int ks = 0; ks < 8; ks++) {
                uint32_t a[4];
                ldsm4t(a, vb + ks * 2048);
                mma16816(oacc[ks & 1], a, pb[ks][0], pb[ks][1]);
            }
        }
        __syncwarp();
        if (lane == 0) mbar_arrive(bar_empty + 8 * slot);
        if (++slot == NSLOT) { slot = 0; ph ^= 1; }
    }

    const int head = cta >> 2;
    float* p_partO = &g_partO[((pair * 4 + 2 * hp) * 4 + split) * 128 + 16 * warp + r8 + 8 * kh];
    float* p_dpart = &g_dpart[(((2 * hp) * 32 + 4 * warp) * NFFN + cta) * 16 + r8 + 8 * kh];
    const float* p_dsrc = &g_dpart[(cta * NFFN + (tid >> 2)) * 16 + (tid & 3) * 4];
    __nv_bfloat16* p_out = out + (cta >> 5) * 512 + (cta & 31) * 16 + (lane >> 1);
    pin(p_partO); pin(p_dpart); pin(p_dsrc); pin(p_out);

    {
        float s0 = l0, s1 = l1;
#pragma unroll
        for (int o = 2; o <= 16; o <<= 1) { s0 += __shfl_xor_sync(0xffffffffu, s0, o); s1 += __shfl_xor_sync(0xffffffffu, s1, o); }
        if (lane < 2) *reinterpret_cast<float2*>(smem + OFF_L + warp * 16 + lane * 8) = make_float2(s0, s1);
        mbar_wait(bar_ready, 0);
        cbar();
        if (warp == 0) {
            const uint32_t other = __shfl_sync(0xffffffffu, M2, lane >> 1);
            float l = 0.f;
#pragma unroll
            for (int ww = 0; ww < 8; ww++) l += *reinterpret_cast<const float*>(smem + OFF_L + ww * 16 + (lane & 3) * 4);
            const float m = (lane & 1) ? bf_hi(other) : bf_lo(other);
            if (lane < 4) st_rel64(&g_ml[(pair * 4 + lane) * 4 + split], __float_as_uint(m), __float_as_uint(l));
        }
        uint32_t pb[8][2];
        {
            uint32_t t4[4];
#pragma unroll
            for (int u = 0; u < 4; u++) {
                ldsm4(t4, poff + u * 64);
                pb[2 * u][0] = t4[0]; pb[2 * u][1] = t4[1]; pb[2 * u + 1][0] = t4[2]; pb[2 * u + 1][1] = t4[3];
            }
        }
        float o2[2][4] = {};
        {
            mbar_wait(bar_full + 8 * slot, ph);
            const uint32_t vb = sbase + slot * SLOT + voff;
            uint32_t a[8][4];
#pragma unroll
            for (int ks = 0; ks < 8; ks++) ldsm4t(a[ks], vb + ks * 2048);
#pragma unroll
            for (int ks = 0; ks < 8; ks++) mma16816((ks & 2) ? o2[ks & 1] : oacc[ks & 1], a[ks], pb[ks][0], pb[ks][1]);
        }
        const float v0 = kh ? (oacc[0][2] + oacc[1][2]) + (o2[0][2] + o2[1][2]) : (oacc[0][0] + oacc[1][0]) + (o2[0][0] + o2[1][0]);
        const float v1 = kh ? (oacc[0][3] + oacc[1][3]) + (o2[0][3] + o2[1][3]) : (oacc[0][1] + oacc[1][1]) + (o2[0][1] + o2[1][1]);
        st_rel32(p_partO, __float_as_uint(v0));
        st_rel32(p_partO + 512, __float_as_uint(v1));
    }

    float hres = 0.f;
    uint32_t df[4][4];
    if (warp < 4) {
        {
            const int ph_idx = (warp * 8 + (head >> 2)) * 4 + (head & 3);
            const float* po = &g_partO[ph_idx * 512 + lane * 4];
            const float* pm = reinterpret_cast<const float*>(&g_ml[ph_idx * 4]);
            uint4 o0, o1, o2, o3, ma, mb;
            Spin sp;
            while (true) {
                o0 = ld_poll4(po); o1 = ld_poll4(po + 128); o2 = ld_poll4(po + 256); o3 = ld_poll4(po + 384);
                ma = ld_poll4(pm); mb = ld_poll4(pm + 4);
                const uint32_t mxv = max(max(max(umax4(o0), umax4(o1)), max(umax4(o2), umax4(o3))), max(umax4(ma), umax4(mb)));
                if (__all_sync(0xffffffffu, mxv != SENT)) break;
                sp.tick();
            }
            const float m0 = __uint_as_float(ma.x), m1 = __uint_as_float(ma.z), m2 = __uint_as_float(mb.x), m3 = __uint_as_float(mb.z);
            const float M = fmaxf(fmaxf(m0, m1), fmaxf(m2, m3));
            float w0 = ex2((m0 - M) * LOG2E), w1 = ex2((m1 - M) * LOG2E), w2 = ex2((m2 - M) * LOG2E), w3 = ex2((m3 - M) * LOG2E);
            const float L = w0 * __uint_as_float(ma.y) + w1 * __uint_as_float(ma.w) + w2 * __uint_as_float(mb.y) + w3 * __uint_as_float(mb.w);
            const float inv = __fdividef(1.0f, L);
            const float e0 = (w0 * __uint_as_float(o0.x) + w1 * __uint_as_float(o1.x) + w2 * __uint_as_float(o2.x) + w3 * __uint_as_float(o3.x)) * inv;
            const float e1 = (w0 * __uint_as_float(o0.y) + w1 * __uint_as_float(o1.y) + w2 * __uint_as_float(o2.y) + w3 * __uint_as_float(o3.y)) * inv;
            const float e2 = (w0 * __uint_as_float(o0.z) + w1 * __uint_as_float(o1.z) + w2 * __uint_as_float(o2.z) + w3 * __uint_as_float(o3.z)) * inv;
            const float e3 = (w0 * __uint_as_float(o0.w) + w1 * __uint_as_float(o1.w) + w2 * __uint_as_float(o2.w) + w3 * __uint_as_float(o3.w)) * inv;
            *reinterpret_cast<uint2*>(smem + OFF_QS + warp * QS_PITCH + lane * 8) = make_uint2(pack_bf16(e0, e1), pack_bf16(e2, e3));
            bar_arrive(2, 256);
        }
        {
            const float* src = &g_ypart[(cta * 32 + 8 * warp + (lane >> 2)) * 16 + (lane & 3) * 4];
            uint16_t* p_h = &g_h[(cta >> 5) * 512 + (cta & 31) * 16 + (lane >> 1)];
            pin(p_h);
            uint4 y;
            Spin sp;
            while (true) {
                y = ld_poll4(src);
                if (__all_sync(0xffffffffu, umax4(y) != SENT)) break;
                sp.tick();
            }
            const bool up = lane & 16, up2 = lane & 8;
            const float a0 = __uint_as_float(y.x), a1 = __uint_as_float(y.y), a2 = __uint_as_float(y.z), a3 = __uint_as_float(y.w);
            const float v0 = (up ? a2 : a0) + __shfl_xor_sync(0xffffffffu, up ? a0 : a2, 16);
            const float v1 = (up ? a3 : a1) + __shfl_xor_sync(0xffffffffu, up ? a1 : a3, 16);
            float v = (up2 ? v1 : v0) + __shfl_xor_sync(0xffffffffu, up2 ? v0 : v1, 8);
            v += __shfl_xor_sync(0xffffffffu, v, 4);
            float* rc = reinterpret_cast<float*>(smem + OFF_RED2);
            if (!(lane & 4)) rc[warp * 16 + 4 * (lane & 3) + (up ? 2 : 0) + (up2 ? 1 : 0)] = v;
            bar_sync(7, 128);
            if (warp == 0) {
                const float* r2 = rc + (lane & 1) * 32 + (lane >> 1);
                float t = r2[0] + r2[16];
                t += __shfl_xor_sync(0xffffffffu, t, 1);
                hres = bf16r(xres + bf16r(t));
                if (!(lane & 1)) st_rel16(p_h, (uint16_t)(__float_as_uint(hres) >> 16));
            }
        }
        {
            const uint4* hr = reinterpret_cast<const uint4*>(g_h + warp * 512);
            uint4 a, b;
            Spin sp;
            while (true) {
                a = ld_poll4(hr + lane); b = ld_poll4(hr + 32 + lane);
                if (__all_sync(0xffffffffu, valid8h(a) & valid8h(b))) break;
                sp.tick();
            }
            if (cta < NFFN) {
                unsigned char* row = smem + OFF_XN + warp * XN_PITCH;
                *reinterpret_cast<uint4*>(row + lane * 16) = a;
                *reinterpret_cast<uint4*>(row + 512 + lane * 16) = b;
                bar_arrive(3, 256);
                float v[16];
                const float2 st = ln_stats(a, b, v);
                if (lane == 0) *reinterpret_cast<float2*>(smem + OFF_ST + warp * 8) = st;
                bar_arrive(4, 256);
                mbar_wait(bar_w + 32, 0); mbar_wait(bar_w + 40, 0);
                const uint32_t wb = sbase + SLOT_WD * SLOT + warp * 2048 + ((lane & 7) + (lane >> 4) * 8) * 128;
#pragma unroll
                for (int i = 0; i < 4; i++) ldsm4t(df[i], wb + (((2 * i + ((lane >> 3) & 1)) ^ (lane & 7)) << 4));
            }
        }
    } else {
        const int m = warp - 4;
        {
            uint32_t af[2][8][4];
            float* p_y = &g_ypart[(((2 * hp) * 32 + (cta & 3) * 8 + 2 * m) * 32 + head) * 16 + r8 + 8 * kh];
            pin(p_y);
            mbar_wait(bar_full + 8 * (SEQ_WO % NSLOT), (SEQ_WO / NSLOT) & 1);
#pragma unroll
            for (int i = 0; i < 2; i++) {
                const int j = 2 * m + i;
                const uint32_t wb = sbase + (SEQ_WO % NSLOT) * SLOT + (j >> 2) * 16384 + ((lane & 7) + (lane >> 4) * 8) * 128 +
                                    ((((2 * j + ((lane >> 3) & 1)) & 7) ^ (lane & 7)) << 4);
#pragma unroll
                for (int ks = 0; ks < 8; ks++) ldsm4t(af[i][ks], wb + ks * 2048);
            }
            bar_sync(2, 256);
            float acc[2][2][4] = {};
            uint32_t t4[4][4];
#pragma unroll
            for (int u = 0; u < 4; u++) ldsm4(t4[u], sbase + OFF_QS + (lane & 3) * QS_PITCH + (4 * u + (lane >> 3)) * 16);
#pragma unroll
            for (int u = 0; u < 4; u++) {
#pragma unroll
                for (int i = 0; i < 2; i++) {
                    mma16816(acc[i][0], af[i][2 * u], t4[u][0], t4[u][1]);
                    mma16816(acc[i][1], af[i][2 * u + 1], t4[u][2], t4[u][3]);
                }
            }
#pragma unroll
            for (int i = 0; i < 2; i++) {
                const float v0 = kh ? acc[i][0][2] + acc[i][1][2] : acc[i][0][0] + acc[i][1][0];
                const float v1 = kh ? acc[i][0][3] + acc[i][1][3] : acc[i][0][1] + acc[i][1][1];
                st_rel32(p_y + i * 32 * 16, __float_as_uint(v0));
                st_rel32(p_y + i * 32 * 16 + 32 * 32 * 16, __float_as_uint(v1));
            }
        }
        if (cta < NFFN) {
            uint32_t gf[8][2][4];
            mbar_wait(bar_w, 0); mbar_wait(bar_w + 8, 0); mbar_wait(bar_w + 16, 0); mbar_wait(bar_w + 24, 0);
#pragma unroll
            for (int ks = 0; ks < 8; ks++) {
                const int k = 128 * m + 16 * ks + (lane & 7) + (lane >> 4) * 8;
                const uint32_t a = sbase + SLOT_WGU * SLOT + k * 32 + ((((lane >> 3) & 1) ^ ((k >> 2) & 1)) << 4);
                ldsm4t(gf[ks][0], a);
                ldsm4t(gf[ks][1], a + 16384);
            }
            float sg = 0.f, su = 0.f;
            {
                float cs[2][4] = {};
#pragma unroll
                for (int ks = 0; ks < 8; ks++) { mma16816(cs[0], gf[ks][0], 0x3F803F80u, 0x3F803F80u); mma16816(cs[1], gf[ks][1], 0x3F803F80u, 0x3F803F80u); }
                float* csb = reinterpret_cast<float*>(smem + OFF_CS);
                if (q4 == 0) {
                    csb[(m * 2 + 0) * 16 + r8] = cs[0][0]; csb[(m * 2 + 0) * 16 + r8 + 8] = cs[0][2];
                    csb[(m * 2 + 1) * 16 + r8] = cs[1][0]; csb[(m * 2 + 1) * 16 + r8 + 8] = cs[1][2];
                }
                bar_sync(5, 128);
                const int c = (tid & 63) >> 2;
#pragma unroll
                for (int ww = 0; ww < 4; ww++) { sg += csb[(ww * 2) * 16 + c]; su += csb[(ww * 2 + 1) * 16 + c]; }
            }
            const uint32_t wdb = sbase + SLOT_WD * SLOT + warp * 2048 + ((lane & 7) + (lane >> 4) * 8) * 128;
            const bool have_wd = __all_sync(0xffffffffu, mbar_try(bar_w + 32, 0) && mbar_try(bar_w + 40, 0));
            if (have_wd) {
#pragma unroll
                for (int i = 0; i < 4; i++) ldsm4t(df[i], wdb + (((2 * i + ((lane >> 3) & 1)) ^ (lane & 7)) << 4));
            }
            bar_sync(3, 256);
            float acc[2][2][4] = {};
            uint32_t t4[4][4];
#pragma unroll
            for (int u = 0; u < 4; u++) ldsm4(t4[u], sbase + OFF_XN + (lane & 3) * XN_PITCH + (16 * m + 4 * u + (lane >> 3)) * 16);
#pragma unroll
            for (int u = 0; u < 4; u++) {
#pragma unroll
                for (int i = 0; i < 2; i++) {
                    mma16816(acc[i][0], gf[2 * u][i], t4[u][0], t4[u][1]);
                    mma16816(acc[i][1], gf[2 * u + 1][i], t4[u][2], t4[u][3]);
                }
            }
            float* red = reinterpret_cast<float*>(smem + OFF_RED);
#pragma unroll
            for (int i = 0; i < 2; i++) {
                const float2 v = kh ? make_float2(acc[i][0][2] + acc[i][1][2], acc[i][0][3] + acc[i][1][3])
                                    : make_float2(acc[i][0][0] + acc[i][1][0], acc[i][0][1] + acc[i][1][1]);
                *reinterpret_cast<float2*>(red + ((m * 2 + i) * 16 + r8 + 8 * kh) * 4 + 2 * hp) = v;
            }
            bar_sync(4, 256);
            if (tid < 192) {
                const int c = (tid & 63) >> 2, b = tid & 3;
                const float2 st = *reinterpret_cast<const float2*>(smem + OFF_ST + b * 8);
                float g = 0.f, u = 0.f;
#pragma unroll
                for (int ww = 0; ww < 4; ww++) { g += red[((ww * 2) * 16 + c) * 4 + b]; u += red[((ww * 2 + 1) * 16 + c) * 4 + b]; }
                g = bf16r((g - st.x * sg) * st.y); u = bf16r((u - st.x * su) * st.y);
                const float inner = 0.7978845608028654f * (g + 0.044715f * g * g * g);
                const float th = 1.0f - __fdividef(2.0f, __expf(2.0f * inner) + 1.0f);
                const float ge = bf16r(0.5f * g * (1.0f + th));
                *reinterpret_cast<__nv_bfloat16*>(smem + OFF_ACT + b * 32 + c * 2) = __float2bfloat16_rn(ge * u);
            }
            if (!have_wd) {
                mbar_wait(bar_w + 32, 0); mbar_wait(bar_w + 40, 0);
#pragma unroll
                for (int i = 0; i < 4; i++) ldsm4t(df[i], wdb + (((2 * i + ((lane >> 3) & 1)) ^ (lane & 7)) << 4));
            }
        }
    }
    if (cta < NFFN) {
        bar_sync(6, 256);
        const uint32_t b0 = *reinterpret_cast<const uint32_t*>(smem + OFF_ACT + (r8 & 3) * 32 + q4 * 4);
        const uint32_t b1 = *reinterpret_cast<const uint32_t*>(smem + OFF_ACT + (r8 & 3) * 32 + 16 + q4 * 4);
        float c[4][4] = {};
#pragma unroll
        for (int i = 0; i < 4; i++) mma16816(c[i], df[i], b0, b1);
#pragma unroll
        for (int i = 0; i < 4; i++) {
            st_rel32(p_dpart + i * NFFN * 16, __float_as_uint(kh ? c[i][2] : c[i][0]));
            st_rel32(p_dpart + i * NFFN * 16 + 32 * NFFN * 16, __float_as_uint(kh ? c[i][3] : c[i][1]));
        }
    } else {
        bar_sync(6, 256);
        delay_cycles(DLY_F_IDLE);
    }

    {
        const int quad = tid & 3;
        const bool two = (tid >> 2) + 64 < NFFN;
        uint4 a, b = make_uint4(0, 0, 0, 0);
        Spin sp;
        delay_cycles(DLY_F);
        while (true) {
            a = ld_poll4(p_dsrc);
            if (two) b = ld_poll4(p_dsrc + 64 * 16);
            if (__all_sync(0xffffffffu, max(umax4(a), umax4(b)) != SENT)) break;
            sp.tick();
        }
        float v[4] = {__uint_as_float(a.x) + __uint_as_float(b.x), __uint_as_float(a.y) + __uint_as_float(b.y),
                      __uint_as_float(a.z) + __uint_as_float(b.z), __uint_as_float(a.w) + __uint_as_float(b.w)};
        {
            const bool up = lane & 16;
            const float s0 = up ? v[0] : v[2], s1 = up ? v[1] : v[3];
            const float k0 = up ? v[2] : v[0], k1 = up ? v[3] : v[1];
            v[0] = k0 + __shfl_xor_sync(0xffffffffu, s0, 16);
            v[1] = k1 + __shfl_xor_sync(0xffffffffu, s1, 16);
            const bool up2 = lane & 8;
            const float s = up2 ? v[0] : v[1], k = up2 ? v[1] : v[0];
            v[0] = k + __shfl_xor_sync(0xffffffffu, s, 8);
            v[0] += __shfl_xor_sync(0xffffffffu, v[0], 4);
            if (!(lane & 4)) reinterpret_cast<float*>(smem + OFF_RED2)[warp * 16 + 4 * quad + ((lane & 16) ? 2 : 0) + ((lane & 8) ? 1 : 0)] = v[0];
        }
        cbar();
        if (warp == 0) {
            const float* r2 = reinterpret_cast<const float*>(smem + OFF_RED2) + (lane & 1) * 64 + (lane >> 1);
            float s = (r2[0] + r2[16]) + (r2[32] + r2[48]);
            s += __shfl_xor_sync(0xffffffffu, s, 1);
            if (!(lane & 1)) *p_out = __float2bfloat16_rn(hres + bf16r(s));
            if (cta == 0 && lane == 0) st_rel32(&g_prog, 0u);
        }
    }
}

typedef CUresult (*EncodeFn)(CUtensorMap*, CUtensorMapDataType, cuuint32_t, void*, const cuuint64_t*, const cuuint64_t*,
                             const cuuint32_t*, const cuuint32_t*, CUtensorMapInterleave, CUtensorMapSwizzle,
                             CUtensorMapL2promotion, CUtensorMapFloatOOBfill);

void encode(EncodeFn fn, CUtensorMap* m, const void* base, int rank, const cuuint64_t* dims, const cuuint64_t* strides,
            const cuuint32_t* box, CUtensorMapSwizzle sw, CUtensorMapL2promotion promo) {
    cuuint32_t es[3] = {1, 1, 1};
    fn(m, CU_TENSOR_MAP_DATA_TYPE_BFLOAT16, (cuuint32_t)rank, const_cast<void*>(base), dims, strides, box, es,
       CU_TENSOR_MAP_INTERLEAVE_NONE, sw, promo, CU_TENSOR_MAP_FLOAT_OOB_FILL_NONE);
}

}

extern "C" void kernel_launch(void* const* d_in, const int* in_sizes, int n_in, void* d_out, int out_size) {
    (void)in_sizes; (void)n_in; (void)out_size;
    static EncodeFn enc = nullptr;
    if (!enc) {
        void* fn = nullptr;
        cudaDriverEntryPointQueryResult qr;
        cudaGetDriverEntryPoint("cuTensorMapEncodeTiled", &fn, cudaEnableDefault, &qr);
        enc = (EncodeFn)fn;
        cudaFuncSetAttribute(fused_decode_kernel, cudaFuncAttributeMaxDynamicSharedMemorySize, SMEM_BYTES);
    }
    const void* x = d_in[0];
    Maps maps;
    {
        cuuint64_t dims[3] = {64, 262144, 2}; cuuint64_t str[2] = {256, 128}; cuuint32_t box[3] = {64, 128, 2};
        encode(enc, &maps.m[0], d_in[1], 3, dims, str, box, CU_TENSOR_MAP_SWIZZLE_128B, CU_TENSOR_MAP_L2_PROMOTION_L2_256B);
        encode(enc, &maps.m[1], d_in[2], 3, dims, str, box, CU_TENSOR_MAP_SWIZZLE_128B, CU_TENSOR_MAP_L2_PROMOTION_L2_256B);
    }
    {
        cuuint64_t dims[3] = {4096, 512, 1}; cuuint64_t str[2] = {8192, 8192 * 512}; cuuint32_t box[3] = {64, 256, 1};
        encode(enc, &maps.m[2], d_in[3], 3, dims, str, box, CU_TENSOR_MAP_SWIZZLE_128B, CU_TENSOR_MAP_L2_PROMOTION_L2_128B);
    }
    {
        cuuint64_t dims[3] = {64, 4096, 8}; cuuint64_t str[2] = {1024, 128}; cuuint32_t box[3] = {64, 128, 2};
        encode(enc, &maps.m[3], d_in[4], 3, dims, str, box, CU_TENSOR_MAP_SWIZZLE_128B, CU_TENSOR_MAP_L2_PROMOTION_L2_256B);
    }
    {
        cuuint64_t dims[3] = {1792, 512, 1}; cuuint64_t str[2] = {3584, 3584 * 512}; cuuint32_t box[3] = {16, 256, 1};
        encode(enc, &maps.m[4], d_in[6], 3, dims, str, box, CU_TENSOR_MAP_SWIZZLE_32B, CU_TENSOR_MAP_L2_PROMOTION_L2_128B);
        encode(enc, &maps.m[5], d_in[7], 3, dims, str, box, CU_TENSOR_MAP_SWIZZLE_32B, CU_TENSOR_MAP_L2_PROMOTION_L2_128B);
    }
    {
        cuuint64_t dims[3] = {64, 1792, 8}; cuuint64_t str[2] = {1024, 128}; cuuint32_t box[3] = {64, 16, 4};
        encode(enc, &maps.m[6], d_in[8], 3, dims, str, box, CU_TENSOR_MAP_SWIZZLE_128B, CU_TENSOR_MAP_L2_PROMOTION_L2_256B);
    }
    fused_decode_kernel<<<NCTA, NTHREADS, SMEM_BYTES, cudaStreamPerThread>>>(maps, (const __nv_bfloat16*)x, (__nv_bfloat16*)d_out);
}
```

```cpp
#include <cuda_runtime.h>
#include <cuda_bf16.h>
#include <cuda.h>
#include <stdint.h>

namespace {

constexpr int NCTA      = 128;
constexpr int NTHREADS  = 320;
constexpr int SLOT      = 32768;
constexpr int NSLOT     = 6;
constexpr int NTILE     = 16;
constexpr int NFFN      = 112;
constexpr int DEPTH_LO  = 2;
#define DHI 3
constexpr int DEPTH_HI  = DHI;
#define THR8 8
constexpr int LEAD_THR8 = THR8;
#define WOM 112
constexpr int WO_MARGIN = WOM;
constexpr int WDEPTH    = 4;
constexpr int SEQ_WO    = 33;
constexpr int NSEQ      = 34;
constexpr int SLOT_WGU  = 4, SLOT_WD = 5;
constexpr int DLY_F     = 500;
constexpr int DLY_F_IDLE = 1100;
constexpr int RESET_TILE = 8;
#define NPRE 1
#define PRE_DLY1 0
#define PRE_DLY2 0
#define SAMPLE_NS 100
constexpr uint32_t SENT = 0xFFFFFFFFu;

constexpr int OFF_XN   = NSLOT * SLOT;
constexpr int XN_PITCH = 1040;
constexpr int OFF_QS   = OFF_XN + 4 * XN_PITCH;
constexpr int QS_PITCH = 272;
constexpr int OFF_P    = OFF_QS + 4 * QS_PITCH;
constexpr int OFF_RED  = OFF_P + 4 * QS_PITCH;
constexpr int OFF_MX   = OFF_RED + 4096;
constexpr int OFF_L    = OFF_MX + 64;
constexpr int OFF_ACT  = OFF_L + 128;
constexpr int OFF_RED2 = OFF_ACT + 128;
constexpr int OFF_CS   = OFF_RED2 + 512;
constexpr int OFF_ST   = OFF_CS + 512;
constexpr int OFF_BAR  = OFF_ST + 32;
constexpr int OFF_VAR  = OFF_BAR + 192;
constexpr int SMEM_USED = OFF_VAR + 64;
constexpr int SMEM_BYTES = SMEM_USED + 1024;
static_assert(OFF_RED % 16 == 0 && OFF_MX % 16 == 0 && OFF_ST % 8 == 0 && OFF_BAR % 8 == 0, "alignment");

__device__ uint2    g_q[4 * 2048];
__device__ float    g_partO[32 * 4 * 4 * 128];
__device__ float2   g_ml[32 * 4 * 4];
__device__ float    g_ypart[4 * 32 * 32 * 16];
__device__ uint16_t g_h[4 * 512];
__device__ float    g_dpart[4 * 32 * NFFN * 16];
__device__ unsigned g_cnt0, g_cnt1, g_prog;

__device__ __forceinline__ uint32_t smem_u32(const void* p) { return (uint32_t)__cvta_generic_to_shared(p); }
__device__ __forceinline__ void mbar_init(uint32_t bar, uint32_t cnt) {
    asm volatile("mbarrier.init.shared::cta.b64 [%0], %1;" ::"r"(bar), "r"(cnt) : "memory");
}
__device__ __forceinline__ void mbar_expect_tx(uint32_t bar, uint32_t bytes) {
    asm volatile("mbarrier.arrive.expect_tx.shared::cta.b64 _, [%0], %1;" ::"r"(bar), "r"(bytes) : "memory");
}
__device__ __forceinline__ void mbar_arrive(uint32_t bar) {
    asm volatile("mbarrier.arrive.shared::cta.b64 _, [%0];" ::"r"(bar) : "memory");
}
__device__ __forceinline__ bool mbar_try(uint32_t bar, uint32_t parity) {
    uint32_t ok;
    asm volatile("{\n.reg .pred p;\nmbarrier.try_wait.parity.shared::cta.b64 p, [%1], %2;\nselp.u32 %0, 1, 0, p;\n}"
                 : "=r"(ok) : "r"(bar), "r"(parity) : "memory");
    return ok != 0;
}
constexpr uint32_t SPIN_LIMIT = 1u << 22;
__device__ __forceinline__ void mbar_wait(uint32_t bar, uint32_t parity) {
    uint32_t it = 0;
    while (!mbar_try(bar, parity)) { if (++it > SPIN_LIMIT) __trap(); }
}
__device__ __forceinline__ void tma3d(uint32_t dst, const CUtensorMap* m, int c0, int c1, int c2, uint32_t bar, uint64_t pol) {
    asm volatile("cp.async.bulk.tensor.3d.shared::cluster.global.mbarrier::complete_tx::bytes.L2::cache_hint [%0], [%1, {%3, %4, %5}], [%2], %6;"
                 ::"r"(dst), "l"(m), "r"(bar), "r"(c0), "r"(c1), "r"(c2), "l"(pol) : "memory");
}
__device__ __forceinline__ void ldsm4(uint32_t (&r)[4], uint32_t addr) {
    asm volatile("ldmatrix.sync.aligned.m8n8.x4.shared.b16 {%0,%1,%2,%3}, [%4];"
                 : "=r"(r[0]), "=r"(r[1]), "=r"(r[2]), "=r"(r[3]) : "r"(addr) : "memory");
}
__device__ __forceinline__ void ldsm4t(uint32_t (&r)[4], uint32_t addr) {
    asm volatile("ldmatrix.sync.aligned.m8n8.x4.trans.shared.b16 {%0,%1,%2,%3}, [%4];"
                 : "=r"(r[0]), "=r"(r[1]), "=r"(r[2]), "=r"(r[3]) : "r"(addr) : "memory");
}
__device__ __forceinline__ void mma16816(float (&c)[4], const uint32_t (&a)[4], uint32_t b0, uint32_t b1) {
    asm volatile("mma.sync.aligned.m16n8k16.row.col.f32.bf16.bf16.f32 {%0,%1,%2,%3}, {%4,%5,%6,%7}, {%8,%9}, {%0,%1,%2,%3};"
                 : "+f"(c[0]), "+f"(c[1]), "+f"(c[2]), "+f"(c[3])
                 : "r"(a[0]), "r"(a[1]), "r"(a[2]), "r"(a[3]), "r"(b0), "r"(b1));
}
__device__ __forceinline__ void cbar() { asm volatile("bar.sync 1, 256;" ::: "memory"); }
__device__ __forceinline__ void bar_sync(int id, int n) { asm volatile("bar.sync %0, %1;" ::"r"(id), "r"(n) : "memory"); }
__device__ __forceinline__ void bar_arrive(int id, int n) { asm volatile("bar.arrive %0, %1;" ::"r"(id), "r"(n) : "memory"); }
__device__ __forceinline__ uint4 ld_poll4(const void* p) {
    uint4 v;
    asm volatile("ld.relaxed.gpu.global.v4.u32 {%0,%1,%2,%3}, [%4];" : "=r"(v.x), "=r"(v.y), "=r"(v.z), "=r"(v.w) : "l"(p) : "memory");
    return v;
}
__device__ __forceinline__ uint2 ld_poll2(const void* p) {
    uint2 v;
    asm volatile("ld.relaxed.gpu.global.v2.u32 {%0,%1}, [%2];" : "=r"(v.x), "=r"(v.y) : "l"(p) : "memory");
    return v;
}
__device__ __forceinline__ void st_rel32(void* p, uint32_t v) { asm volatile("st.relaxed.gpu.global.u32 [%0], %1;" ::"l"(p), "r"(v) : "memory"); }
__device__ __forceinline__ void st_rel16(void* p, uint16_t v) { asm volatile("st.relaxed.gpu.global.u16 [%0], %1;" ::"l"(p), "h"(v) : "memory"); }
__device__ __forceinline__ void st_rel64(void* p, uint32_t a, uint32_t b) { asm volatile("st.relaxed.gpu.global.v2.u32 [%0], {%1,%2};" ::"l"(p), "r"(a), "r"(b) : "memory"); }
__device__ __forceinline__ void st_rel128(void* p, uint32_t v) { asm volatile("st.relaxed.gpu.global.v4.u32 [%0], {%1,%1,%1,%1};" ::"l"(p), "r"(v) : "memory"); }
__device__ __forceinline__ uint32_t umax4(const uint4& v) { return max(max(v.x, v.y), max(v.z, v.w)); }
template <class T> __device__ __forceinline__ void pin(T*& p) { asm volatile("" : "+l"(p)); }
__device__ __forceinline__ bool valid8h(const uint4& v) {
    return (__vcmpeq2(v.x, SENT) | __vcmpeq2(v.y, SENT) | __vcmpeq2(v.z, SENT) | __vcmpeq2(v.w, SENT)) == 0;
}
struct Spin {
    uint32_t it = 0;
    __device__ __forceinline__ void tick() { if (++it > SPIN_LIMIT) __trap(); }
};
__device__ __forceinline__ void wait_progress(int n) {
    Spin sp; unsigned v;
    while (true) {
        asm volatile("ld.relaxed.gpu.global.u32 %0, [%1];" : "=r"(v) : "l"(&g_prog) : "memory");
        if ((int)v >= n) break;
        sp.tick(); __nanosleep(64);
    }
}
__device__ __forceinline__ uint32_t pack_bf16(float lo, float hi) {
    uint32_t r; asm("cvt.rn.bf16x2.f32 %0, %1, %2;" : "=r"(r) : "f"(hi), "f"(lo)); return r;
}
__device__ __forceinline__ void delay_cycles(int n) { if (n > 0) { const long long t0 = clock64(); while (clock64() - t0 < n) {} } }
__device__ __forceinline__ float bf16r(float x) { return __uint_as_float(pack_bf16(0.f, x) & 0xFFFF0000u); }
__device__ __forceinline__ float bf_lo(uint32_t v) { return __uint_as_float(v << 16); }
__device__ __forceinline__ float bf_hi(uint32_t v) { return __uint_as_float(v & 0xFFFF0000u); }
__device__ __forceinline__ uint32_t hmax2(uint32_t a, uint32_t b) {
    uint32_t r; asm("max.bf16x2 %0, %1, %2;" : "=r"(r) : "r"(a), "r"(b)); return r;
}
__device__ __forceinline__ float ex2(float x) { float r; asm("ex2.approx.ftz.f32 %0, %1;" : "=f"(r) : "f"(x)); return r; }

__device__ __forceinline__ float2 ln_stats(const uint4& a, const uint4& b, float (&v)[16]) {
    v[0] = bf_lo(a.x); v[1] = bf_hi(a.x); v[2] = bf_lo(a.y); v[3] = bf_hi(a.y);
    v[4] = bf_lo(a.z); v[5] = bf_hi(a.z); v[6] = bf_lo(a.w); v[7] = bf_hi(a.w);
    v[8] = bf_lo(b.x); v[9] = bf_hi(b.x); v[10] = bf_lo(b.y); v[11] = bf_hi(b.y);
    v[12] = bf_lo(b.z); v[13] = bf_hi(b.z); v[14] = bf_lo(b.w); v[15] = bf_hi(b.w);
    const float shift = __shfl_sync(0xffffffffu, v[0], 0);
    float s0 = 0.f, s1 = 0.f, s2 = 0.f, s3 = 0.f, q0 = 0.f, q1 = 0.f, q2 = 0.f, q3 = 0.f;
#pragma unroll
    for (int i = 0; i < 16; i += 4) {
        const float d0 = v[i] - shift, d1 = v[i + 1] - shift, d2 = v[i + 2] - shift, d3 = v[i + 3] - shift;
        s0 += d0; s1 += d1; s2 += d2; s3 += d3;
        q0 = fmaf(d0, d0, q0); q1 = fmaf(d1, d1, q1); q2 = fmaf(d2, d2, q2); q3 = fmaf(d3, d3, q3);
    }
    float s = (s0 + s1) + (s2 + s3), ss = (q0 + q1) + (q2 + q3);
#pragma unroll
    for (int o = 16; o > 0; o >>= 1) { s += __shfl_xor_sync(0xffffffffu, s, o); ss += __shfl_xor_sync(0xffffffffu, ss, o); }
    const float md = s * (1.0f / 512.0f);
    const float var = fmaxf(ss * (1.0f / 512.0f) - md * md, 0.f);
    const float m = bf16r(shift + md);
    float sq; asm("sqrt.approx.f32 %0, %1;" : "=f"(sq) : "f"(bf16r(bf16r(var) + 1e-5f)));
    const float sd = bf16r(sq);
    return make_float2(m, __fdividef(1.0f, sd));
}

struct Maps { CUtensorMap m[7]; };

__global__ void __launch_bounds__(NTHREADS, 1)
fused_decode_kernel(const __grid_constant__ Maps maps, const __nv_bfloat16* __restrict__ x, __nv_bfloat16* __restrict__ out)
{
    extern __shared__ __align__(1024) unsigned char smem_raw[];
    unsigned char* smem = smem_raw + ((1024u - (smem_u32(smem_raw) & 1023u)) & 1023u);
    const uint32_t sbase = smem_u32(smem);
    const uint32_t bar_full = sbase + OFF_BAR, bar_empty = sbase + OFF_BAR + 48, bar_ready = sbase + OFF_BAR + 96, bar_w = sbase + OFF_BAR + 104;
    volatile unsigned* vars = reinterpret_cast<volatile unsigned*>(smem + OFF_VAR);
    const int tid = threadIdx.x, warp = tid >> 5, lane = tid & 31;
    const int cta = blockIdx.x;

    uint4 xa = make_uint4(0, 0, 0, 0), xb = xa;
    float xres = 0.f;
    unsigned cnt0 = 0;
    if (warp < 4) {
        const uint4* xr = reinterpret_cast<const uint4*>(x + warp * 512);
        xa = __ldg(xr + lane); xb = __ldg(xr + 32 + lane);
        if (warp == 0) xres = __bfloat162float(x[(cta >> 5) * 512 + (cta & 31) * 16 + (lane >> 1)]);
        if (tid == 0) cnt0 = atomicAdd(&g_cnt0, 1u);
    } else if (warp == 7) {
        st_rel128(&g_q[(lane >> 3) * 2048 + cta * 16 + (lane & 7) * 2], 0u);
    }
    uint64_t pol;
    asm volatile("createpolicy.fractional.L2::evict_first.b64 %0, 1.0;" : "=l"(pol));
    if (__builtin_expect(tid == 256, 1)) {
        for (int i = 0; i < NSLOT; i++) { mbar_init(bar_full + 8 * i, 1); mbar_init(bar_empty + 8 * i, 8); }
        asm volatile("fence.mbarrier_init.release.cluster;" ::: "memory");
        mbar_expect_tx(bar_full, 32768);
        tma3d(sbase, &maps.m[2], cta * 32, 0, 0, bar_full, pol);
        tma3d(sbase + 16384, &maps.m[2], cta * 32, 256, 0, bar_full, pol);
        delay_cycles(PRE_DLY1);
        mbar_expect_tx(bar_full + 8, 32768);
        tma3d(sbase + SLOT, &maps.m[0], 0, cta * (NTILE * 128), 0, bar_full + 8, pol);
        if (NPRE > 0) asm volatile("red.relaxed.gpu.global.add.u32 [%0], %1;" ::"l"(&g_prog), "r"(NPRE) : "memory");
        mbar_init(bar_ready, 1);
        for (int i = 0; i < 6; i++) mbar_init(bar_w + 8 * i, 1);
        vars[1] = 0; vars[2] = 0; vars[3] = 0;
        asm volatile("fence.mbarrier_init.release.cluster;" ::: "memory");
    } else if (tid > 256 && tid <= 263) {
        asm volatile("prefetch.tensormap [%0];" ::"l"(&maps.m[tid - 257]) : "memory");
    }
    if (warp == 8) { __syncwarp(); bar_arrive(8, NTHREADS); } else bar_sync(8, NTHREADS);

    if (warp == 8) {
        if (lane == 0) {
            const int key0 = cta * (NTILE * 128);
            int arrived = 0;
            int nkv = NPRE;
            for (int i = 1 + NPRE; i < NSEQ; i++) {
                const int slot = i % NSLOT;
                const bool is_w = (i == SEQ_WO);
                if (i >= NSLOT) mbar_wait(bar_empty + 8 * slot, ((i / NSLOT) - 1) & 1);
                const int grel = (int)vars[2];
                const int lead8 = (nkv * NCTA - grel) / (NCTA / 8);
                const int d = (lead8 > LEAD_THR8) ? DEPTH_LO : DEPTH_HI;
                while (arrived < i - d + 1) { mbar_wait(bar_full + 8 * (arrived % NSLOT), (arrived / NSLOT) & 1); arrived++; }
                if (i == SEQ_WO && grel < NCTA * 32 - WO_MARGIN) wait_progress(NCTA * 32 - WO_MARGIN);
                const uint32_t dst = sbase + slot * SLOT, fb = bar_full + 8 * slot;
                mbar_expect_tx(fb, 32768);
                if (is_w) tma3d(dst, &maps.m[3], 0, (cta >> 2) * 128, (cta & 3) * 2, fb, pol);
                else      tma3d(dst, &maps.m[nkv & 1], 0, key0 + (nkv >> 1) * 128, 0, fb, pol);
                if (!is_w) {
                    asm volatile("red.relaxed.gpu.global.add.u32 [%0], 1;" ::"l"(&g_prog) : "memory");
                    nkv++;
                }
            }
            vars[3] = 1;
            if (cta < NFFN) {
                mbar_wait(bar_empty + 8 * SLOT_WGU, (34 / NSLOT - 1) & 1);
                mbar_wait(bar_empty + 8 * SLOT_WD, (35 / NSLOT - 1) & 1);
                wait_progress(NCTA * 32);
                mbar_wait(bar_full + 8 * (SEQ_WO % NSLOT), (SEQ_WO / NSLOT) & 1);
                for (int k = 0; k < 6; k++) {
                    if (k >= WDEPTH) mbar_wait(bar_w + 8 * (k - WDEPTH), 0);
                    mbar_expect_tx(bar_w + 8 * k, 8192);
                    const int mi = (k < 4) ? 4 + (k >> 1) : 6;
                    const int c0 = (k < 4) ? cta * 16 : 0, c1 = (k < 4) ? (k & 1) * 256 : cta * 16, c2 = (k < 4) ? 0 : (k - 4) * 4;
                    tma3d(sbase + SLOT_WGU * SLOT + k * 8192, &maps.m[mi], c0, c1, c2, bar_w + 8 * k, pol);
                }
            }
        }
        return;
    }

    const int pair = cta >> 2, split = cta & 3;

    if (warp == 9) {
        Spin sp;
        auto sample = [&]() {
            unsigned v;
            asm volatile("ld.relaxed.gpu.global.u32 %0, [%1];" : "=r"(v) : "l"(&g_prog) : "memory");
            if (lane == 0) vars[2] = v;
        };
        while (vars[1] < RESET_TILE) { sp.tick(); sample(); __nanosleep(SAMPLE_NS); }
        const unsigned epoch = vars[0];
#pragma unroll 1
        for (int u = lane; u < 128; u += 32) {
            st_rel128(&g_partO[((pair * 4 + (u >> 5)) * 4 + split) * 128 + (u & 31) * 4], SENT);
            const int seg = u >> 2;
            st_rel128(&g_ypart[(((seg >> 3) * 32 + (cta & 3) * 8 + (seg & 7)) * 32 + (cta >> 2)) * 16 + (u & 3) * 4], SENT);
        }
        if (lane < 4) st_rel64(&g_ml[(pair * 4 + lane) * 4 + split], SENT, SENT);
        if (lane < 2) st_rel128(&g_h[(cta >> 5) * 512 + (cta & 31) * 16 + lane * 8], SENT);
        if (cta < NFFN) {
#pragma unroll 1
            for (int e = lane; e < 512; e += 32) st_rel128(&g_dpart[((e >> 2) * NFFN + cta) * 16 + (e & 3) * 4], SENT);
        }
        __threadfence();
        __syncwarp();
        if (lane == 0) {
            atomicAdd(&g_cnt1, 1u);
            unsigned v; Spin sp2;
            while (true) {
                asm volatile("ld.acquire.gpu.global.u32 %0, [%1];" : "=r"(v) : "l"(&g_cnt1) : "memory");
                if ((int)(v - (epoch + 1) * NCTA) >= 0) break;
                sp2.tick(); sample(); __nanosleep(128);
            }
            mbar_arrive(bar_ready);
        }
        __syncwarp();
        while (vars[3] == 0) { sp.tick(); sample(); __nanosleep(SAMPLE_NS); }
        return;
    }

    const int r8 = lane >> 2, q4 = lane & 3;
    const int hp = q4 & 1, kh = q4 >> 1;
    constexpr float LOG2E = 1.4426950408889634f;
    const int bq = pair >> 3, gq = pair & 7;

    if (tid == 0) vars[0] = cnt0 >> 7;

    if (warp < 4) {
        float v[16];
        const float2 st = ln_stats(xa, xb, v);
        uint32_t o[8];
#pragma unroll
        for (int i = 0; i < 8; i++) o[i] = pack_bf16(bf16r(v[2 * i] - st.x) * st.y, bf16r(v[2 * i + 1] - st.x) * st.y);
        unsigned char* row = smem + OFF_XN + warp * XN_PITCH;
        *reinterpret_cast<uint4*>(row + lane * 16) = make_uint4(o[0], o[1], o[2], o[3]);
        *reinterpret_cast<uint4*>(row + 512 + lane * 16) = make_uint4(o[4], o[5], o[6], o[7]);
    }
    cbar();
    const uint32_t tag = vars[0] + 1;

    {
        uint32_t bfr[4][2];
        {
            uint32_t t4[4];
#pragma unroll
            for (int u = 0; u < 2; u++) {
                ldsm4(t4, sbase + OFF_XN + (lane & 3) * XN_PITCH + (8 * warp + 4 * u + (lane >> 3)) * 16);
                bfr[2 * u][0] = t4[0]; bfr[2 * u][1] = t4[1]; bfr[2 * u + 1][0] = t4[2]; bfr[2 * u + 1][1] = t4[3];
            }
        }
        mbar_wait(bar_full + 0, 0);
        float acc[2][4] = {};
#pragma unroll
        for (int ks = 0; ks < 4; ks++) {
            const int k = 64 * warp + 16 * ks + (lane & 7) + (lane >> 4) * 8;
#pragma unroll
            for (int mt = 0; mt < 2; mt++) {
                uint32_t a[4];
                const int chunk = 2 * mt + ((lane >> 3) & 1);
                ldsm4t(a, sbase + k * 64 + ((chunk ^ ((k >> 1) & 3)) << 4));
                mma16816(acc[mt], a, bfr[ks][0], bfr[ks][1]);
            }
        }
        __syncwarp();
        if (lane == 0) mbar_arrive(bar_empty + 0);
        float* red = reinterpret_cast<float*>(smem + OFF_RED);
#pragma unroll
        for (int mt = 0; mt < 2; mt++) {
            float2 v = kh ? make_float2(acc[mt][2], acc[mt][3]) : make_float2(acc[mt][0], acc[mt][1]);
            *reinterpret_cast<float2*>(red + ((warp * 2 + mt) * 16 + r8 + 8 * kh) * 4 + 2 * hp) = v;
        }
        cbar();
        if (tid < 64) {
            const int b = tid >> 4, c2 = tid & 15;
            float s0 = 0.f, s1 = 0.f;
            const int c0 = 2 * c2, c1 = 2 * c2 + 1;
#pragma unroll
            for (int ww = 0; ww < 8; ww++) {
                s0 += red[((ww * 2 + (c0 >> 4)) * 16 + (c0 & 15)) * 4 + b];
                s1 += red[((ww * 2 + (c1 >> 4)) * 16 + (c1 & 15)) * 4 + b];
            }
            st_rel64(&g_q[b * 2048 + cta * 16 + c2], pack_bf16(s0, s1), tag);
        }
        {
            const uint2* src = &g_q[bq * 2048 + gq * 256 + tid];
            uint2 v;
            Spin sp;
            while (true) { v = ld_poll2(src); if (__all_sync(0xffffffffu, v.y == tag)) break; sp.tick(); }
            *reinterpret_cast<uint32_t*>(smem + OFF_QS + (tid >> 6) * QS_PITCH + (tid & 63) * 4) = v.x;
        }
        cbar();
    }
    uint32_t qf[8][2];
    {
        uint32_t t4[4];
#pragma unroll
        for (int u = 0; u < 4; u++) {
            ldsm4(t4, sbase + OFF_QS + (lane & 3) * QS_PITCH + (4 * u + (lane >> 3)) * 16);
            qf[2 * u][0] = t4[0]; qf[2 * u][1] = t4[1]; qf[2 * u + 1][0] = t4[2]; qf[2 * u + 1][1] = t4[3];
        }
    }

    const uint32_t voff = (warp >> 2) * 16384 + ((lane & 7) + (lane >> 4) * 8) * 128 +
                          ((((2 * warp + ((lane >> 3) & 1)) & 7) ^ (lane & 7)) << 4);
    const uint32_t poff = sbase + OFF_P + (lane & 3) * QS_PITCH + (lane >> 3) * 16;
    const uint32_t koff = (16 * warp + (lane & 7) + ((lane >> 3) & 1) * 8) * 128;
    const uint32_t kx = lane & 7, kc = lane >> 4;
    constexpr float SCALE = 0.08838834764831845f;
    uint32_t* mxbuf = reinterpret_cast<uint32_t*>(smem + OFF_MX);
    uint32_t M2 = 0xFF80FF80u;
    float l0 = 0.f, l1 = 0.f;
    float oacc[2][4] = {};
    int slot = 1; uint32_t ph = 0;

    for (int t = 0;; t++) {
        mbar_wait(bar_full + 8 * slot, ph);
        float sa[4] = {}, sb[4] = {};
        {
            const uint32_t kb = sbase + slot * SLOT + koff;
#pragma unroll
            for (int ks = 0; ks < 8; ks++) {
                uint32_t a[4];
                ldsm4(a, kb + (ks >> 2) * 16384 + (((2 * (ks & 3) + kc) ^ kx) << 4));
                if (ks & 1) mma16816(sb, a, qf[ks][0], qf[ks][1]); else mma16816(sa, a, qf[ks][0], qf[ks][1]);
            }
        }
        __syncwarp();
        if (lane == 0) mbar_arrive(bar_empty + 8 * slot);
        if (++slot == NSLOT) { slot = 0; ph ^= 1; }

        const float r0 = kh ? sa[2] + sb[2] : sa[0] + sb[0];
        const float r1 = kh ? sa[3] + sb[3] : sa[1] + sb[1];
        uint32_t sp = pack_bf16(r0, r1);
        sp = pack_bf16(bf_lo(sp) * SCALE, bf_hi(sp) * SCALE);
        uint32_t mx = sp;
#pragma unroll
        for (int o = 2; o <= 16; o <<= 1) mx = hmax2(mx, __shfl_xor_sync(0xffffffffu, mx, o));
        if (lane < 2) mxbuf[lane * 8 + warp] = mx;
        if (tid == 0) vars[1] = t + 1;
        cbar();
        {
            const uint4 m0 = *reinterpret_cast<const uint4*>(mxbuf + hp * 8), m1 = *reinterpret_cast<const uint4*>(mxbuf + hp * 8 + 4);
            uint32_t mt = hmax2(hmax2(hmax2(m0.x, m0.y), hmax2(m0.z, m0.w)), hmax2(hmax2(m1.x, m1.y), hmax2(m1.z, m1.w)));
            const uint32_t Mn = hmax2(M2, mt);
            const float a0 = ex2((bf_lo(M2) - bf_lo(Mn)) * LOG2E), a1 = ex2((bf_hi(M2) - bf_hi(Mn)) * LOG2E);
            const float p0 = ex2((bf_lo(sp) - bf_lo(Mn)) * LOG2E), p1 = ex2((bf_hi(sp) - bf_hi(Mn)) * LOG2E);
            M2 = Mn;
            l0 = fmaf(l0, a0, p0); l1 = fmaf(l1, a1, p1);
            const uint32_t pp = pack_bf16(p0, p1);
            unsigned char* pd = smem + OFF_P + (2 * hp) * QS_PITCH + (16 * warp + r8 + 8 * kh) * 2;
            *reinterpret_cast<uint16_t*>(pd) = (uint16_t)(pp & 0xFFFF);
            *reinterpret_cast<uint16_t*>(pd + QS_PITCH) = (uint16_t)(pp >> 16);
#pragma unroll
            for (int c = 0; c < 2; c++) { oacc[c][0] *= a0; oacc[c][1] *= a1; oacc[c][2] *= a0; oacc[c][3] *= a1; }
        }
        if (t == NTILE - 1) break;
        cbar();
        uint32_t pb[8][2];
        {
            uint32_t t4[4];
#pragma unroll
            for (int u = 0; u < 4; u++) {
                ldsm4(t4, poff + u * 64);
                pb[2 * u][0] = t4[0]; pb[2 * u][1] = t4[1]; pb[2 * u + 1][0] = t4[2]; pb[2 * u + 1][1] = t4[3];
            }
        }
        mbar_wait(bar_full + 8 * slot, ph);
        {
            const uint32_t vb = sbase + slot * SLOT + voff;
#pragma unroll
            for (int ks = 0; ks < 8; ks++) {
                uint32_t a[4];
                ldsm4t(a, vb + ks * 2048);
                mma16816(oacc[ks & 1], a, pb[ks][0], pb[ks][1]);
            }
        }
        __syncwarp();
        if (lane == 0) mbar_arrive(bar_empty + 8 * slot);
        if (++slot == NSLOT) { slot = 0; ph ^= 1; }
    }

    const int head = cta >> 2;
    float* p_partO = &g_partO[((pair * 4 + 2 * hp) * 4 + split) * 128 + 16 * warp + r8 + 8 * kh];
    float* p_dpart = &g_dpart[(((2 * hp) * 32 + 4 * warp) * NFFN + cta) * 16 + r8 + 8 * kh];
    const float* p_dsrc = &g_dpart[(cta * NFFN + (tid >> 2)) * 16 + (tid & 3) * 4];
    __nv_bfloat16* p_out = out + (cta >> 5) * 512 + (cta & 31) * 16 + (lane >> 1);
    pin(p_partO); pin(p_dpart); pin(p_dsrc); pin(p_out);

    {
        float s0 = l0, s1 = l1;
#pragma unroll
        for (int o = 2; o <= 16; o <<= 1) { s0 += __shfl_xor_sync(0xffffffffu, s0, o); s1 += __shfl_xor_sync(0xffffffffu, s1, o); }
        if (lane < 2) *reinterpret_cast<float2*>(smem + OFF_L + warp * 16 + lane * 8) = make_float2(s0, s1);
        mbar_wait(bar_ready, 0);
        cbar();
        if (warp == 0) {
            const uint32_t other = __shfl_sync(0xffffffffu, M2, lane >> 1);
            float l = 0.f;
#pragma unroll
            for (int ww = 0; ww < 8; ww++) l += *reinterpret_cast<const float*>(smem + OFF_L + ww * 16 + (lane & 3) * 4);
            const float m = (lane & 1) ? bf_hi(other) : bf_lo(other);
            if (lane < 4) st_rel64(&g_ml[(pair * 4 + lane) * 4 + split], __float_as_uint(m), __float_as_uint(l));
        }
        uint32_t pb[8][2];
        {
            uint32_t t4[4];
#pragma unroll
            for (int u = 0; u < 4; u++) {
                ldsm4(t4, poff + u * 64);
                pb[2 * u][0] = t4[0]; pb[2 * u][1] = t4[1]; pb[2 * u + 1][0] = t4[2]; pb[2 * u + 1][1] = t4[3];
            }
        }
        float o2[2][4] = {};
        {
            mbar_wait(bar_full + 8 * slot, ph);
            const uint32_t vb = sbase + slot * SLOT + voff;
            uint32_t a[8][4];
#pragma unroll
            for (int ks = 0; ks < 8; ks++) ldsm4t(a[ks], vb + ks * 2048);
#pragma unroll
            for (int ks = 0; ks < 8; ks++) mma16816((ks & 2) ? o2[ks & 1] : oacc[ks & 1], a[ks], pb[ks][0], pb[ks][1]);
        }
        const float v0 = kh ? (oacc[0][2] + oacc[1][2]) + (o2[0][2] + o2[1][2]) : (oacc[0][0] + oacc[1][0]) + (o2[0][0] + o2[1][0]);
        const float v1 = kh ? (oacc[0][3] + oacc[1][3]) + (o2[0][3] + o2[1][3]) : (oacc[0][1] + oacc[1][1]) + (o2[0][1] + o2[1][1]);
        st_rel32(p_partO, __float_as_uint(v0));
        st_rel32(p_partO + 512, __float_as_uint(v1));
    }

    float hres = 0.f;
    uint32_t df[4][4];
    if (warp < 4) {
        {
            const int ph_idx = (warp * 8 + (head >> 2)) * 4 + (head & 3);
            const float* po = &g_partO[ph_idx * 512 + lane * 4];
            const float* pm = reinterpret_cast<const float*>(&g_ml[ph_idx * 4]);
            uint4 o0, o1, o2, o3, ma, mb;
            Spin sp;
            while (true) {
                o0 = ld_poll4(po); o1 = ld_poll4(po + 128); o2 = ld_poll4(po + 256); o3 = ld_poll4(po + 384);
                ma = ld_poll4(pm); mb = ld_poll4(pm + 4);
                const uint32_t mxv = max(max(max(umax4(o0), umax4(o1)), max(umax4(o2), umax4(o3))), max(umax4(ma), umax4(mb)));
                if (__all_sync(0xffffffffu, mxv != SENT)) break;
                sp.tick();
            }
            const float m0 = __uint_as_float(ma.x), m1 = __uint_as_float(ma.z), m2 = __uint_as_float(mb.x), m3 = __uint_as_float(mb.z);
            const float M = fmaxf(fmaxf(m0, m1), fmaxf(m2, m3));
            float w0 = ex2((m0 - M) * LOG2E), w1 = ex2((m1 - M) * LOG2E), w2 = ex2((m2 - M) * LOG2E), w3 = ex2((m3 - M) * LOG2E);
            const float L = w0 * __uint_as_float(ma.y) + w1 * __uint_as_float(ma.w) + w2 * __uint_as_float(mb.y) + w3 * __uint_as_float(mb.w);
            const float inv = __fdividef(1.0f, L);
            const float e0 = (w0 * __uint_as_float(o0.x) + w1 * __uint_as_float(o1.x) + w2 * __uint_as_float(o2.x) + w3 * __uint_as_float(o3.x)) * inv;
            const float e1 = (w0 * __uint_as_float(o0.y) + w1 * __uint_as_float(o1.y) + w2 * __uint_as_float(o2.y) + w3 * __uint_as_float(o3.y)) * inv;
            const float e2 = (w0 * __uint_as_float(o0.z) + w1 * __uint_as_float(o1.z) + w2 * __uint_as_float(o2.z) + w3 * __uint_as_float(o3.z)) * inv;
            const float e3 = (w0 * __uint_as_float(o0.w) + w1 * __uint_as_float(o1.w) + w2 * __uint_as_float(o2.w) + w3 * __uint_as_float(o3.w)) * inv;
            *reinterpret_cast<uint2*>(smem + OFF_QS + warp * QS_PITCH + lane * 8) = make_uint2(pack_bf16(e0, e1), pack_bf16(e2, e3));
            bar_arrive(2, 256);
        }
        {
            const float* src = &g_ypart[(cta * 32 + 8 * warp + (lane >> 2)) * 16 + (lane & 3) * 4];
            uint16_t* p_h = &g_h[(cta >> 5) * 512 + (cta & 31) * 16 + (lane >> 1)];
            pin(p_h);
            uint4 y;
            Spin sp;
            while (true) {
                y = ld_poll4(src);
                if (__all_sync(0xffffffffu, umax4(y) != SENT)) break;
                sp.tick();
            }
            const bool up = lane & 16, up2 = lane & 8;
            const float a0 = __uint_as_float(y.x), a1 = __uint_as_float(y.y), a2 = __uint_as_float(y.z), a3 = __uint_as_float(y.w);
            const float v0 = (up ? a2 : a0) + __shfl_xor_sync(0xffffffffu, up ? a0 : a2, 16);
            const float v1 = (up ? a3 : a1) + __shfl_xor_sync(0xffffffffu, up ? a1 : a3, 16);
            float v = (up2 ? v1 : v0) + __shfl_xor_sync(0xffffffffu, up2 ? v0 : v1, 8);
            v += __shfl_xor_sync(0xffffffffu, v, 4);
            float* rc = reinterpret_cast<float*>(smem + OFF_RED2);
            if (!(lane & 4)) rc[warp * 16 + 4 * (lane & 3) + (up ? 2 : 0) + (up2 ? 1 : 0)] = v;
            bar_sync(7, 128);
            if (warp == 0) {
                const float* r2 = rc + (lane & 1) * 32 + (lane >> 1);
                float t = r2[0] + r2[16];
                t += __shfl_xor_sync(0xffffffffu, t, 1);
                hres = bf16r(xres + bf16r(t));
                if (!(lane & 1)) st_rel16(p_h, (uint16_t)(__float_as_uint(hres) >> 16));
            }
        }
        {
            const uint4* hr = reinterpret_cast<const uint4*>(g_h + warp * 512);
            uint4 a, b;
            Spin sp;
            while (true) {
                a = ld_poll4(hr + lane); b = ld_poll4(hr + 32 + lane);
                if (__all_sync(0xffffffffu, valid8h(a) & valid8h(b))) break;
                sp.tick();
            }
            if (cta < NFFN) {
                unsigned char* row = smem + OFF_XN + warp * XN_PITCH;
                *reinterpret_cast<uint4*>(row + lane * 16) = a;
                *reinterpret_cast<uint4*>(row + 512 + lane * 16) = b;
                bar_arrive(3, 256);
                float v[16];
                const float2 st = ln_stats(a, b, v);
                if (lane == 0) *reinterpret_cast<float2*>(smem + OFF_ST + warp * 8) = st;
                bar_arrive(4, 256);
                mbar_wait(bar_w + 32, 0); mbar_wait(bar_w + 40, 0);
                const uint32_t wb = sbase + SLOT_WD * SLOT + warp * 2048 + ((lane & 7) + (lane >> 4) * 8) * 128;
#pragma unroll
                for (int i = 0; i < 4; i++) ldsm4t(df[i], wb + (((2 * i + ((lane >> 3) & 1)) ^ (lane & 7)) << 4));
            }
        }
    } else {
        const int m = warp - 4;
        {
            uint32_t af[2][8][4];
            float* p_y = &g_ypart[(((2 * hp) * 32 + (cta & 3) * 8 + 2 * m) * 32 + head) * 16 + r8 + 8 * kh];
            pin(p_y);
            mbar_wait(bar_full + 8 * (SEQ_WO % NSLOT), (SEQ_WO / NSLOT) & 1);
#pragma unroll
            for (int i = 0; i < 2; i++) {
                const int j = 2 * m + i;
                const uint32_t wb = sbase + (SEQ_WO % NSLOT) * SLOT + (j >> 2) * 16384 + ((lane & 7) + (lane >> 4) * 8) * 128 +
                                    ((((2 * j + ((lane >> 3) & 1)) & 7) ^ (lane & 7)) << 4);
#pragma unroll
                for (int ks = 0; ks < 8; ks++) ldsm4t(af[i][ks], wb + ks * 2048);
            }
            bar_sync(2, 256);
            float acc[2][2][4] = {};
            uint32_t t4[4][4];
#pragma unroll
            for (int u = 0; u < 4; u++) ldsm4(t4[u], sbase + OFF_QS + (lane & 3) * QS_PITCH + (4 * u + (lane >> 3)) * 16);
#pragma unroll
            for (int u = 0; u < 4; u++) {
#pragma unroll
                for (int i = 0; i < 2; i++) {
                    mma16816(acc[i][0], af[i][2 * u], t4[u][0], t4[u][1]);
                    mma16816(acc[i][1], af[i][2 * u + 1], t4[u][2], t4[u][3]);
                }
            }
#pragma unroll
            for (int i = 0; i < 2; i++) {
                const float v0 = kh ? acc[i][0][2] + acc[i][1][2] : acc[i][0][0] + acc[i][1][0];
                const float v1 = kh ? acc[i][0][3] + acc[i][1][3] : acc[i][0][1] + acc[i][1][1];
                st_rel32(p_y + i * 32 * 16, __float_as_uint(v0));
                st_rel32(p_y + i * 32 * 16 + 32 * 32 * 16, __float_as_uint(v1));
            }
        }
        if (cta < NFFN) {
            uint32_t gf[8][2][4];
            mbar_wait(bar_w, 0); mbar_wait(bar_w + 8, 0); mbar_wait(bar_w + 16, 0); mbar_wait(bar_w + 24, 0);
#pragma unroll
            for (int ks = 0; ks < 8; ks++) {
                const int k = 128 * m + 16 * ks + (lane & 7) + (lane >> 4) * 8;
                const uint32_t a = sbase + SLOT_WGU * SLOT + k * 32 + ((((lane >> 3) & 1) ^ ((k >> 2) & 1)) << 4);
                ldsm4t(gf[ks][0], a);
                ldsm4t(gf[ks][1], a + 16384);
            }
            float sg = 0.f, su = 0.f;
            {
                float cs[2][4] = {};
#pragma unroll
                for (int ks = 0; ks < 8; ks++) { mma16816(cs[0], gf[ks][0], 0x3F803F80u, 0x3F803F80u); mma16816(cs[1], gf[ks][1], 0x3F803F80u, 0x3F803F80u); }
                float* csb = reinterpret_cast<float*>(smem + OFF_CS);
                if (q4 == 0) {
                    csb[(m * 2 + 0) * 16 + r8] = cs[0][0]; csb[(m * 2 + 0) * 16 + r8 + 8] = cs[0][2];
                    csb[(m * 2 + 1) * 16 + r8] = cs[1][0]; csb[(m * 2 + 1) * 16 + r8 + 8] = cs[1][2];
                }
                bar_sync(5, 128);
                const int c = (tid & 63) >> 2;
#pragma unroll
                for (int ww = 0; ww < 4; ww++) { sg += csb[(ww * 2) * 16 + c]; su += csb[(ww * 2 + 1) * 16 + c]; }
            }
            const uint32_t wdb = sbase + SLOT_WD * SLOT + warp * 2048 + ((lane & 7) + (lane >> 4) * 8) * 128;
            const bool have_wd = __all_sync(0xffffffffu, mbar_try(bar_w + 32, 0) && mbar_try(bar_w + 40, 0));
            if (have_wd) {
#pragma unroll
                for (int i = 0; i < 4; i++) ldsm4t(df[i], wdb + (((2 * i + ((lane >> 3) & 1)) ^ (lane & 7)) << 4));
            }
            bar_sync(3, 256);
            float acc[2][2][4] = {};
            uint32_t t4[4][4];
#pragma unroll
            for (int u = 0; u < 4; u++) ldsm4(t4[u], sbase + OFF_XN + (lane & 3) * XN_PITCH + (16 * m + 4 * u + (lane >> 3)) * 16);
#pragma unroll
            for (int u = 0; u < 4; u++) {
#pragma unroll
                for (int i = 0; i < 2; i++) {
                    mma16816(acc[i][0], gf[2 * u][i], t4[u][0], t4[u][1]);
                    mma16816(acc[i][1], gf[2 * u + 1][i], t4[u][2], t4[u][3]);
                }
            }
            float* red = reinterpret_cast<float*>(smem + OFF_RED);
#pragma unroll
            for (int i = 0; i < 2; i++) {
                const float2 v = kh ? make_float2(acc[i][0][2] + acc[i][1][2], acc[i][0][3] + acc[i][1][3])
                                    : make_float2(acc[i][0][0] + acc[i][1][0], acc[i][0][1] + acc[i][1][1]);
                *reinterpret_cast<float2*>(red + ((m * 2 + i) * 16 + r8 + 8 * kh) * 4 + 2 * hp) = v;
            }
            bar_sync(4, 256);
            if (tid < 192) {
                const int c = (tid & 63) >> 2, b = tid & 3;
                const float2 st = *reinterpret_cast<const float2*>(smem + OFF_ST + b * 8);
                float g = 0.f, u = 0.f;
#pragma unroll
                for (int ww = 0; ww < 4; ww++) { g += red[((ww * 2) * 16 + c) * 4 + b]; u += red[((ww * 2 + 1) * 16 + c) * 4 + b]; }
                g = bf16r((g - st.x * sg) * st.y); u = bf16r((u - st.x * su) * st.y);
                const float inner = 0.7978845608028654f * (g + 0.044715f * g * g * g);
                const float th = 1.0f - __fdividef(2.0f, __expf(2.0f * inner) + 1.0f);
                const float ge = bf16r(0.5f * g * (1.0f + th));
                *reinterpret_cast<__nv_bfloat16*>(smem + OFF_ACT + b * 32 + c * 2) = __float2bfloat16_rn(ge * u);
            }
            if (!have_wd) {
                mbar_wait(bar_w + 32, 0); mbar_wait(bar_w + 40, 0);
#pragma unroll
                for (int i = 0; i < 4; i++) ldsm4t(df[i], wdb + (((2 * i + ((lane >> 3) & 1)) ^ (lane & 7)) << 4));
            }
        }
    }
    if (cta < NFFN) {
        bar_sync(6, 256);
        const uint32_t b0 = *reinterpret_cast<const uint32_t*>(smem + OFF_ACT + (r8 & 3) * 32 + q4 * 4);
        const uint32_t b1 = *reinterpret_cast<const uint32_t*>(smem + OFF_ACT + (r8 & 3) * 32 + 16 + q4 * 4);
        float c[4][4] = {};
#pragma unroll
        for (int i = 0; i < 4; i++) mma16816(c[i], df[i], b0, b1);
#pragma unroll
        for (int i = 0; i < 4; i++) {
            st_rel32(p_dpart + i * NFFN * 16, __float_as_uint(kh ? c[i][2] : c[i][0]));
            st_rel32(p_dpart + i * NFFN * 16 + 32 * NFFN * 16, __float_as_uint(kh ? c[i][3] : c[i][1]));
        }
    } else {
        bar_sync(6, 256);
        delay_cycles(DLY_F_IDLE);
    }

    {
        const int quad = tid & 3;
        const bool two = (tid >> 2) + 64 < NFFN;
        uint4 a, b = make_uint4(0, 0, 0, 0);
        Spin sp;
        delay_cycles(DLY_F);
        while (true) {
            a = ld_poll4(p_dsrc);
            if (two) b = ld_poll4(p_dsrc + 64 * 16);
            if (__all_sync(0xffffffffu, max(umax4(a), umax4(b)) != SENT)) break;
            sp.tick();
        }
        float v[4] = {__uint_as_float(a.x) + __uint_as_float(b.x), __uint_as_float(a.y) + __uint_as_float(b.y),
                      __uint_as_float(a.z) + __uint_as_float(b.z), __uint_as_float(a.w) + __uint_as_float(b.w)};
        {
            const bool up = lane & 16;
            const float s0 = up ? v[0] : v[2], s1 = up ? v[1] : v[3];
            const float k0 = up ? v[2] : v[0], k1 = up ? v[3] : v[1];
            v[0] = k0 + __shfl_xor_sync(0xffffffffu, s0, 16);
            v[1] = k1 + __shfl_xor_sync(0xffffffffu, s1, 16);
            const bool up2 = lane & 8;
            const float s = up2 ? v[0] : v[1], k = up2 ? v[1] : v[0];
            v[0] = k + __shfl_xor_sync(0xffffffffu, s, 8);
            v[0] += __shfl_xor_sync(0xffffffffu, v[0], 4);
            if (!(lane & 4)) reinterpret_cast<float*>(smem + OFF_RED2)[warp * 16 + 4 * quad + ((lane & 16) ? 2 : 0) + ((lane & 8) ? 1 : 0)] = v[0];
        }
        cbar();
        if (warp == 0) {
            const float* r2 = reinterpret_cast<const float*>(smem + OFF_RED2) + (lane & 1) * 64 + (lane >> 1);
            float s = (r2[0] + r2[16]) + (r2[32] + r2[48]);
            s += __shfl_xor_sync(0xffffffffu, s, 1);
            if (!(lane & 1)) *p_out = __float2bfloat16_rn(hres + bf16r(s));
            if (cta == 0 && lane == 0) st_rel32(&g_prog, 0u);
        }
    }
}

typedef CUresult (*EncodeFn)(CUtensorMap*, CUtensorMapDataType, cuuint32_t, void*, const cuuint64_t*, const cuuint64_t*,
                             const cuuint32_t*, const cuuint32_t*, CUtensorMapInterleave, CUtensorMapSwizzle,
                             CUtensorMapL2promotion, CUtensorMapFloatOOBfill);

void encode(EncodeFn fn, CUtensorMap* m, const void* base, int rank, const cuuint64_t* dims, const cuuint64_t* strides,
            const cuuint32_t* box, CUtensorMapSwizzle sw, CUtensorMapL2promotion promo) {
    cuuint32_t es[3] = {1, 1, 1};
    fn(m, CU_TENSOR_MAP_DATA_TYPE_BFLOAT16, (cuuint32_t)rank, const_cast<void*>(base), dims, strides, box, es,
       CU_TENSOR_MAP_INTERLEAVE_NONE, sw, promo, CU_TENSOR_MAP_FLOAT_OOB_FILL_NONE);
}

}

extern "C" void kernel_launch(void* const* d_in, const int* in_sizes, int n_in, void* d_out, int out_size) {
    (void)in_sizes; (void)n_in; (void)out_size;
    static EncodeFn enc = nullptr;
    if (!enc) {
        void* fn = nullptr;
        cudaDriverEntryPointQueryResult qr;
        cudaGetDriverEntryPoint("cuTensorMapEncodeTiled", &fn, cudaEnableDefault, &qr);
        enc = (EncodeFn)fn;
        cudaFuncSetAttribute(fused_decode_kernel, cudaFuncAttributeMaxDynamicSharedMemorySize, SMEM_BYTES);
    }
    const void* x = d_in[0];
    Maps maps;
    {
        cuuint64_t dims[3] = {64, 262144, 2}; cuuint64_t str[2] = {256, 128}; cuuint32_t box[3] = {64, 128, 2};
        encode(enc, &maps.m[0], d_in[1], 3, dims, str, box, CU_TENSOR_MAP_SWIZZLE_128B, CU_TENSOR_MAP_L2_PROMOTION_L2_256B);
        encode(enc, &maps.m[1], d_in[2], 3, dims, str, box, CU_TENSOR_MAP_SWIZZLE_128B, CU_TENSOR_MAP_L2_PROMOTION_L2_256B);
    }
    {
        cuuint64_t dims[3] = {4096, 512, 1}; cuuint64_t str[2] = {8192, 8192 * 512}; cuuint32_t box[3] = {32, 256, 1};
        encode(enc, &maps.m[2], d_in[3], 3, dims, str, box, CU_TENSOR_MAP_SWIZZLE_64B, CU_TENSOR_MAP_L2_PROMOTION_L2_128B);
    }
    {
        cuuint64_t dims[3] = {64, 4096, 8}; cuuint64_t str[2] = {1024, 128}; cuuint32_t box[3] = {64, 128, 2};
        encode(enc, &maps.m[3], d_in[4], 3, dims, str, box, CU_TENSOR_MAP_SWIZZLE_128B, CU_TENSOR_MAP_L2_PROMOTION_L2_256B);
    }
    {
        cuuint64_t dims[3] = {1792, 512, 1}; cuuint64_t str[2] = {3584, 3584 * 512}; cuuint32_t box[3] = {16, 256, 1};
        encode(enc, &maps.m[4], d_in[6], 3, dims, str, box, CU_TENSOR_MAP_SWIZZLE_32B, CU_TENSOR_MAP_L2_PROMOTION_L2_128B);
        encode(enc, &maps.m[5], d_in[7], 3, dims, str, box, CU_TENSOR_MAP_SWIZZLE_32B, CU_TENSOR_MAP_L2_PROMOTION_L2_128B);
    }
    {
        cuuint64_t dims[3] = {64, 1792, 8}; cuuint64_t str[2] = {1024, 128}; cuuint32_t box[3] = {64, 16, 4};
        encode(enc, &maps.m[6], d_in[8], 3, dims, str, box, CU_TENSOR_MAP_SWIZZLE_128B, CU_TENSOR_MAP_L2_PROMOTION_L2_256B);
    }
    fused_decode_kernel<<<NCTA, NTHREADS, SMEM_BYTES, cudaStreamPerThread>>>(maps, (const __nv_bfloat16*)x, (__nv_bfloat16*)d_out);
}
```

```cpp
#include <cuda_runtime.h>
#include <cuda_bf16.h>
#include <cuda.h>
#include <stdint.h>

namespace {

constexpr int NCTA      = 128;
constexpr int NTHREADS  = 320;
constexpr int SLOT      = 32768;
constexpr int NSLOT     = 6;
constexpr int NTILE     = 16;
constexpr int NFFN      = 112;
constexpr int DEPTH_LO  = 2;
constexpr int DEPTH_HI  = 3;
constexpr int LEAD_THR8 = 8;
constexpr int WO_MARGIN = 112;
constexpr int WDEPTH    = 4;
constexpr int SEQ_WO    = 33;
constexpr int NSEQ      = 34;
constexpr int SLOT_WGU  = 4, SLOT_WD = 5;
constexpr int DLY_F     = 500;
constexpr int DLY_F_IDLE = 1100;
constexpr int RESET_TILE = 8;
constexpr int SAMPLE_NS = 100;
constexpr uint32_t SENT = 0xFFFFFFFFu;

constexpr int OFF_XN   = NSLOT * SLOT;
constexpr int XN_PITCH = 1040;
constexpr int OFF_QS   = OFF_XN + 4 * XN_PITCH;
constexpr int QS_PITCH = 272;
constexpr int OFF_P    = OFF_QS + 4 * QS_PITCH;
constexpr int OFF_RED  = OFF_P + 4 * QS_PITCH;
constexpr int OFF_MX   = OFF_RED + 4096;
constexpr int OFF_L    = OFF_MX + 64;
constexpr int OFF_ACT  = OFF_L + 128;
constexpr int OFF_RED2 = OFF_ACT + 128;
constexpr int OFF_CS   = OFF_RED2 + 512;
constexpr int OFF_ST   = OFF_CS + 512;
constexpr int OFF_BAR  = OFF_ST + 32;
constexpr int OFF_VAR  = OFF_BAR + 192;
constexpr int SMEM_USED = OFF_VAR + 64;
constexpr int SMEM_BYTES = SMEM_USED + 1024;
static_assert(OFF_RED % 16 == 0 && OFF_MX % 16 == 0 && OFF_ST % 8 == 0 && OFF_BAR % 8 == 0, "alignment");

__device__ uint2    g_q[4 * 2048];
__device__ float    g_partO[32 * 4 * 4 * 128];
__device__ float2   g_ml[32 * 4 * 4];
__device__ float    g_ypart[4 * 32 * 32 * 16];
__device__ uint16_t g_h[4 * 512];
__device__ float    g_dpart[4 * 32 * NFFN * 16];
__device__ unsigned g_cnt0, g_cnt1, g_prog;

__device__ __forceinline__ uint32_t smem_u32(const void* p) { return (uint32_t)__cvta_generic_to_shared(p); }
__device__ __forceinline__ void mbar_init(uint32_t bar, uint32_t cnt) {
    asm volatile("mbarrier.init.shared::cta.b64 [%0], %1;" ::"r"(bar), "r"(cnt) : "memory");
}
__device__ __forceinline__ void mbar_expect_tx(uint32_t bar, uint32_t bytes) {
    asm volatile("mbarrier.arrive.expect_tx.shared::cta.b64 _, [%0], %1;" ::"r"(bar), "r"(bytes) : "memory");
}
__device__ __forceinline__ void mbar_arrive(uint32_t bar) {
    asm volatile("mbarrier.arrive.shared::cta.b64 _, [%0];" ::"r"(bar) : "memory");
}
__device__ __forceinline__ bool mbar_try(uint32_t bar, uint32_t parity) {
    uint32_t ok;
    asm volatile("{\n.reg .pred p;\nmbarrier.try_wait.parity.shared::cta.b64 p, [%1], %2;\nselp.u32 %0, 1, 0, p;\n}"
                 : "=r"(ok) : "r"(bar), "r"(parity) : "memory");
    return ok != 0;
}
constexpr uint32_t SPIN_LIMIT = 1u << 22;
__device__ __forceinline__ void mbar_wait(uint32_t bar, uint32_t parity) {
    uint32_t it = 0;
    while (!mbar_try(bar, parity)) { if (++it > SPIN_LIMIT) __trap(); }
}
__device__ __forceinline__ void tma3d(uint32_t dst, const CUtensorMap* m, int c0, int c1, int c2, uint32_t bar, uint64_t pol) {
    asm volatile("cp.async.bulk.tensor.3d.shared::cluster.global.mbarrier::complete_tx::bytes.L2::cache_hint [%0], [%1, {%3, %4, %5}], [%2], %6;"
                 ::"r"(dst), "l"(m), "r"(bar), "r"(c0), "r"(c1), "r"(c2), "l"(pol) : "memory");
}
__device__ __forceinline__ void ldsm4(uint32_t (&r)[4], uint32_t addr) {
    asm volatile("ldmatrix.sync.aligned.m8n8.x4.shared.b16 {%0,%1,%2,%3}, [%4];"
                 : "=r"(r[0]), "=r"(r[1]), "=r"(r[2]), "=r"(r[3]) : "r"(addr) : "memory");
}
__device__ __forceinline__ void ldsm4t(uint32_t (&r)[4], uint32_t addr) {
    asm volatile("ldmatrix.sync.aligned.m8n8.x4.trans.shared.b16 {%0,%1,%2,%3}, [%4];"
                 : "=r"(r[0]), "=r"(r[1]), "=r"(r[2]), "=r"(r[3]) : "r"(addr) : "memory");
}
__device__ __forceinline__ void mma16816(float (&c)[4], const uint32_t (&a)[4], uint32_t b0, uint32_t b1) {
    asm volatile("mma.sync.aligned.m16n8k16.row.col.f32.bf16.bf16.f32 {%0,%1,%2,%3}, {%4,%5,%6,%7}, {%8,%9}, {%0,%1,%2,%3};"
                 : "+f"(c[0]), "+f"(c[1]), "+f"(c[2]), "+f"(c[3])
                 : "r"(a[0]), "r"(a[1]), "r"(a[2]), "r"(a[3]), "r"(b0), "r"(b1));
}
__device__ __forceinline__ void cbar() { asm volatile("bar.sync 1, 256;" ::: "memory"); }
__device__ __forceinline__ void bar_sync(int id, int n) { asm volatile("bar.sync %0, %1;" ::"r"(id), "r"(n) : "memory"); }
__device__ __forceinline__ void bar_arrive(int id, int n) { asm volatile("bar.arrive %0, %1;" ::"r"(id), "r"(n) : "memory"); }
__device__ __forceinline__ uint4 ld_poll4(const void* p) {
    uint4 v;
    asm volatile("ld.relaxed.gpu.global.v4.u32 {%0,%1,%2,%3}, [%4];" : "=r"(v.x), "=r"(v.y), "=r"(v.z), "=r"(v.w) : "l"(p) : "memory");
    return v;
}
__device__ __forceinline__ uint2 ld_poll2(const void* p) {
    uint2 v;
    asm volatile("ld.relaxed.gpu.global.v2.u32 {%0,%1}, [%2];" : "=r"(v.x), "=r"(v.y) : "l"(p) : "memory");
    return v;
}
__device__ __forceinline__ void st_rel32(void* p, uint32_t v) { asm volatile("st.relaxed.gpu.global.u32 [%0], %1;" ::"l"(p), "r"(v) : "memory"); }
__device__ __forceinline__ void st_rel16(void* p, uint16_t v) { asm volatile("st.relaxed.gpu.global.u16 [%0], %1;" ::"l"(p), "h"(v) : "memory"); }
__device__ __forceinline__ void st_rel64(void* p, uint32_t a, uint32_t b) { asm volatile("st.relaxed.gpu.global.v2.u32 [%0], {%1,%2};" ::"l"(p), "r"(a), "r"(b) : "memory"); }
__device__ __forceinline__ void st_rel128(void* p, uint32_t v) { asm volatile("st.relaxed.gpu.global.v4.u32 [%0], {%1,%1,%1,%1};" ::"l"(p), "r"(v) : "memory"); }
__device__ __forceinline__ uint32_t umax4(const uint4& v) { return max(max(v.x, v.y), max(v.z, v.w)); }
template <class T> __device__ __forceinline__ void pin(T*& p) { asm volatile("" : "+l"(p)); }
__device__ __forceinline__ bool valid8h(const uint4& v) {
    return (__vcmpeq2(v.x, SENT) | __vcmpeq2(v.y, SENT) | __vcmpeq2(v.z, SENT) | __vcmpeq2(v.w, SENT)) == 0;
}
struct Spin {
    uint32_t it = 0;
    __device__ __forceinline__ void tick() { if (++it > SPIN_LIMIT) __trap(); }
};
__device__ __forceinline__ void wait_progress(int n) {
    Spin sp; unsigned v;
    while (true) {
        asm volatile("ld.relaxed.gpu.global.u32 %0, [%1];" : "=r"(v) : "l"(&g_prog) : "memory");
        if ((int)v >= n) break;
        sp.tick(); __nanosleep(64);
    }
}
__device__ __forceinline__ uint32_t pack_bf16(float lo, float hi) {
    uint32_t r; asm("cvt.rn.bf16x2.f32 %0, %1, %2;" : "=r"(r) : "f"(hi), "f"(lo)); return r;
}
__device__ __forceinline__ void delay_cycles(int n) { if (n > 0) { const long long t0 = clock64(); while (clock64() - t0 < n) {} } }
__device__ __forceinline__ float bf16r(float x) { return __uint_as_float(pack_bf16(0.f, x) & 0xFFFF0000u); }
__device__ __forceinline__ float bf_lo(uint32_t v) { return __uint_as_float(v << 16); }
__device__ __forceinline__ float bf_hi(uint32_t v) { return __uint_as_float(v & 0xFFFF0000u); }
__device__ __forceinline__ uint32_t hmax2(uint32_t a, uint32_t b) {
    uint32_t r; asm("max.bf16x2 %0, %1, %2;" : "=r"(r) : "r"(a), "r"(b)); return r;
}
__device__ __forceinline__ float ex2(float x) { float r; asm("ex2.approx.ftz.f32 %0, %1;" : "=f"(r) : "f"(x)); return r; }

__device__ __forceinline__ float2 ln_stats(const uint4& a, const uint4& b, float (&v)[16]) {
    v[0] = bf_lo(a.x); v[1] = bf_hi(a.x); v[2] = bf_lo(a.y); v[3] = bf_hi(a.y);
    v[4] = bf_lo(a.z); v[5] = bf_hi(a.z); v[6] = bf_lo(a.w); v[7] = bf_hi(a.w);
    v[8] = bf_lo(b.x); v[9] = bf_hi(b.x); v[10] = bf_lo(b.y); v[11] = bf_hi(b.y);
    v[12] = bf_lo(b.z); v[13] = bf_hi(b.z); v[14] = bf_lo(b.w); v[15] = bf_hi(b.w);
    const float shift = __shfl_sync(0xffffffffu, v[0], 0);
    float s0 = 0.f, s1 = 0.f, s2 = 0.f, s3 = 0.f, q0 = 0.f, q1 = 0.f, q2 = 0.f, q3 = 0.f;
#pragma unroll
    for (int i = 0; i < 16; i += 4) {
        const float d0 = v[i] - shift, d1 = v[i + 1] - shift, d2 = v[i + 2] - shift, d3 = v[i + 3] - shift;
        s0 += d0; s1 += d1; s2 += d2; s3 += d3;
        q0 = fmaf(d0, d0, q0); q1 = fmaf(d1, d1, q1); q2 = fmaf(d2, d2, q2); q3 = fmaf(d3, d3, q3);
    }
    float s = (s0 + s1) + (s2 + s3), ss = (q0 + q1) + (q2 + q3);
#pragma unroll
    for (int o = 16; o > 0; o >>= 1) { s += __shfl_xor_sync(0xffffffffu, s, o); ss += __shfl_xor_sync(0xffffffffu, ss, o); }
    const float md = s * (1.0f / 512.0f);
    const float var = fmaxf(ss * (1.0f / 512.0f) - md * md, 0.f);
    const float m = bf16r(shift + md);
    float sq; asm("sqrt.approx.f32 %0, %1;" : "=f"(sq) : "f"(bf16r(bf16r(var) + 1e-5f)));
    const float sd = bf16r(sq);
    return make_float2(m, __fdividef(1.0f, sd));
}

struct Maps { CUtensorMap m[7]; };

__global__ void __launch_bounds__(NTHREADS, 1)
fused_decode_kernel(const __grid_constant__ Maps maps, const __nv_bfloat16* __restrict__ x, __nv_bfloat16* __restrict__ out)
{
    extern __shared__ __align__(1024) unsigned char smem_raw[];
    unsigned char* smem = smem_raw + ((1024u - (smem_u32(smem_raw) & 1023u)) & 1023u);
    const uint32_t sbase = smem_u32(smem);
    const uint32_t bar_full = sbase + OFF_BAR, bar_empty = sbase + OFF_BAR + 48, bar_ready = sbase + OFF_BAR + 96, bar_w = sbase + OFF_BAR + 104;
    volatile unsigned* vars = reinterpret_cast<volatile unsigned*>(smem + OFF_VAR);
    const int tid = threadIdx.x, warp = tid >> 5, lane = tid & 31;
    const int cta = blockIdx.x;

    uint4 xa = make_uint4(0, 0, 0, 0), xb = xa;
    float xres = 0.f;
    unsigned cnt0 = 0;
    if (warp < 4) {
        const uint4* xr = reinterpret_cast<const uint4*>(x + warp * 512);
        xa = __ldg(xr + lane); xb = __ldg(xr + 32 + lane);
        if (warp == 0) xres = __bfloat162float(x[(cta >> 5) * 512 + (cta & 31) * 16 + (lane >> 1)]);
        if (tid == 0) cnt0 = atomicAdd(&g_cnt0, 1u);
    } else if (warp == 7) {
        st_rel128(&g_q[(lane >> 3) * 2048 + cta * 16 + (lane & 7) * 2], 0u);
    }
    uint64_t pol;
    asm volatile("createpolicy.fractional.L2::evict_first.b64 %0, 1.0;" : "=l"(pol));
    if (__builtin_expect(tid == 256, 1)) {
        for (int i = 0; i < NSLOT; i++) { mbar_init(bar_full + 8 * i, 1); mbar_init(bar_empty + 8 * i, 8); }
        asm volatile("fence.mbarrier_init.release.cluster;" ::: "memory");
        mbar_expect_tx(bar_full, 32768);
        tma3d(sbase, &maps.m[2], cta * 32, 0, 0, bar_full, pol);
        tma3d(sbase + 16384, &maps.m[2], cta * 32, 256, 0, bar_full, pol);
        mbar_expect_tx(bar_full + 8, 32768);
        tma3d(sbase + SLOT, &maps.m[0], 0, cta * (NTILE * 128), 0, bar_full + 8, pol);
        mbar_expect_tx(bar_full + 16, 32768);
        tma3d(sbase + 2 * SLOT, &maps.m[1], 0, cta * (NTILE * 128), 0, bar_full + 16, pol);
        asm volatile("red.relaxed.gpu.global.add.u32 [%0], 2;" ::"l"(&g_prog) : "memory");
        mbar_init(bar_ready, 1);
        for (int i = 0; i < 6; i++) mbar_init(bar_w + 8 * i, 1);
        vars[1] = 0; vars[2] = 0; vars[3] = 0;
        asm volatile("fence.mbarrier_init.release.cluster;" ::: "memory");
    } else if (tid > 256 && tid <= 263) {
        asm volatile("prefetch.tensormap [%0];" ::"l"(&maps.m[tid - 257]) : "memory");
    }
    if (warp == 8) { __syncwarp(); bar_arrive(8, NTHREADS); } else bar_sync(8, NTHREADS);

    if (warp == 8) {
        if (lane == 0) {
            const int key0 = cta * (NTILE * 128);
            int arrived = 0;
            int nkv = 2;
            for (int i = 3; i < NSEQ; i++) {
                const int slot = i % NSLOT;
                const bool is_w = (i == SEQ_WO);
                if (i >= NSLOT) mbar_wait(bar_empty + 8 * slot, ((i / NSLOT) - 1) & 1);
                const int grel = (int)vars[2];
                const int lead8 = (nkv * NCTA - grel) / (NCTA / 8);
                const int d = (lead8 > LEAD_THR8) ? DEPTH_LO : DEPTH_HI;
                while (arrived < i - d + 1) { mbar_wait(bar_full + 8 * (arrived % NSLOT), (arrived / NSLOT) & 1); arrived++; }
                if (i == SEQ_WO && grel < NCTA * 32 - WO_MARGIN) wait_progress(NCTA * 32 - WO_MARGIN);
                const uint32_t dst = sbase + slot * SLOT, fb = bar_full + 8 * slot;
                mbar_expect_tx(fb, 32768);
                if (is_w) tma3d(dst, &maps.m[3], 0, (cta >> 2) * 128, (cta & 3) * 2, fb, pol);
                else      tma3d(dst, &maps.m[nkv & 1], 0, key0 + (nkv >> 1) * 128, 0, fb, pol);
                if (!is_w) {
                    asm volatile("red.relaxed.gpu.global.add.u32 [%0], 1;" ::"l"(&g_prog) : "memory");
                    nkv++;
                }
            }
            vars[3] = 1;
            if (cta < NFFN) {
                mbar_wait(bar_empty + 8 * SLOT_WGU, (34 / NSLOT - 1) & 1);
                mbar_wait(bar_empty + 8 * SLOT_WD, (35 / NSLOT - 1) & 1);
                wait_progress(NCTA * 32);
                mbar_wait(bar_full + 8 * (SEQ_WO % NSLOT), (SEQ_WO / NSLOT) & 1);
                for (int k = 0; k < 6; k++) {
                    if (k >= WDEPTH) mbar_wait(bar_w + 8 * (k - WDEPTH), 0);
                    mbar_expect_tx(bar_w + 8 * k, 8192);
                    const int mi = (k < 4) ? 4 + (k >> 1) : 6;
                    const int c0 = (k < 4) ? cta * 16 : 0, c1 = (k < 4) ? (k & 1) * 256 : cta * 16, c2 = (k < 4) ? 0 : (k - 4) * 4;
                    tma3d(sbase + SLOT_WGU * SLOT + k * 8192, &maps.m[mi], c0, c1, c2, bar_w + 8 * k, pol);
                }
            }
        }
        return;
    }

    const int pair = cta >> 2, split = cta & 3;

    if (warp == 9) {
        Spin sp;
        auto sample = [&]() {
            unsigned v;
            asm volatile("ld.relaxed.gpu.global.u32 %0, [%1];" : "=r"(v) : "l"(&g_prog) : "memory");
            if (lane == 0) vars[2] = v;
        };
        while (vars[1] < RESET_TILE) { sp.tick(); sample(); __nanosleep(SAMPLE_NS); }
        const unsigned epoch = vars[0];
#pragma unroll 1
        for (int u = lane; u < 128; u += 32) {
            st_rel128(&g_partO[((pair * 4 + (u >> 5)) * 4 + split) * 128 + (u & 31) * 4], SENT);
            const int seg = u >> 2;
            st_rel128(&g_ypart[(((seg >> 3) * 32 + (cta & 3) * 8 + (seg & 7)) * 32 + (cta >> 2)) * 16 + (u & 3) * 4], SENT);
        }
        if (lane < 4) st_rel64(&g_ml[(pair * 4 + lane) * 4 + split], SENT, SENT);
        if (lane < 2) st_rel128(&g_h[(cta >> 5) * 512 + (cta & 31) * 16 + lane * 8], SENT);
        if (cta < NFFN) {
#pragma unroll 1
            for (int e = lane; e < 512; e += 32) st_rel128(&g_dpart[((e >> 2) * NFFN + cta) * 16 + (e & 3) * 4], SENT);
        }
        __threadfence();
        __syncwarp();
        if (lane == 0) {
            atomicAdd(&g_cnt1, 1u);
            unsigned v; Spin sp2;
            while (true) {
                asm volatile("ld.acquire.gpu.global.u32 %0, [%1];" : "=r"(v) : "l"(&g_cnt1) : "memory");
                if ((int)(v - (epoch + 1) * NCTA) >= 0) break;
                sp2.tick(); sample(); __nanosleep(128);
            }
            mbar_arrive(bar_ready);
        }
        __syncwarp();
        while (vars[3] == 0) { sp.tick(); sample(); __nanosleep(SAMPLE_NS); }
        return;
    }

    const int r8 = lane >> 2, q4 = lane & 3;
    const int hp = q4 & 1, kh = q4 >> 1;
    constexpr float LOG2E = 1.4426950408889634f;
    const int bq = pair >> 3, gq = pair & 7;

    if (tid == 0) vars[0] = cnt0 >> 7;

    if (warp < 4) {
        float v[16];
        const float2 st = ln_stats(xa, xb, v);
        uint32_t o[8];
#pragma unroll
        for (int i = 0; i < 8; i++) o[i] = pack_bf16(bf16r(v[2 * i] - st.x) * st.y, bf16r(v[2 * i + 1] - st.x) * st.y);
        unsigned char* row = smem + OFF_XN + warp * XN_PITCH;
        *reinterpret_cast<uint4*>(row + lane * 16) = make_uint4(o[0], o[1], o[2], o[3]);
        *reinterpret_cast<uint4*>(row + 512 + lane * 16) = make_uint4(o[4], o[5], o[6], o[7]);
    }
    cbar();
    const uint32_t tag = vars[0] + 1;

    {
        uint32_t bfr[4][2];
        {
            uint32_t t4[4];
#pragma unroll
            for (int u = 0; u < 2; u++) {
                ldsm4(t4, sbase + OFF_XN + (lane & 3) * XN_PITCH + (8 * warp + 4 * u + (lane >> 3)) * 16);
                bfr[2 * u][0] = t4[0]; bfr[2 * u][1] = t4[1]; bfr[2 * u + 1][0] = t4[2]; bfr[2 * u + 1][1] = t4[3];
            }
        }
        mbar_wait(bar_full + 0, 0);
        float acc[2][4] = {};
#pragma unroll
        for (int ks = 0; ks < 4; ks++) {
            const int k = 64 * warp + 16 * ks + (lane & 7) + (lane >> 4) * 8;
#pragma unroll
            for (int mt = 0; mt < 2; mt++) {
                uint32_t a[4];
                const int chunk = 2 * mt + ((lane >> 3) & 1);
                ldsm4t(a, sbase + k * 64 + ((chunk ^ ((k >> 1) & 3)) << 4));
                mma16816(acc[mt], a, bfr[ks][0], bfr[ks][1]);
            }
        }
        __syncwarp();
        if (lane == 0) mbar_arrive(bar_empty + 0);
        float* red = reinterpret_cast<float*>(smem + OFF_RED);
#pragma unroll
        for (int mt = 0; mt < 2; mt++) {
            float2 v = kh ? make_float2(acc[mt][2], acc[mt][3]) : make_float2(acc[mt][0], acc[mt][1]);
            *reinterpret_cast<float2*>(red + ((warp * 2 + mt) * 16 + r8 + 8 * kh) * 4 + 2 * hp) = v;
        }
        cbar();
        if (tid < 64) {
            const int b = tid >> 4, c2 = tid & 15;
            float s0 = 0.f, s1 = 0.f;
            const int c0 = 2 * c2, c1 = 2 * c2 + 1;
#pragma unroll
            for (int ww = 0; ww < 8; ww++) {
                s0 += red[((ww * 2 + (c0 >> 4)) * 16 + (c0 & 15)) * 4 + b];
                s1 += red[((ww * 2 + (c1 >> 4)) * 16 + (c1 & 15)) * 4 + b];
            }
            st_rel64(&g_q[b * 2048 + cta * 16 + c2], pack_bf16(s0, s1), tag);
        }
        {
            const uint2* src = &g_q[bq * 2048 + gq * 256 + tid];
            uint2 v;
            Spin sp;
            while (true) { v = ld_poll2(src); if (__all_sync(0xffffffffu, v.y == tag)) break; sp.tick(); }
            *reinterpret_cast<uint32_t*>(smem + OFF_QS + (tid >> 6) * QS_PITCH + (tid & 63) * 4) = v.x;
        }
        cbar();
    }
    uint32_t qf[8][2];
    {
        uint32_t t4[4];
#pragma unroll
        for (int u = 0; u < 4; u++) {
            ldsm4(t4, sbase + OFF_QS + (lane & 3) * QS_PITCH + (4 * u + (lane >> 3)) * 16);
            qf[2 * u][0] = t4[0]; qf[2 * u][1] = t4[1]; qf[2 * u + 1][0] = t4[2]; qf[2 * u + 1][1] = t4[3];
        }
    }

    const uint32_t voff = (warp >> 2) * 16384 + ((lane & 7) + (lane >> 4) * 8) * 128 +
                          ((((2 * warp + ((lane >> 3) & 1)) & 7) ^ (lane & 7)) << 4);
    const uint32_t poff = sbase + OFF_P + (lane & 3) * QS_PITCH + (lane >> 3) * 16;
    const uint32_t koff = (16 * warp + (lane & 7) + ((lane >> 3) & 1) * 8) * 128;
    const uint32_t kx = lane & 7, kc = lane >> 4;
    constexpr float SCALE = 0.08838834764831845f;
    uint32_t* mxbuf = reinterpret_cast<uint32_t*>(smem + OFF_MX);
    uint32_t M2 = 0xFF80FF80u;
    float l0 = 0.f, l1 = 0.f;
    float oacc[2][4] = {};
    int slot = 1; uint32_t ph = 0;

    for (int t = 0;; t++) {
        mbar_wait(bar_full + 8 * slot, ph);
        float sa[4] = {}, sb[4] = {};
        {
            const uint32_t kb = sbase + slot * SLOT + koff;
#pragma unroll
            for (int ks = 0; ks < 8; ks++) {
                uint32_t a[4];
                ldsm4(a, kb + (ks >> 2) * 16384 + (((2 * (ks & 3) + kc) ^ kx) << 4));
                if (ks & 1) mma16816(sb, a, qf[ks][0], qf[ks][1]); else mma16816(sa, a, qf[ks][0], qf[ks][1]);
            }
        }
        __syncwarp();
        if (lane == 0) mbar_arrive(bar_empty + 8 * slot);
        if (++slot == NSLOT) { slot = 0; ph ^= 1; }

        const float r0 = kh ? sa[2] + sb[2] : sa[0] + sb[0];
        const float r1 = kh ? sa[3] + sb[3] : sa[1] + sb[1];
        uint32_t sp = pack_bf16(r0, r1);
        sp = pack_bf16(bf_lo(sp) * SCALE, bf_hi(sp) * SCALE);
        uint32_t mx = sp;
#pragma unroll
        for (int o = 2; o <= 16; o <<= 1) mx = hmax2(mx, __shfl_xor_sync(0xffffffffu, mx, o));
        if (lane < 2) mxbuf[lane * 8 + warp] = mx;
        if (tid == 0) vars[1] = t + 1;
        cbar();
        {
            const uint4 m0 = *reinterpret_cast<const uint4*>(mxbuf + hp * 8), m1 = *reinterpret_cast<const uint4*>(mxbuf + hp * 8 + 4);
            uint32_t mt = hmax2(hmax2(hmax2(m0.x, m0.y), hmax2(m0.z, m0.w)), hmax2(hmax2(m1.x, m1.y), hmax2(m1.z, m1.w)));
            const uint32_t Mn = hmax2(M2, mt);
            const float a0 = ex2((bf_lo(M2) - bf_lo(Mn)) * LOG2E), a1 = ex2((bf_hi(M2) - bf_hi(Mn)) * LOG2E);
            const float p0 = ex2((bf_lo(sp) - bf_lo(Mn)) * LOG2E), p1 = ex2((bf_hi(sp) - bf_hi(Mn)) * LOG2E);
            M2 = Mn;
            l0 = fmaf(l0, a0, p0); l1 = fmaf(l1, a1, p1);
            const uint32_t pp = pack_bf16(p0, p1);
            unsigned char* pd = smem + OFF_P + (2 * hp) * QS_PITCH + (16 * warp + r8 + 8 * kh) * 2;
            *reinterpret_cast<uint16_t*>(pd) = (uint16_t)(pp & 0xFFFF);
            *reinterpret_cast<uint16_t*>(pd + QS_PITCH) = (uint16_t)(pp >> 16);
#pragma unroll
            for (int c = 0; c < 2; c++) { oacc[c][0] *= a0; oacc[c][1] *= a1; oacc[c][2] *= a0; oacc[c][3] *= a1; }
        }
        if (t == NTILE - 1) break;
        cbar();
        uint32_t pb[8][2];
        {
            uint32_t t4[4];
#pragma unroll
            for (int u = 0; u < 4; u++) {
                ldsm4(t4, poff + u * 64);
                pb[2 * u][0] = t4[0]; pb[2 * u][1] = t4[1]; pb[2 * u + 1][0] = t4[2]; pb[2 * u + 1][1] = t4[3];
            }
        }
        mbar_wait(bar_full + 8 * slot, ph);
        {
            const uint32_t vb = sbase + slot * SLOT + voff;
#pragma unroll
            for (int ks = 0; ks < 8; ks++) {
                uint32_t a[4];
                ldsm4t(a, vb + ks * 2048);
                mma16816(oacc[ks & 1], a, pb[ks][0], pb[ks][1]);
            }
        }
        __syncwarp();
        if (lane == 0) mbar_arrive(bar_empty + 8 * slot);
        if (++slot == NSLOT) { slot = 0; ph ^= 1; }
    }

    const int head = cta >> 2;
    float* p_partO = &g_partO[((pair * 4 + 2 * hp) * 4 + split) * 128 + 16 * warp + r8 + 8 * kh];
    float* p_dpart = &g_dpart[(((2 * hp) * 32 + 4 * warp) * NFFN + cta) * 16 + r8 + 8 * kh];
    const float* p_dsrc = &g_dpart[(cta * NFFN + (tid >> 2)) * 16 + (tid & 3) * 4];
    __nv_bfloat16* p_out = out + (cta >> 5) * 512 + (cta & 31) * 16 + (lane >> 1);
    pin(p_partO); pin(p_dpart); pin(p_dsrc); pin(p_out);

    {
        float s0 = l0, s1 = l1;
#pragma unroll
        for (int o = 2; o <= 16; o <<= 1) { s0 += __shfl_xor_sync(0xffffffffu, s0, o); s1 += __shfl_xor_sync(0xffffffffu, s1, o); }
        if (lane < 2) *reinterpret_cast<float2*>(smem + OFF_L + warp * 16 + lane * 8) = make_float2(s0, s1);
        mbar_wait(bar_ready, 0);
        cbar();
        if (warp == 0) {
            const uint32_t other = __shfl_sync(0xffffffffu, M2, lane >> 1);
            float l = 0.f;
#pragma unroll
            for (int ww = 0; ww < 8; ww++) l += *reinterpret_cast<const float*>(smem + OFF_L + ww * 16 + (lane & 3) * 4);
            const float m = (lane & 1) ? bf_hi(other) : bf_lo(other);
            if (lane < 4) st_rel64(&g_ml[(pair * 4 + lane) * 4 + split], __float_as_uint(m), __float_as_uint(l));
        }
        uint32_t pb[8][2];
        {
            uint32_t t4[4];
#pragma unroll
            for (int u = 0; u < 4; u++) {
                ldsm4(t4, poff + u * 64);
                pb[2 * u][0] = t4[0]; pb[2 * u][1] = t4[1]; pb[2 * u + 1][0] = t4[2]; pb[2 * u + 1][1] = t4[3];
            }
        }
        float o2[2][4] = {};
        {
            mbar_wait(bar_full + 8 * slot, ph);
            const uint32_t vb = sbase + slot * SLOT + voff;
            uint32_t a[8][4];
#pragma unroll
            for (int ks = 0; ks < 8; ks++) ldsm4t(a[ks], vb + ks * 2048);
#pragma unroll
            for (int ks = 0; ks < 8; ks++) mma16816((ks & 2) ? o2[ks & 1] : oacc[ks & 1], a[ks], pb[ks][0], pb[ks][1]);
        }
        const float v0 = kh ? (oacc[0][2] + oacc[1][2]) + (o2[0][2] + o2[1][2]) : (oacc[0][0] + oacc[1][0]) + (o2[0][0] + o2[1][0]);
        const float v1 = kh ? (oacc[0][3] + oacc[1][3]) + (o2[0][3] + o2[1][3]) : (oacc[0][1] + oacc[1][1]) + (o2[0][1] + o2[1][1]);
        st_rel32(p_partO, __float_as_uint(v0));
        st_rel32(p_partO + 512, __float_as_uint(v1));
    }

    float hres = 0.f;
    uint32_t df[4][4];
    if (warp < 4) {
        {
            const int ph_idx = (warp * 8 + (head >> 2)) * 4 + (head & 3);
            const float* po = &g_partO[ph_idx * 512 + lane * 4];
            const float* pm = reinterpret_cast<const float*>(&g_ml[ph_idx * 4]);
            uint4 o0, o1, o2, o3, ma, mb;
            Spin sp;
            while (true) {
                o0 = ld_poll4(po); o1 = ld_poll4(po + 128); o2 = ld_poll4(po + 256); o3 = ld_poll4(po + 384);
                ma = ld_poll4(pm); mb = ld_poll4(pm + 4);
                const uint32_t mxv = max(max(max(umax4(o0), umax4(o1)), max(umax4(o2), umax4(o3))), max(umax4(ma), umax4(mb)));
                if (__all_sync(0xffffffffu, mxv != SENT)) break;
                sp.tick();
            }
            const float m0 = __uint_as_float(ma.x), m1 = __uint_as_float(ma.z), m2 = __uint_as_float(mb.x), m3 = __uint_as_float(mb.z);
            const float M = fmaxf(fmaxf(m0, m1), fmaxf(m2, m3));
            float w0 = ex2((m0 - M) * LOG2E), w1 = ex2((m1 - M) * LOG2E), w2 = ex2((m2 - M) * LOG2E), w3 = ex2((m3 - M) * LOG2E);
            const float L = w0 * __uint_as_float(ma.y) + w1 * __uint_as_float(ma.w) + w2 * __uint_as_float(mb.y) + w3 * __uint_as_float(mb.w);
            const float inv = __fdividef(1.0f, L);
            const float e0 = (w0 * __uint_as_float(o0.x) + w1 * __uint_as_float(o1.x) + w2 * __uint_as_float(o2.x) + w3 * __uint_as_float(o3.x)) * inv;
            const float e1 = (w0 * __uint_as_float(o0.y) + w1 * __uint_as_float(o1.y) + w2 * __uint_as_float(o2.y) + w3 * __uint_as_float(o3.y)) * inv;
            const float e2 = (w0 * __uint_as_float(o0.z) + w1 * __uint_as_float(o1.z) + w2 * __uint_as_float(o2.z) + w3 * __uint_as_float(o3.z)) * inv;
            const float e3 = (w0 * __uint_as_float(o0.w) + w1 * __uint_as_float(o1.w) + w2 * __uint_as_float(o2.w) + w3 * __uint_as_float(o3.w)) * inv;
            *reinterpret_cast<uint2*>(smem + OFF_QS + warp * QS_PITCH + lane * 8) = make_uint2(pack_bf16(e0, e1), pack_bf16(e2, e3));
            bar_arrive(2, 256);
        }
        {
            const float* src = &g_ypart[(cta * 32 + 8 * warp + (lane >> 2)) * 16 + (lane & 3) * 4];
            uint16_t* p_h = &g_h[(cta >> 5) * 512 + (cta & 31) * 16 + (lane >> 1)];
            pin(p_h);
            uint4 y;
            Spin sp;
            while (true) {
                y = ld_poll4(src);
                if (__all_sync(0xffffffffu, umax4(y) != SENT)) break;
                sp.tick();
            }
            const bool up = lane & 16, up2 = lane & 8;
            const float a0 = __uint_as_float(y.x), a1 = __uint_as_float(y.y), a2 = __uint_as_float(y.z), a3 = __uint_as_float(y.w);
            const float v0 = (up ? a2 : a0) + __shfl_xor_sync(0xffffffffu, up ? a0 : a2, 16);
            const float v1 = (up ? a3 : a1) + __shfl_xor_sync(0xffffffffu, up ? a1 : a3, 16);
            float v = (up2 ? v1 : v0) + __shfl_xor_sync(0xffffffffu, up2 ? v0 : v1, 8);
            v += __shfl_xor_sync(0xffffffffu, v, 4);
            float* rc = reinterpret_cast<float*>(smem + OFF_RED2);
            if (!(lane & 4)) rc[warp * 16 + 4 * (lane & 3) + (up ? 2 : 0) + (up2 ? 1 : 0)] = v;
            bar_sync(7, 128);
            if (warp == 0) {
                const float* r2 = rc + (lane & 1) * 32 + (lane >> 1);
                float t = r2[0] + r2[16];
                t += __shfl_xor_sync(0xffffffffu, t, 1);
                hres = bf16r(xres + bf16r(t));
                if (!(lane & 1)) st_rel16(p_h, (uint16_t)(__float_as_uint(hres) >> 16));
            }
        }
        {
            const uint4* hr = reinterpret_cast<const uint4*>(g_h + warp * 512);
            uint4 a, b;
            Spin sp;
            while (true) {
                a = ld_poll4(hr + lane); b = ld_poll4(hr + 32 + lane);
                if (__all_sync(0xffffffffu, valid8h(a) & valid8h(b))) break;
                sp.tick();
            }
            if (cta < NFFN) {
                unsigned char* row = smem + OFF_XN + warp * XN_PITCH;
                *reinterpret_cast<uint4*>(row + lane * 16) = a;
                *reinterpret_cast<uint4*>(row + 512 + lane * 16) = b;
                bar_arrive(3, 256);
                float v[16];
                const float2 st = ln_stats(a, b, v);
                if (lane == 0) *reinterpret_cast<float2*>(smem + OFF_ST + warp * 8) = st;
                bar_arrive(4, 256);
                mbar_wait(bar_w + 32, 0); mbar_wait(bar_w + 40, 0);
                const uint32_t wb = sbase + SLOT_WD * SLOT + warp * 2048 + ((lane & 7) + (lane >> 4) * 8) * 128;
#pragma unroll
                for (int i = 0; i < 4; i++) ldsm4t(df[i], wb + (((2 * i + ((lane >> 3) & 1)) ^ (lane & 7)) << 4));
            }
        }
    } else {
        const int m = warp - 4;
        {
            uint32_t af[2][8][4];
            float* p_y = &g_ypart[(((2 * hp) * 32 + (cta & 3) * 8 + 2 * m) * 32 + head) * 16 + r8 + 8 * kh];
            pin(p_y);
            mbar_wait(bar_full + 8 * (SEQ_WO % NSLOT), (SEQ_WO / NSLOT) & 1);
#pragma unroll
            for (int i = 0; i < 2; i++) {
                const int j = 2 * m + i;
                const uint32_t wb = sbase + (SEQ_WO % NSLOT) * SLOT + (j >> 2) * 16384 + ((lane & 7) + (lane >> 4) * 8) * 128 +
                                    ((((2 * j + ((lane >> 3) & 1)) & 7) ^ (lane & 7)) << 4);
#pragma unroll
                for (int ks = 0; ks < 8; ks++) ldsm4t(af[i][ks], wb + ks * 2048);
            }
            bar_sync(2, 256);
            float acc[2][2][4] = {};
            uint32_t t4[4][4];
#pragma unroll
            for (int u = 0; u < 4; u++) ldsm4(t4[u], sbase + OFF_QS + (lane & 3) * QS_PITCH + (4 * u + (lane >> 3)) * 16);
#pragma unroll
            for (int u = 0; u < 4; u++) {
#pragma unroll
                for (int i = 0; i < 2; i++) {
                    mma16816(acc[i][0], af[i][2 * u], t4[u][0], t4[u][1]);
                    mma16816(acc[i][1], af[i][2 * u + 1], t4[u][2], t4[u][3]);
                }
            }
#pragma unroll
            for (int i = 0; i < 2; i++) {
                const float v0 = kh ? acc[i][0][2] + acc[i][1][2] : acc[i][0][0] + acc[i][1][0];
                const float v1 = kh ? acc[i][0][3] + acc[i][1][3] : acc[i][0][1] + acc[i][1][1];
                st_rel32(p_y + i * 32 * 16, __float_as_uint(v0));
                st_rel32(p_y + i * 32 * 16 + 32 * 32 * 16, __float_as_uint(v1));
            }
        }
        if (cta < NFFN) {
            uint32_t gf[8][2][4];
            mbar_wait(bar_w, 0); mbar_wait(bar_w + 8, 0); mbar_wait(bar_w + 16, 0); mbar_wait(bar_w + 24, 0);
#pragma unroll
            for (int ks = 0; ks < 8; ks++) {
                const int k = 128 * m + 16 * ks + (lane & 7) + (lane >> 4) * 8;
                const uint32_t a = sbase + SLOT_WGU * SLOT + k * 32 + ((((lane >> 3) & 1) ^ ((k >> 2) & 1)) << 4);
                ldsm4t(gf[ks][0], a);
                ldsm4t(gf[ks][1], a + 16384);
            }
            float sg = 0.f, su = 0.f;
            {
                float cs[2][4] = {};
#pragma unroll
                for (int ks = 0; ks < 8; ks++) { mma16816(cs[0], gf[ks][0], 0x3F803F80u, 0x3F803F80u); mma16816(cs[1], gf[ks][1], 0x3F803F80u, 0x3F803F80u); }
                float* csb = reinterpret_cast<float*>(smem + OFF_CS);
                if (q4 == 0) {
                    csb[(m * 2 + 0) * 16 + r8] = cs[0][0]; csb[(m * 2 + 0) * 16 + r8 + 8] = cs[0][2];
                    csb[(m * 2 + 1) * 16 + r8] = cs[1][0]; csb[(m * 2 + 1) * 16 + r8 + 8] = cs[1][2];
                }
                bar_sync(5, 128);
                const int c = (tid & 63) >> 2;
#pragma unroll
                for (int ww = 0; ww < 4; ww++) { sg += csb[(ww * 2) * 16 + c]; su += csb[(ww * 2 + 1) * 16 + c]; }
            }
            const uint32_t wdb = sbase + SLOT_WD * SLOT + warp * 2048 + ((lane & 7) + (lane >> 4) * 8) * 128;
            const bool have_wd = __all_sync(0xffffffffu, mbar_try(bar_w + 32, 0) && mbar_try(bar_w + 40, 0));
            if (have_wd) {
#pragma unroll
                for (int i = 0; i < 4; i++) ldsm4t(df[i], wdb + (((2 * i + ((lane >> 3) & 1)) ^ (lane & 7)) << 4));
            }
            bar_sync(3, 256);
            float acc[2][2][4] = {};
            uint32_t t4[4][4];
#pragma unroll
            for (int u = 0; u < 4; u++) ldsm4(t4[u], sbase + OFF_XN + (lane & 3) * XN_PITCH + (16 * m + 4 * u + (lane >> 3)) * 16);
#pragma unroll
            for (int u = 0; u < 4; u++) {
#pragma unroll
                for (int i = 0; i < 2; i++) {
                    mma16816(acc[i][0], gf[2 * u][i], t4[u][0], t4[u][1]);
                    mma16816(acc[i][1], gf[2 * u + 1][i], t4[u][2], t4[u][3]);
                }
            }
            float* red = reinterpret_cast<float*>(smem + OFF_RED);
#pragma unroll
            for (int i = 0; i < 2; i++) {
                const float2 v = kh ? make_float2(acc[i][0][2] + acc[i][1][2], acc[i][0][3] + acc[i][1][3])
                                    : make_float2(acc[i][0][0] + acc[i][1][0], acc[i][0][1] + acc[i][1][1]);
                *reinterpret_cast<float2*>(red + ((m * 2 + i) * 16 + r8 + 8 * kh) * 4 + 2 * hp) = v;
            }
            bar_sync(4, 256);
            if (tid < 192) {
                const int c = (tid & 63) >> 2, b = tid & 3;
                const float2 st = *reinterpret_cast<const float2*>(smem + OFF_ST + b * 8);
                float g = 0.f, u = 0.f;
#pragma unroll
                for (int ww = 0; ww < 4; ww++) { g += red[((ww * 2) * 16 + c) * 4 + b]; u += red[((ww * 2 + 1) * 16 + c) * 4 + b]; }
                g = bf16r((g - st.x * sg) * st.y); u = bf16r((u - st.x * su) * st.y);
                const float inner = 0.7978845608028654f * (g + 0.044715f * g * g * g);
                const float th = 1.0f - __fdividef(2.0f, __expf(2.0f * inner) + 1.0f);
                const float ge = bf16r(0.5f * g * (1.0f + th));
                *reinterpret_cast<__nv_bfloat16*>(smem + OFF_ACT + b * 32 + c * 2) = __float2bfloat16_rn(ge * u);
            }
            if (!have_wd) {
                mbar_wait(bar_w + 32, 0); mbar_wait(bar_w + 40, 0);
#pragma unroll
                for (int i = 0; i < 4; i++) ldsm4t(df[i], wdb + (((2 * i + ((lane >> 3) & 1)) ^ (lane & 7)) << 4));
            }
        }
    }
    if (cta < NFFN) {
        bar_sync(6, 256);
        const uint32_t b0 = *reinterpret_cast<const uint32_t*>(smem + OFF_ACT + (r8 & 3) * 32 + q4 * 4);
        const uint32_t b1 = *reinterpret_cast<const uint32_t*>(smem + OFF_ACT + (r8 & 3) * 32 + 16 + q4 * 4);
        float c[4][4] = {};
#pragma unroll
        for (int i = 0; i < 4; i++) mma16816(c[i], df[i], b0, b1);
#pragma unroll
        for (int i = 0; i < 4; i++) {
            st_rel32(p_dpart + i * NFFN * 16, __float_as_uint(kh ? c[i][2] : c[i][0]));
            st_rel32(p_dpart + i * NFFN * 16 + 32 * NFFN * 16, __float_as_uint(kh ? c[i][3] : c[i][1]));
        }
    } else {
        bar_sync(6, 256);
        delay_cycles(DLY_F_IDLE);
    }

    {
        const int quad = tid & 3;
        const bool two = (tid >> 2) + 64 < NFFN;
        uint4 a, b = make_uint4(0, 0, 0, 0);
        Spin sp;
        delay_cycles(DLY_F);
        while (true) {
            a = ld_poll4(p_dsrc);
            if (two) b = ld_poll4(p_dsrc + 64 * 16);
            if (__all_sync(0xffffffffu, max(umax4(a), umax4(b)) != SENT)) break;
            sp.tick();
        }
        float v[4] = {__uint_as_float(a.x) + __uint_as_float(b.x), __uint_as_float(a.y) + __uint_as_float(b.y),
                      __uint_as_float(a.z) + __uint_as_float(b.z), __uint_as_float(a.w) + __uint_as_float(b.w)};
        {
            const bool up = lane & 16;
            const float s0 = up ? v[0] : v[2], s1 = up ? v[1] : v[3];
            const float k0 = up ? v[2] : v[0], k1 = up ? v[3] : v[1];
            v[0] = k0 + __shfl_xor_sync(0xffffffffu, s0, 16);
            v[1] = k1 + __shfl_xor_sync(0xffffffffu, s1, 16);
            const bool up2 = lane & 8;
            const float s = up2 ? v[0] : v[1], k = up2 ? v[1] : v[0];
            v[0] = k + __shfl_xor_sync(0xffffffffu, s, 8);
            v[0] += __shfl_xor_sync(0xffffffffu, v[0], 4);
            if (!(lane & 4)) reinterpret_cast<float*>(smem + OFF_RED2)[warp * 16 + 4 * quad + ((lane & 16) ? 2 : 0) + ((lane & 8) ? 1 : 0)] = v[0];
        }
        cbar();
        if (warp == 0) {
            const float* r2 = reinterpret_cast<const float*>(smem + OFF_RED2) + (lane & 1) * 64 + (lane >> 1);
            float s = (r2[0] + r2[16]) + (r2[32] + r2[48]);
            s += __shfl_xor_sync(0xffffffffu, s, 1);
            if (!(lane & 1)) *p_out = __float2bfloat16_rn(hres + bf16r(s));
            if (cta == 0 && lane == 0) st_rel32(&g_prog, 0u);
        }
    }
}

typedef CUresult (*EncodeFn)(CUtensorMap*, CUtensorMapDataType, cuuint32_t, void*, const cuuint64_t*, const cuuint64_t*,
                             const cuuint32_t*, const cuuint32_t*, CUtensorMapInterleave, CUtensorMapSwizzle,
                             CUtensorMapL2promotion, CUtensorMapFloatOOBfill);

void encode(EncodeFn fn, CUtensorMap* m, const void* base, int rank, const cuuint64_t* dims, const cuuint64_t* strides,
            const cuuint32_t* box, CUtensorMapSwizzle sw, CUtensorMapL2promotion promo) {
    cuuint32_t es[3] = {1, 1, 1};
    fn(m, CU_TENSOR_MAP_DATA_TYPE_BFLOAT16, (cuuint32_t)rank, const_cast<void*>(base), dims, strides, box, es,
       CU_TENSOR_MAP_INTERLEAVE_NONE, sw, promo, CU_TENSOR_MAP_FLOAT_OOB_FILL_NONE);
}

}

extern "C" void kernel_launch(void* const* d_in, const int* in_sizes, int n_in, void* d_out, int out_size) {
    (void)in_sizes; (void)n_in; (void)out_size;
    static EncodeFn enc = nullptr;
    if (!enc) {
        void* fn = nullptr;
        cudaDriverEntryPointQueryResult qr;
        cudaGetDriverEntryPoint("cuTensorMapEncodeTiled", &fn, cudaEnableDefault, &qr);
        enc = (EncodeFn)fn;
        cudaFuncSetAttribute(fused_decode_kernel, cudaFuncAttributeMaxDynamicSharedMemorySize, SMEM_BYTES);
    }
    const void* x = d_in[0];
    Maps maps;
    {
        cuuint64_t dims[3] = {64, 262144, 2}; cuuint64_t str[2] = {256, 128}; cuuint32_t box[3] = {64, 128, 2};
        encode(enc, &maps.m[0], d_in[1], 3, dims, str, box, CU_TENSOR_MAP_SWIZZLE_128B, CU_TENSOR_MAP_L2_PROMOTION_L2_256B);
        encode(enc, &maps.m[1], d_in[2], 3, dims, str, box, CU_TENSOR_MAP_SWIZZLE_128B, CU_TENSOR_MAP_L2_PROMOTION_L2_256B);
    }
    {
        cuuint64_t dims[3] = {4096, 512, 1}; cuuint64_t str[2] = {8192, 8192 * 512}; cuuint32_t box[3] = {32, 256, 1};
        encode(enc, &maps.m[2], d_in[3], 3, dims, str, box, CU_TENSOR_MAP_SWIZZLE_64B, CU_TENSOR_MAP_L2_PROMOTION_L2_128B);
    }
    {
        cuuint64_t dims[3] = {64, 4096, 8}; cuuint64_t str[2] = {1024, 128}; cuuint32_t box[3] = {64, 128, 2};
        encode(enc, &maps.m[3], d_in[4], 3, dims, str, box, CU_TENSOR_MAP_SWIZZLE_128B, CU_TENSOR_MAP_L2_PROMOTION_L2_256B);
    }
    {
        cuuint64_t dims[3] = {1792, 512, 1}; cuuint64_t str[2] = {3584, 3584 * 512}; cuuint32_t box[3] = {16, 256, 1};
        encode(enc, &maps.m[4], d_in[6], 3, dims, str, box, CU_TENSOR_MAP_SWIZZLE_32B, CU_TENSOR_MAP_L2_PROMOTION_L2_128B);
        encode(enc, &maps.m[5], d_in[7], 3, dims, str, box, CU_TENSOR_MAP_SWIZZLE_32B, CU_TENSOR_MAP_L2_PROMOTION_L2_128B);
    }
    {
        cuuint64_t dims[3] = {64, 1792, 8}; cuuint64_t str[2] = {1024, 128}; cuuint32_t box[3] = {64, 16, 4};
        encode(enc, &maps.m[6], d_in[8], 3, dims, str, box, CU_TENSOR_MAP_SWIZZLE_128B, CU_TENSOR_MAP_L2_PROMOTION_L2_256B);
    }
    fused_decode_kernel<<<NCTA, NTHREADS, SMEM_BYTES, cudaStreamPerThread>>>(maps, (const __nv_bfloat16*)x, (__nv_bfloat16*)d_out);
}
```

```cpp
#include <cuda_runtime.h>
#include <cuda_bf16.h>
#include <cuda.h>
#include <stdint.h>

namespace {

constexpr int NCTA      = 128;
constexpr int NTHREADS  = 320;
constexpr int SLOT      = 32768;
constexpr int NSLOT     = 6;
constexpr int NTILE     = 16;
constexpr int NFFN      = 112;
constexpr int DEPTH_LO  = 2;
constexpr int DEPTH_HI  = 3;
constexpr int LEAD_THR8 = 8;
constexpr int WO_MARGIN = 112;
constexpr int WDEPTH    = 4;
constexpr int SEQ_WO    = 33;
constexpr int NSEQ      = 34;
constexpr int SLOT_WGU  = 4, SLOT_WD = 5;
constexpr int DLY_F     = 500;
constexpr int DLY_F_IDLE = 1100;
constexpr int RESET_TILE = 8;
constexpr int SAMPLE_NS = 100;
constexpr uint32_t SENT = 0xFFFFFFFFu;

constexpr int OFF_XN   = NSLOT * SLOT;
constexpr int XN_PITCH = 1040;
constexpr int OFF_QS   = OFF_XN + 4 * XN_PITCH;
constexpr int QS_PITCH = 272;
constexpr int OFF_P    = OFF_QS + 4 * QS_PITCH;
constexpr int OFF_RED  = OFF_P + 4 * QS_PITCH;
constexpr int OFF_MX   = OFF_RED + 4096;
constexpr int OFF_L    = OFF_MX + 64;
constexpr int OFF_ACT  = OFF_L + 128;
constexpr int OFF_RED2 = OFF_ACT + 128;
constexpr int OFF_CS   = OFF_RED2 + 512;
constexpr int OFF_ST   = OFF_CS + 512;
constexpr int OFF_BAR  = OFF_ST + 32;
constexpr int OFF_VAR  = OFF_BAR + 192;
constexpr int SMEM_USED = OFF_VAR + 64;
constexpr int SMEM_BYTES = SMEM_USED + 1024;
static_assert(OFF_RED % 16 == 0 && OFF_MX % 16 == 0 && OFF_ST % 8 == 0 && OFF_BAR % 8 == 0, "alignment");

__device__ uint2    g_q[4 * 2048];
__device__ float    g_partO[32 * 4 * 4 * 128];
__device__ float2   g_ml[32 * 4 * 4];
__device__ float    g_ypart[4 * 32 * 32 * 16];
__device__ uint16_t g_h[4 * 512];
__device__ float    g_dpart[4 * 32 * NFFN * 16];
__device__ unsigned g_cnt0, g_cnt1, g_prog;

__device__ __forceinline__ uint32_t smem_u32(const void* p) { return (uint32_t)__cvta_generic_to_shared(p); }
__device__ __forceinline__ void mbar_init(uint32_t bar, uint32_t cnt) {
    asm volatile("mbarrier.init.shared::cta.b64 [%0], %1;" ::"r"(bar), "r"(cnt) : "memory");
}
__device__ __forceinline__ void mbar_expect_tx(uint32_t bar, uint32_t bytes) {
    asm volatile("mbarrier.arrive.expect_tx.shared::cta.b64 _, [%0], %1;" ::"r"(bar), "r"(bytes) : "memory");
}
__device__ __forceinline__ void mbar_arrive(uint32_t bar) {
    asm volatile("mbarrier.arrive.shared::cta.b64 _, [%0];" ::"r"(bar) : "memory");
}
__device__ __forceinline__ bool mbar_try(uint32_t bar, uint32_t parity) {
    uint32_t ok;
    asm volatile("{\n.reg .pred p;\nmbarrier.try_wait.parity.shared::cta.b64 p, [%1], %2;\nselp.u32 %0, 1, 0, p;\n}"
                 : "=r"(ok) : "r"(bar), "r"(parity) : "memory");
    return ok != 0;
}
constexpr uint32_t SPIN_LIMIT = 1u << 22;
__device__ __forceinline__ void mbar_wait(uint32_t bar, uint32_t parity) {
    uint32_t it = 0;
    while (!mbar_try(bar, parity)) { if (++it > SPIN_LIMIT) __trap(); }
}
__device__ __forceinline__ void tma3d(uint32_t dst, const CUtensorMap* m, int c0, int c1, int c2, uint32_t bar, uint64_t pol) {
    asm volatile("cp.async.bulk.tensor.3d.shared::cluster.global.mbarrier::complete_tx::bytes.L2::cache_hint [%0], [%1, {%3, %4, %5}], [%2], %6;"
                 ::"r"(dst), "l"(m), "r"(bar), "r"(c0), "r"(c1), "r"(c2), "l"(pol) : "memory");
}
__device__ __forceinline__ void ldsm4(uint32_t (&r)[4], uint32_t addr) {
    asm volatile("ldmatrix.sync.aligned.m8n8.x4.shared.b16 {%0,%1,%2,%3}, [%4];"
                 : "=r"(r[0]), "=r"(r[1]), "=r"(r[2]), "=r"(r[3]) : "r"(addr) : "memory");
}
__device__ __forceinline__ void ldsm4t(uint32_t (&r)[4], uint32_t addr) {
    asm volatile("ldmatrix.sync.aligned.m8n8.x4.trans.shared.b16 {%0,%1,%2,%3}, [%4];"
                 : "=r"(r[0]), "=r"(r[1]), "=r"(r[2]), "=r"(r[3]) : "r"(addr) : "memory");
}
__device__ __forceinline__ void mma16816(float (&c)[4], const uint32_t (&a)[4], uint32_t b0, uint32_t b1) {
    asm volatile("mma.sync.aligned.m16n8k16.row.col.f32.bf16.bf16.f32 {%0,%1,%2,%3}, {%4,%5,%6,%7}, {%8,%9}, {%0,%1,%2,%3};"
                 : "+f"(c[0]), "+f"(c[1]), "+f"(c[2]), "+f"(c[3])
                 : "r"(a[0]), "r"(a[1]), "r"(a[2]), "r"(a[3]), "r"(b0), "r"(b1));
}
__device__ __forceinline__ void cbar() { asm volatile("bar.sync 1, 256;" ::: "memory"); }
__device__ __forceinline__ void bar_sync(int id, int n) { asm volatile("bar.sync %0, %1;" ::"r"(id), "r"(n) : "memory"); }
__device__ __forceinline__ void bar_arrive(int id, int n) { asm volatile("bar.arrive %0, %1;" ::"r"(id), "r"(n) : "memory"); }
__device__ __forceinline__ uint4 ld_poll4(const void* p) {
    uint4 v;
    asm volatile("ld.relaxed.gpu.global.v4.u32 {%0,%1,%2,%3}, [%4];" : "=r"(v.x), "=r"(v.y), "=r"(v.z), "=r"(v.w) : "l"(p) : "memory");
    return v;
}
__device__ __forceinline__ uint2 ld_poll2(const void* p) {
    uint2 v;
    asm volatile("ld.relaxed.gpu.global.v2.u32 {%0,%1}, [%2];" : "=r"(v.x), "=r"(v.y) : "l"(p) : "memory");
    return v;
}
__device__ __forceinline__ void st_rel32(void* p, uint32_t v) { asm volatile("st.relaxed.gpu.global.u32 [%0], %1;" ::"l"(p), "r"(v) : "memory"); }
__device__ __forceinline__ void st_rel16(void* p, uint16_t v) { asm volatile("st.relaxed.gpu.global.u16 [%0], %1;" ::"l"(p), "h"(v) : "memory"); }
__device__ __forceinline__ void st_rel64(void* p, uint32_t a, uint32_t b) { asm volatile("st.relaxed.gpu.global.v2.u32 [%0], {%1,%2};" ::"l"(p), "r"(a), "r"(b) : "memory"); }
__device__ __forceinline__ void st_rel128(void* p, uint32_t v) { asm volatile("st.relaxed.gpu.global.v4.u32 [%0], {%1,%1,%1,%1};" ::"l"(p), "r"(v) : "memory"); }
__device__ __forceinline__ uint32_t umax4(const uint4& v) { return max(max(v.x, v.y), max(v.z, v.w)); }
template <class T> __device__ __forceinline__ void pin(T*& p) { asm volatile("" : "+l"(p)); }
__device__ __forceinline__ bool valid8h(const uint4& v) {
    return (__vcmpeq2(v.x, SENT) | __vcmpeq2(v.y, SENT) | __vcmpeq2(v.z, SENT) | __vcmpeq2(v.w, SENT)) == 0;
}
struct Spin {
    uint32_t it = 0;
    __device__ __forceinline__ void tick() { if (++it > SPIN_LIMIT) __trap(); }
};
__device__ __forceinline__ void wait_progress(int n) {
    Spin sp; unsigned v;
    while (true) {
        asm volatile("ld.relaxed.gpu.global.u32 %0, [%1];" : "=r"(v) : "l"(&g_prog) : "memory");
        if ((int)v >= n) break;
        sp.tick(); __nanosleep(64);
    }
}
__device__ __forceinline__ uint32_t pack_bf16(float lo, float hi) {
    uint32_t r; asm("cvt.rn.bf16x2.f32 %0, %1, %2;" : "=r"(r) : "f"(hi), "f"(lo)); return r;
}
__device__ __forceinline__ void delay_cycles(int n) { if (n > 0) { const long long t0 = clock64(); while (clock64() - t0 < n) {} } }
__device__ __forceinline__ float bf16r(float x) { return __uint_as_float(pack_bf16(0.f, x) & 0xFFFF0000u); }
__device__ __forceinline__ float bf_lo(uint32_t v) { return __uint_as_float(v << 16); }
__device__ __forceinline__ float bf_hi(uint32_t v) { return __uint_as_float(v & 0xFFFF0000u); }
__device__ __forceinline__ uint32_t hmax2(uint32_t a, uint32_t b) {
    uint32_t r; asm("max.bf16x2 %0, %1, %2;" : "=r"(r) : "r"(a), "r"(b)); return r;
}
__device__ __forceinline__ float ex2(float x) { float r; asm("ex2.approx.ftz.f32 %0, %1;" : "=f"(r) : "f"(x)); return r; }

__device__ __forceinline__ float2 ln_stats(const uint4& a, const uint4& b, float (&v)[16]) {
    v[0] = bf_lo(a.x); v[1] = bf_hi(a.x); v[2] = bf_lo(a.y); v[3] = bf_hi(a.y);
    v[4] = bf_lo(a.z); v[5] = bf_hi(a.z); v[6] = bf_lo(a.w); v[7] = bf_hi(a.w);
    v[8] = bf_lo(b.x); v[9] = bf_hi(b.x); v[10] = bf_lo(b.y); v[11] = bf_hi(b.y);
    v[12] = bf_lo(b.z); v[13] = bf_hi(b.z); v[14] = bf_lo(b.w); v[15] = bf_hi(b.w);
    const float shift = __shfl_sync(0xffffffffu, v[0], 0);
    float s0 = 0.f, s1 = 0.f, s2 = 0.f, s3 = 0.f, q0 = 0.f, q1 = 0.f, q2 = 0.f, q3 = 0.f;
#pragma unroll
    for (int i = 0; i < 16; i += 4) {
        const float d0 = v[i] - shift, d1 = v[i + 1] - shift, d2 = v[i + 2] - shift, d3 = v[i + 3] - shift;
        s0 += d0; s1 += d1; s2 += d2; s3 += d3;
        q0 = fmaf(d0, d0, q0); q1 = fmaf(d1, d1, q1); q2 = fmaf(d2, d2, q2); q3 = fmaf(d3, d3, q3);
    }
    float s = (s0 + s1) + (s2 + s3), ss = (q0 + q1) + (q2 + q3);
#pragma unroll
    for (int o = 16; o > 0; o >>= 1) { s += __shfl_xor_sync(0xffffffffu, s, o); ss += __shfl_xor_sync(0xffffffffu, ss, o); }
    const float md = s * (1.0f / 512.0f);
    const float var = fmaxf(ss * (1.0f / 512.0f) - md * md, 0.f);
    const float m = bf16r(shift + md);
    float sq; asm("sqrt.approx.f32 %0, %1;" : "=f"(sq) : "f"(bf16r(bf16r(var) + 1e-5f)));
    const float sd = bf16r(sq);
    return make_float2(m, __fdividef(1.0f, sd));
}

struct Maps { CUtensorMap m[7]; };

__global__ void __launch_bounds__(NTHREADS, 1)
fused_decode_kernel(const __grid_constant__ Maps maps, const __nv_bfloat16* __restrict__ x, __nv_bfloat16* __restrict__ out)
{
    extern __shared__ __align__(1024) unsigned char smem_raw[];
    unsigned char* smem = smem_raw + ((1024u - (smem_u32(smem_raw) & 1023u)) & 1023u);
    const uint32_t sbase = smem_u32(smem);
    const uint32_t bar_full = sbase + OFF_BAR, bar_empty = sbase + OFF_BAR + 48, bar_ready = sbase + OFF_BAR + 96, bar_w = sbase + OFF_BAR + 104;
    volatile unsigned* vars = reinterpret_cast<volatile unsigned*>(smem + OFF_VAR);
    const int tid = threadIdx.x, warp = tid >> 5, lane = tid & 31;
    const int cta = blockIdx.x;

    uint4 xa = make_uint4(0, 0, 0, 0), xb = xa;
    float xres = 0.f;
    unsigned cnt0 = 0;
    if (warp < 4) {
        const uint4* xr = reinterpret_cast<const uint4*>(x + warp * 512);
        xa = __ldg(xr + lane); xb = __ldg(xr + 32 + lane);
        if (warp == 0) xres = __bfloat162float(x[(cta >> 5) * 512 + (cta & 31) * 16 + (lane >> 1)]);
        if (tid == 0) cnt0 = atomicAdd(&g_cnt0, 1u);
    } else if (warp == 7) {
        st_rel128(&g_q[(lane >> 3) * 2048 + cta * 16 + (lane & 7) * 2], 0u);
    }
    uint64_t pol;
    asm volatile("createpolicy.fractional.L2::evict_first.b64 %0, 1.0;" : "=l"(pol));
    if (__builtin_expect(tid == 256, 1)) {
        for (int i = 0; i < NSLOT; i++) { mbar_init(bar_full + 8 * i, 1); mbar_init(bar_empty + 8 * i, 8); }
        asm volatile("fence.mbarrier_init.release.cluster;" ::: "memory");
        mbar_expect_tx(bar_full, 32768);
        tma3d(sbase, &maps.m[2], cta * 32, 0, 0, bar_full, pol);
        tma3d(sbase + 16384, &maps.m[2], cta * 32, 256, 0, bar_full, pol);
        mbar_expect_tx(bar_full + 8, 32768);
        tma3d(sbase + SLOT, &maps.m[0], 0, cta * (NTILE * 128), 0, bar_full + 8, pol);
        mbar_expect_tx(bar_full + 16, 32768);
        tma3d(sbase + 2 * SLOT, &maps.m[1], 0, cta * (NTILE * 128), 0, bar_full + 16, pol);
        asm volatile("red.relaxed.gpu.global.add.u32 [%0], 2;" ::"l"(&g_prog) : "memory");
        mbar_init(bar_ready, 1);
        for (int i = 0; i < 6; i++) mbar_init(bar_w + 8 * i, 1);
        vars[1] = 0; vars[2] = 0; vars[3] = 0;
        asm volatile("fence.mbarrier_init.release.cluster;" ::: "memory");
    } else if (tid > 256 && tid <= 263) {
        asm volatile("prefetch.tensormap [%0];" ::"l"(&maps.m[tid - 257]) : "memory");
    }
    if (warp == 8) { __syncwarp(); bar_arrive(8, NTHREADS); } else bar_sync(8, NTHREADS);

    if (warp == 8) {
        if (lane == 0) {
            const int key0 = cta * (NTILE * 128);
            int arrived = 0;
            int nkv = 2;
            const int nseq = (cta < NFFN) ? NSEQ + 6 : NSEQ;
            for (int i = 3; i < nseq; i++) {
                uint32_t dst, fb, bytes = 32768;
                int mi, c0 = 0, c1, c2 = 0;
                if (i < NSEQ) {
                    const int slot = i % NSLOT;
                    if (i >= NSLOT) mbar_wait(bar_empty + 8 * slot, ((i / NSLOT) - 1) & 1);
                    const int grel = (int)vars[2];
                    const int lead8 = (nkv * NCTA - grel) / (NCTA / 8);
                    const int d = (lead8 > LEAD_THR8) ? DEPTH_LO : DEPTH_HI;
                    while (arrived < i - d + 1) { mbar_wait(bar_full + 8 * (arrived % NSLOT), (arrived / NSLOT) & 1); arrived++; }
                    dst = sbase + slot * SLOT; fb = bar_full + 8 * slot;
                    if (i == SEQ_WO) { mi = 3; c1 = (cta >> 2) * 128; c2 = (cta & 3) * 2; }
                    else             { mi = nkv & 1; c1 = key0 + (nkv >> 1) * 128; }
                } else {
                    const int k = i - NSEQ;
                    if (k == 0) {
                        mbar_wait(bar_empty + 8 * SLOT_WGU, (34 / NSLOT - 1) & 1);
                        mbar_wait(bar_empty + 8 * SLOT_WD, (35 / NSLOT - 1) & 1);
                    }
                    if (k >= WDEPTH) mbar_wait(bar_w + 8 * (k - WDEPTH), 0);
                    dst = sbase + SLOT_WGU * SLOT + k * 8192; fb = bar_w + 8 * k; bytes = 8192;
                    mi = (k < 4) ? 4 + (k >> 1) : 6;
                    c0 = (k < 4) ? cta * 16 : 0; c1 = (k < 4) ? (k & 1) * 256 : cta * 16; c2 = (k < 4) ? 0 : (k - 4) * 4;
                }
                const int need = (i == SEQ_WO) ? NCTA * 32 - WO_MARGIN : (i == NSEQ) ? NCTA * 32 : 0;
                if ((int)vars[2] < need) wait_progress(need);
                if (i == NSEQ) mbar_wait(bar_full + 8 * (SEQ_WO % NSLOT), (SEQ_WO / NSLOT) & 1);
                mbar_expect_tx(fb, bytes);
                tma3d(dst, &maps.m[mi], c0, c1, c2, fb, pol);
                if (i < SEQ_WO) {
                    asm volatile("red.relaxed.gpu.global.add.u32 [%0], 1;" ::"l"(&g_prog) : "memory");
                    nkv++;
                }
                if (i == SEQ_WO) vars[3] = 1;
            }
        }
        return;
    }

    const int pair = cta >> 2, split = cta & 3;

    if (warp == 9) {
        Spin sp;
        auto sample = [&]() {
            unsigned v;
            asm volatile("ld.relaxed.gpu.global.u32 %0, [%1];" : "=r"(v) : "l"(&g_prog) : "memory");
            if (lane == 0) vars[2] = v;
        };
        while (vars[1] < RESET_TILE) { sp.tick(); sample(); __nanosleep(SAMPLE_NS); }
        const unsigned epoch = vars[0];
#pragma unroll 1
        for (int u = lane; u < 128; u += 32) {
            st_rel128(&g_partO[((pair * 4 + (u >> 5)) * 4 + split) * 128 + (u & 31) * 4], SENT);
            const int seg = u >> 2;
            st_rel128(&g_ypart[(((seg >> 3) * 32 + (cta & 3) * 8 + (seg & 7)) * 32 + (cta >> 2)) * 16 + (u & 3) * 4], SENT);
        }
        if (lane < 4) st_rel64(&g_ml[(pair * 4 + lane) * 4 + split], SENT, SENT);
        if (lane < 2) st_rel128(&g_h[(cta >> 5) * 512 + (cta & 31) * 16 + lane * 8], SENT);
        if (cta < NFFN) {
#pragma unroll 1
            for (int e = lane; e < 512; e += 32) st_rel128(&g_dpart[((e >> 2) * NFFN + cta) * 16 + (e & 3) * 4], SENT);
        }
        __threadfence();
        __syncwarp();
        if (lane == 0) {
            atomicAdd(&g_cnt1, 1u);
            unsigned v; Spin sp2;
            while (true) {
                asm volatile("ld.acquire.gpu.global.u32 %0, [%1];" : "=r"(v) : "l"(&g_cnt1) : "memory");
                if ((int)(v - (epoch + 1) * NCTA) >= 0) break;
                sp2.tick(); sample(); __nanosleep(128);
            }
            mbar_arrive(bar_ready);
        }
        __syncwarp();
        while (vars[3] == 0) { sp.tick(); sample(); __nanosleep(SAMPLE_NS); }
        return;
    }

    const int r8 = lane >> 2, q4 = lane & 3;
    const int hp = q4 & 1, kh = q4 >> 1;
    constexpr float LOG2E = 1.4426950408889634f;
    const int bq = pair >> 3, gq = pair & 7;

    if (tid == 0) vars[0] = cnt0 >> 7;

    if (warp < 4) {
        float v[16];
        const float2 st = ln_stats(xa, xb, v);
        uint32_t o[8];
#pragma unroll
        for (int i = 0; i < 8; i++) o[i] = pack_bf16(bf16r(v[2 * i] - st.x) * st.y, bf16r(v[2 * i + 1] - st.x) * st.y);
        unsigned char* row = smem + OFF_XN + warp * XN_PITCH;
        *reinterpret_cast<uint4*>(row + lane * 16) = make_uint4(o[0], o[1], o[2], o[3]);
        *reinterpret_cast<uint4*>(row + 512 + lane * 16) = make_uint4(o[4], o[5], o[6], o[7]);
    }
    cbar();
    const uint32_t tag = vars[0] + 1;

    {
        uint32_t bfr[4][2];
        {
            uint32_t t4[4];
#pragma unroll
            for (int u = 0; u < 2; u++) {
                ldsm4(t4, sbase + OFF_XN + (lane & 3) * XN_PITCH + (8 * warp + 4 * u + (lane >> 3)) * 16);
                bfr[2 * u][0] = t4[0]; bfr[2 * u][1] = t4[1]; bfr[2 * u + 1][0] = t4[2]; bfr[2 * u + 1][1] = t4[3];
            }
        }
        mbar_wait(bar_full + 0, 0);
        float acc[2][4] = {};
#pragma unroll
        for (int ks = 0; ks < 4; ks++) {
            const int k = 64 * warp + 16 * ks + (lane & 7) + (lane >> 4) * 8;
#pragma unroll
            for (int mt = 0; mt < 2; mt++) {
                uint32_t a[4];
                const int chunk = 2 * mt + ((lane >> 3) & 1);
                ldsm4t(a, sbase + k * 64 + ((chunk ^ ((k >> 1) & 3)) << 4));
                mma16816(acc[mt], a, bfr[ks][0], bfr[ks][1]);
            }
        }
        __syncwarp();
        if (lane == 0) mbar_arrive(bar_empty + 0);
        float* red = reinterpret_cast<float*>(smem + OFF_RED);
#pragma unroll
        for (int mt = 0; mt < 2; mt++) {
            float2 v = kh ? make_float2(acc[mt][2], acc[mt][3]) : make_float2(acc[mt][0], acc[mt][1]);
            *reinterpret_cast<float2*>(red + ((warp * 2 + mt) * 16 + r8 + 8 * kh) * 4 + 2 * hp) = v;
        }
        cbar();
        if (tid < 64) {
            const int b = tid >> 4, c2 = tid & 15;
            float s0 = 0.f, s1 = 0.f;
            const int c0 = 2 * c2, c1 = 2 * c2 + 1;
#pragma unroll
            for (int ww = 0; ww < 8; ww++) {
                s0 += red[((ww * 2 + (c0 >> 4)) * 16 + (c0 & 15)) * 4 + b];
                s1 += red[((ww * 2 + (c1 >> 4)) * 16 + (c1 & 15)) * 4 + b];
            }
            st_rel64(&g_q[b * 2048 + cta * 16 + c2], pack_bf16(s0, s1), tag);
        }
        {
            const uint2* src = &g_q[bq * 2048 + gq * 256 + tid];
            uint2 v;
            Spin sp;
            while (true) { v = ld_poll2(src); if (__all_sync(0xffffffffu, v.y == tag)) break; sp.tick(); }
            *reinterpret_cast<uint32_t*>(smem + OFF_QS + (tid >> 6) * QS_PITCH + (tid & 63) * 4) = v.x;
        }
        cbar();
    }
    uint32_t qf[8][2];
    {
        uint32_t t4[4];
#pragma unroll
        for (int u = 0; u < 4; u++) {
            ldsm4(t4, sbase + OFF_QS + (lane & 3) * QS_PITCH + (4 * u + (lane >> 3)) * 16);
            qf[2 * u][0] = t4[0]; qf[2 * u][1] = t4[1]; qf[2 * u + 1][0] = t4[2]; qf[2 * u + 1][1] = t4[3];
        }
    }

    const uint32_t voff = (warp >> 2) * 16384 + ((lane & 7) + (lane >> 4) * 8) * 128 +
                          ((((2 * warp + ((lane >> 3) & 1)) & 7) ^ (lane & 7)) << 4);
    const uint32_t poff = sbase + OFF_P + (lane & 3) * QS_PITCH + (lane >> 3) * 16;
    const uint32_t koff = (16 * warp + (lane & 7) + ((lane >> 3) & 1) * 8) * 128;
    const uint32_t kx = lane & 7, kc = lane >> 4;
    constexpr float SCALE = 0.08838834764831845f;
    uint32_t* mxbuf = reinterpret_cast<uint32_t*>(smem + OFF_MX);
    uint32_t M2 = 0xFF80FF80u;
    float l0 = 0.f, l1 = 0.f;
    float oacc[2][4] = {};
    int slot = 1; uint32_t ph = 0;

    for (int t = 0;; t++) {
        mbar_wait(bar_full + 8 * slot, ph);
        float sa[4] = {}, sb[4] = {};
        {
            const uint32_t kb = sbase + slot * SLOT + koff;
#pragma unroll
            for (int ks = 0; ks < 8; ks++) {
                uint32_t a[4];
                ldsm4(a, kb + (ks >> 2) * 16384 + (((2 * (ks & 3) + kc) ^ kx) << 4));
                if (ks & 1) mma16816(sb, a, qf[ks][0], qf[ks][1]); else mma16816(sa, a, qf[ks][0], qf[ks][1]);
            }
        }
        __syncwarp();
        if (lane == 0) mbar_arrive(bar_empty + 8 * slot);
        if (++slot == NSLOT) { slot = 0; ph ^= 1; }

        const float r0 = kh ? sa[2] + sb[2] : sa[0] + sb[0];
        const float r1 = kh ? sa[3] + sb[3] : sa[1] + sb[1];
        uint32_t sp = pack_bf16(r0, r1);
        sp = pack_bf16(bf_lo(sp) * SCALE, bf_hi(sp) * SCALE);
        uint32_t mx = sp;
#pragma unroll
        for (int o = 2; o <= 16; o <<= 1) mx = hmax2(mx, __shfl_xor_sync(0xffffffffu, mx, o));
        if (lane < 2) mxbuf[lane * 8 + warp] = mx;
        if (tid == 0) vars[1] = t + 1;
        cbar();
        {
            const uint4 m0 = *reinterpret_cast<const uint4*>(mxbuf + hp * 8), m1 = *reinterpret_cast<const uint4*>(mxbuf + hp * 8 + 4);
            uint32_t mt = hmax2(hmax2(hmax2(m0.x, m0.y), hmax2(m0.z, m0.w)), hmax2(hmax2(m1.x, m1.y), hmax2(m1.z, m1.w)));
            const uint32_t Mn = hmax2(M2, mt);
            const float a0 = ex2((bf_lo(M2) - bf_lo(Mn)) * LOG2E), a1 = ex2((bf_hi(M2) - bf_hi(Mn)) * LOG2E);
            const float p0 = ex2((bf_lo(sp) - bf_lo(Mn)) * LOG2E), p1 = ex2((bf_hi(sp) - bf_hi(Mn)) * LOG2E);
            M2 = Mn;
            l0 = fmaf(l0, a0, p0); l1 = fmaf(l1, a1, p1);
            const uint32_t pp = pack_bf16(p0, p1);
            unsigned char* pd = smem + OFF_P + (2 * hp) * QS_PITCH + (16 * warp + r8 + 8 * kh) * 2;
            *reinterpret_cast<uint16_t*>(pd) = (uint16_t)(pp & 0xFFFF);
            *reinterpret_cast<uint16_t*>(pd + QS_PITCH) = (uint16_t)(pp >> 16);
#pragma unroll
            for (int c = 0; c < 2; c++) { oacc[c][0] *= a0; oacc[c][1] *= a1; oacc[c][2] *= a0; oacc[c][3] *= a1; }
        }
        if (t == NTILE - 1) break;
        cbar();
        uint32_t pb[8][2];
        {
            uint32_t t4[4];
#pragma unroll
            for (int u = 0; u < 4; u++) {
                ldsm4(t4, poff + u * 64);
                pb[2 * u][0] = t4[0]; pb[2 * u][1] = t4[1]; pb[2 * u + 1][0] = t4[2]; pb[2 * u + 1][1] = t4[3];
            }
        }
        mbar_wait(bar_full + 8 * slot, ph);
        {
            const uint32_t vb = sbase + slot * SLOT + voff;
#pragma unroll
            for (int ks = 0; ks < 8; ks++) {
                uint32_t a[4];
                ldsm4t(a, vb + ks * 2048);
                mma16816(oacc[ks & 1], a, pb[ks][0], pb[ks][1]);
            }
        }
        __syncwarp();
        if (lane == 0) mbar_arrive(bar_empty + 8 * slot);
        if (++slot == NSLOT) { slot = 0; ph ^= 1; }
    }

    const int head = cta >> 2;
    float* p_partO = &g_partO[((pair * 4 + 2 * hp) * 4 + split) * 128 + 16 * warp + r8 + 8 * kh];
    float* p_dpart = &g_dpart[(((2 * hp) * 32 + 4 * warp) * NFFN + cta) * 16 + r8 + 8 * kh];
    const float* p_dsrc = &g_dpart[(cta * NFFN + (tid >> 2)) * 16 + (tid & 3) * 4];
    __nv_bfloat16* p_out = out + (cta >> 5) * 512 + (cta & 31) * 16 + (lane >> 1);
    pin(p_partO); pin(p_dpart); pin(p_dsrc); pin(p_out);

    {
        float s0 = l0, s1 = l1;
#pragma unroll
        for (int o = 2; o <= 16; o <<= 1) { s0 += __shfl_xor_sync(0xffffffffu, s0, o); s1 += __shfl_xor_sync(0xffffffffu, s1, o); }
        if (lane < 2) *reinterpret_cast<float2*>(smem + OFF_L + warp * 16 + lane * 8) = make_float2(s0, s1);
        mbar_wait(bar_ready, 0);
        cbar();
        if (warp == 0) {
            const uint32_t other = __shfl_sync(0xffffffffu, M2, lane >> 1);
            float l = 0.f;
#pragma unroll
            for (int ww = 0; ww < 8; ww++) l += *reinterpret_cast<const float*>(smem + OFF_L + ww * 16 + (lane & 3) * 4);
            const float m = (lane & 1) ? bf_hi(other) : bf_lo(other);
            if (lane < 4) st_rel64(&g_ml[(pair * 4 + lane) * 4 + split], __float_as_uint(m), __float_as_uint(l));
        }
        uint32_t pb[8][2];
        {
            uint32_t t4[4];
#pragma unroll
            for (int u = 0; u < 4; u++) {
                ldsm4(t4, poff + u * 64);
                pb[2 * u][0] = t4[0]; pb[2 * u][1] = t4[1]; pb[2 * u + 1][0] = t4[2]; pb[2 * u + 1][1] = t4[3];
            }
        }
        float o2[2][4] = {};
        {
            mbar_wait(bar_full + 8 * slot, ph);
            const uint32_t vb = sbase + slot * SLOT + voff;
            uint32_t a[8][4];
#pragma unroll
            for (int ks = 0; ks < 8; ks++) ldsm4t(a[ks], vb + ks * 2048);
#pragma unroll
            for (int ks = 0; ks < 8; ks++) mma16816((ks & 2) ? o2[ks & 1] : oacc[ks & 1], a[ks], pb[ks][0], pb[ks][1]);
        }
        const float v0 = kh ? (oacc[0][2] + oacc[1][2]) + (o2[0][2] + o2[1][2]) : (oacc[0][0] + oacc[1][0]) + (o2[0][0] + o2[1][0]);
        const float v1 = kh ? (oacc[0][3] + oacc[1][3]) + (o2[0][3] + o2[1][3]) : (oacc[0][1] + oacc[1][1]) + (o2[0][1] + o2[1][1]);
        st_rel32(p_partO, __float_as_uint(v0));
        st_rel32(p_partO + 512, __float_as_uint(v1));
    }

    float hres = 0.f;
    uint32_t df[4][4];
    if (warp < 4) {
        {
            const int ph_idx = (warp * 8 + (head >> 2)) * 4 + (head & 3);
            const float* po = &g_partO[ph_idx * 512 + lane * 4];
            const float* pm = reinterpret_cast<const float*>(&g_ml[ph_idx * 4]);
            uint4 o0, o1, o2, o3, ma, mb;
            Spin sp;
            while (true) {
                o0 = ld_poll4(po); o1 = ld_poll4(po + 128); o2 = ld_poll4(po + 256); o3 = ld_poll4(po + 384);
                ma = ld_poll4(pm); mb = ld_poll4(pm + 4);
                const uint32_t mxv = max(max(max(umax4(o0), umax4(o1)), max(umax4(o2), umax4(o3))), max(umax4(ma), umax4(mb)));
                if (__all_sync(0xffffffffu, mxv != SENT)) break;
                sp.tick();
            }
            const float m0 = __uint_as_float(ma.x), m1 = __uint_as_float(ma.z), m2 = __uint_as_float(mb.x), m3 = __uint_as_float(mb.z);
            const float M = fmaxf(fmaxf(m0, m1), fmaxf(m2, m3));
            float w0 = ex2((m0 - M) * LOG2E), w1 = ex2((m1 - M) * LOG2E), w2 = ex2((m2 - M) * LOG2E), w3 = ex2((m3 - M) * LOG2E);
            const float L = w0 * __uint_as_float(ma.y) + w1 * __uint_as_float(ma.w) + w2 * __uint_as_float(mb.y) + w3 * __uint_as_float(mb.w);
            const float inv = __fdividef(1.0f, L);
            const float e0 = (w0 * __uint_as_float(o0.x) + w1 * __uint_as_float(o1.x) + w2 * __uint_as_float(o2.x) + w3 * __uint_as_float(o3.x)) * inv;
            const float e1 = (w0 * __uint_as_float(o0.y) + w1 * __uint_as_float(o1.y) + w2 * __uint_as_float(o2.y) + w3 * __uint_as_float(o3.y)) * inv;
            const float e2 = (w0 * __uint_as_float(o0.z) + w1 * __uint_as_float(o1.z) + w2 * __uint_as_float(o2.z) + w3 * __uint_as_float(o3.z)) * inv;
            const float e3 = (w0 * __uint_as_float(o0.w) + w1 * __uint_as_float(o1.w) + w2 * __uint_as_float(o2.w) + w3 * __uint_as_float(o3.w)) * inv;
            *reinterpret_cast<uint2*>(smem + OFF_QS + warp * QS_PITCH + lane * 8) = make_uint2(pack_bf16(e0, e1), pack_bf16(e2, e3));
            bar_arrive(2, 256);
        }
        {
            const float* src = &g_ypart[(cta * 32 + 8 * warp + (lane >> 2)) * 16 + (lane & 3) * 4];
            uint16_t* p_h = &g_h[(cta >> 5) * 512 + (cta & 31) * 16 + (lane >> 1)];
            pin(p_h);
            uint4 y;
            Spin sp;
            while (true) {
                y = ld_poll4(src);
                if (__all_sync(0xffffffffu, umax4(y) != SENT)) break;
                sp.tick();
            }
            const bool up = lane & 16, up2 = lane & 8;
            const float a0 = __uint_as_float(y.x), a1 = __uint_as_float(y.y), a2 = __uint_as_float(y.z), a3 = __uint_as_float(y.w);
            const float v0 = (up ? a2 : a0) + __shfl_xor_sync(0xffffffffu, up ? a0 : a2, 16);
            const float v1 = (up ? a3 : a1) + __shfl_xor_sync(0xffffffffu, up ? a1 : a3, 16);
            float v = (up2 ? v1 : v0) + __shfl_xor_sync(0xffffffffu, up2 ? v0 : v1, 8);
            v += __shfl_xor_sync(0xffffffffu, v, 4);
            float* rc = reinterpret_cast<float*>(smem + OFF_RED2);
            if (!(lane & 4)) rc[warp * 16 + 4 * (lane & 3) + (up ? 2 : 0) + (up2 ? 1 : 0)] = v;
            bar_sync(7, 128);
            if (warp == 0) {
                const float* r2 = rc + (lane & 1) * 32 + (lane >> 1);
                float t = r2[0] + r2[16];
                t += __shfl_xor_sync(0xffffffffu, t, 1);
                hres = bf16r(xres + bf16r(t));
                if (!(lane & 1)) st_rel16(p_h, (uint16_t)(__float_as_uint(hres) >> 16));
            }
        }
        {
            const uint4* hr = reinterpret_cast<const uint4*>(g_h + warp * 512);
            uint4 a, b;
            Spin sp;
            while (true) {
                a = ld_poll4(hr + lane); b = ld_poll4(hr + 32 + lane);
                if (__all_sync(0xffffffffu, valid8h(a) & valid8h(b))) break;
                sp.tick();
            }
            if (cta < NFFN) {
                unsigned char* row = smem + OFF_XN + warp * XN_PITCH;
                *reinterpret_cast<uint4*>(row + lane * 16) = a;
                *reinterpret_cast<uint4*>(row + 512 + lane * 16) = b;
                bar_arrive(3, 256);
                float v[16];
                const float2 st = ln_stats(a, b, v);
                if (lane == 0) *reinterpret_cast<float2*>(smem + OFF_ST + warp * 8) = st;
                bar_arrive(4, 256);
                mbar_wait(bar_w + 32, 0); mbar_wait(bar_w + 40, 0);
                const uint32_t wb = sbase + SLOT_WD * SLOT + warp * 2048 + ((lane & 7) + (lane >> 4) * 8) * 128;
#pragma unroll
                for (int i = 0; i < 4; i++) ldsm4t(df[i], wb + (((2 * i + ((lane >> 3) & 1)) ^ (lane & 7)) << 4));
            }
        }
    } else {
        const int m = warp - 4;
        {
            uint32_t af[2][8][4];
            float* p_y = &g_ypart[(((2 * hp) * 32 + (cta & 3) * 8 + 2 * m) * 32 + head) * 16 + r8 + 8 * kh];
            pin(p_y);
            mbar_wait(bar_full + 8 * (SEQ_WO % NSLOT), (SEQ_WO / NSLOT) & 1);
#pragma unroll
            for (int i = 0; i < 2; i++) {
                const int j = 2 * m + i;
                const uint32_t wb = sbase + (SEQ_WO % NSLOT) * SLOT + (j >> 2) * 16384 + ((lane & 7) + (lane >> 4) * 8) * 128 +
                                    ((((2 * j + ((lane >> 3) & 1)) & 7) ^ (lane & 7)) << 4);
#pragma unroll
                for (int ks = 0; ks < 8; ks++) ldsm4t(af[i][ks], wb + ks * 2048);
            }
            bar_sync(2, 256);
            float acc[2][2][4] = {};
            uint32_t t4[4][4];
#pragma unroll
            for (int u = 0; u < 4; u++) ldsm4(t4[u], sbase + OFF_QS + (lane & 3) * QS_PITCH + (4 * u + (lane >> 3)) * 16);
#pragma unroll
            for (int u = 0; u < 4; u++) {
#pragma unroll
                for (int i = 0; i < 2; i++) {
                    mma16816(acc[i][0], af[i][2 * u], t4[u][0], t4[u][1]);
                    mma16816(acc[i][1], af[i][2 * u + 1], t4[u][2], t4[u][3]);
                }
            }
#pragma unroll
            for (int i = 0; i < 2; i++) {
                const float v0 = kh ? acc[i][0][2] + acc[i][1][2] : acc[i][0][0] + acc[i][1][0];
                const float v1 = kh ? acc[i][0][3] + acc[i][1][3] : acc[i][0][1] + acc[i][1][1];
                st_rel32(p_y + i * 32 * 16, __float_as_uint(v0));
                st_rel32(p_y + i * 32 * 16 + 32 * 32 * 16, __float_as_uint(v1));
            }
        }
        if (cta < NFFN) {
            uint32_t gf[8][2][4];
            mbar_wait(bar_w, 0); mbar_wait(bar_w + 8, 0); mbar_wait(bar_w + 16, 0); mbar_wait(bar_w + 24, 0);
#pragma unroll
            for (int ks = 0; ks < 8; ks++) {
                const int k = 128 * m + 16 * ks + (lane & 7) + (lane >> 4) * 8;
                const uint32_t a = sbase + SLOT_WGU * SLOT + k * 32 + ((((lane >> 3) & 1) ^ ((k >> 2) & 1)) << 4);
                ldsm4t(gf[ks][0], a);
                ldsm4t(gf[ks][1], a + 16384);
            }
            float sg = 0.f, su = 0.f;
            {
                float cs[2][4] = {};
#pragma unroll
                for (int ks = 0; ks < 8; ks++) { mma16816(cs[0], gf[ks][0], 0x3F803F80u, 0x3F803F80u); mma16816(cs[1], gf[ks][1], 0x3F803F80u, 0x3F803F80u); }
                float* csb = reinterpret_cast<float*>(smem + OFF_CS);
                if (q4 == 0) {
                    csb[(m * 2 + 0) * 16 + r8] = cs[0][0]; csb[(m * 2 + 0) * 16 + r8 + 8] = cs[0][2];
                    csb[(m * 2 + 1) * 16 + r8] = cs[1][0]; csb[(m * 2 + 1) * 16 + r8 + 8] = cs[1][2];
                }
                bar_sync(5, 128);
                const int c = (tid & 63) >> 2;
#pragma unroll
                for (int ww = 0; ww < 4; ww++) { sg += csb[(ww * 2) * 16 + c]; su += csb[(ww * 2 + 1) * 16 + c]; }
            }
            const uint32_t wdb = sbase + SLOT_WD * SLOT + warp * 2048 + ((lane & 7) + (lane >> 4) * 8) * 128;
            const bool have_wd = __all_sync(0xffffffffu, mbar_try(bar_w + 32, 0) && mbar_try(bar_w + 40, 0));
            if (have_wd) {
#pragma unroll
                for (int i = 0; i < 4; i++) ldsm4t(df[i], wdb + (((2 * i + ((lane >> 3) & 1)) ^ (lane & 7)) << 4));
            }
            bar_sync(3, 256);
            float acc[2][2][4] = {};
            uint32_t t4[4][4];
#pragma unroll
            for (int u = 0; u < 4; u++) ldsm4(t4[u], sbase + OFF_XN + (lane & 3) * XN_PITCH + (16 * m + 4 * u + (lane >> 3)) * 16);
#pragma unroll
            for (int u = 0; u < 4; u++) {
#pragma unroll
                for (int i = 0; i < 2; i++) {
                    mma16816(acc[i][0], gf[2 * u][i], t4[u][0], t4[u][1]);
                    mma16816(acc[i][1], gf[2 * u + 1][i], t4[u][2], t4[u][3]);
                }
            }
            float* red = reinterpret_cast<float*>(smem + OFF_RED);
#pragma unroll
            for (int i = 0; i < 2; i++) {
                const float2 v = kh ? make_float2(acc[i][0][2] + acc[i][1][2], acc[i][0][3] + acc[i][1][3])
                                    : make_float2(acc[i][0][0] + acc[i][1][0], acc[i][0][1] + acc[i][1][1]);
                *reinterpret_cast<float2*>(red + ((m * 2 + i) * 16 + r8 + 8 * kh) * 4 + 2 * hp) = v;
            }
            bar_sync(4, 256);
            if (tid < 192) {
                const int c = (tid & 63) >> 2, b = tid & 3;
                const float2 st = *reinterpret_cast<const float2*>(smem + OFF_ST + b * 8);
                float g = 0.f, u = 0.f;
#pragma unroll
                for (int ww = 0; ww < 4; ww++) { g += red[((ww * 2) * 16 + c) * 4 + b]; u += red[((ww * 2 + 1) * 16 + c) * 4 + b]; }
                g = bf16r((g - st.x * sg) * st.y); u = bf16r((u - st.x * su) * st.y);
                const float inner = 0.7978845608028654f * (g + 0.044715f * g * g * g);
                const float th = 1.0f - __fdividef(2.0f, __expf(2.0f * inner) + 1.0f);
                const float ge = bf16r(0.5f * g * (1.0f + th));
                *reinterpret_cast<__nv_bfloat16*>(smem + OFF_ACT + b * 32 + c * 2) = __float2bfloat16_rn(ge * u);
            }
            if (!have_wd) {
                mbar_wait(bar_w + 32, 0); mbar_wait(bar_w + 40, 0);
#pragma unroll
                for (int i = 0; i < 4; i++) ldsm4t(df[i], wdb + (((2 * i + ((lane >> 3) & 1)) ^ (lane & 7)) << 4));
            }
        }
    }
    if (cta < NFFN) {
        bar_sync(6, 256);
        const uint32_t b0 = *reinterpret_cast<const uint32_t*>(smem + OFF_ACT + (r8 & 3) * 32 + q4 * 4);
        const uint32_t b1 = *reinterpret_cast<const uint32_t*>(smem + OFF_ACT + (r8 & 3) * 32 + 16 + q4 * 4);
        float c[4][4] = {};
#pragma unroll
        for (int i = 0; i < 4; i++) mma16816(c[i], df[i], b0, b1);
#pragma unroll
        for (int i = 0; i < 4; i++) {
            st_rel32(p_dpart + i * NFFN * 16, __float_as_uint(kh ? c[i][2] : c[i][0]));
            st_rel32(p_dpart + i * NFFN * 16 + 32 * NFFN * 16, __float_as_uint(kh ? c[i][3] : c[i][1]));
        }
    } else {
        bar_sync(6, 256);
        delay_cycles(DLY_F_IDLE);
    }

    {
        const int quad = tid & 3;
        const bool two = (tid >> 2) + 64 < NFFN;
        uint4 a, b = make_uint4(0, 0, 0, 0);
        Spin sp;
        delay_cycles(DLY_F);
        while (true) {
            a = ld_poll4(p_dsrc);
            if (two) b = ld_poll4(p_dsrc + 64 * 16);
            if (__all_sync(0xffffffffu, max(umax4(a), umax4(b)) != SENT)) break;
            sp.tick();
        }
        float v[4] = {__uint_as_float(a.x) + __uint_as_float(b.x), __uint_as_float(a.y) + __uint_as_float(b.y),
                      __uint_as_float(a.z) + __uint_as_float(b.z), __uint_as_float(a.w) + __uint_as_float(b.w)};
        {
            const bool up = lane & 16;
            const float s0 = up ? v[0] : v[2], s1 = up ? v[1] : v[3];
            const float k0 = up ? v[2] : v[0], k1 = up ? v[3] : v[1];
            v[0] = k0 + __shfl_xor_sync(0xffffffffu, s0, 16);
            v[1] = k1 + __shfl_xor_sync(0xffffffffu, s1, 16);
            const bool up2 = lane & 8;
            const float s = up2 ? v[0] : v[1], k = up2 ? v[1] : v[0];
            v[0] = k + __shfl_xor_sync(0xffffffffu, s, 8);
            v[0] += __shfl_xor_sync(0xffffffffu, v[0], 4);
            if (!(lane & 4)) reinterpret_cast<float*>(smem + OFF_RED2)[warp * 16 + 4 * quad + ((lane & 16) ? 2 : 0) + ((lane & 8) ? 1 : 0)] = v[0];
        }
        cbar();
        if (warp == 0) {
            const float* r2 = reinterpret_cast<const float*>(smem + OFF_RED2) + (lane & 1) * 64 + (lane >> 1);
            float s = (r2[0] + r2[16]) + (r2[32] + r2[48]);
            s += __shfl_xor_sync(0xffffffffu, s, 1);
            if (!(lane & 1)) *p_out = __float2bfloat16_rn(hres + bf16r(s));
            if (cta == 0 && lane == 0) st_rel32(&g_prog, 0u);
        }
    }
}

typedef CUresult (*EncodeFn)(CUtensorMap*, CUtensorMapDataType, cuuint32_t, void*, const cuuint64_t*, const cuuint64_t*,
                             const cuuint32_t*, const cuuint32_t*, CUtensorMapInterleave, CUtensorMapSwizzle,
                             CUtensorMapL2promotion, CUtensorMapFloatOOBfill);

void encode(EncodeFn fn, CUtensorMap* m, const void* base, int rank, const cuuint64_t* dims, const cuuint64_t* strides,
            const cuuint32_t* box, CUtensorMapSwizzle sw, CUtensorMapL2promotion promo) {
    cuuint32_t es[3] = {1, 1, 1};
    fn(m, CU_TENSOR_MAP_DATA_TYPE_BFLOAT16, (cuuint32_t)rank, const_cast<void*>(base), dims, strides, box, es,
       CU_TENSOR_MAP_INTERLEAVE_NONE, sw, promo, CU_TENSOR_MAP_FLOAT_OOB_FILL_NONE);
}

}

extern "C" void kernel_launch(void* const* d_in, const int* in_sizes, int n_in, void* d_out, int out_size) {
    (void)in_sizes; (void)n_in; (void)out_size;
    static EncodeFn enc = nullptr;
    if (!enc) {
        void* fn = nullptr;
        cudaDriverEntryPointQueryResult qr;
        cudaGetDriverEntryPoint("cuTensorMapEncodeTiled", &fn, cudaEnableDefault, &qr);
        enc = (EncodeFn)fn;
        cudaFuncSetAttribute(fused_decode_kernel, cudaFuncAttributeMaxDynamicSharedMemorySize, SMEM_BYTES);
    }
    const void* x = d_in[0];
    Maps maps;
    {
        cuuint64_t dims[3] = {64, 262144, 2}; cuuint64_t str[2] = {256, 128}; cuuint32_t box[3] = {64, 128, 2};
        encode(enc, &maps.m[0], d_in[1], 3, dims, str, box, CU_TENSOR_MAP_SWIZZLE_128B, CU_TENSOR_MAP_L2_PROMOTION_L2_256B);
        encode(enc, &maps.m[1], d_in[2], 3, dims, str, box, CU_TENSOR_MAP_SWIZZLE_128B, CU_TENSOR_MAP_L2_PROMOTION_L2_256B);
    }
    {
        cuuint64_t dims[3] = {4096, 512, 1}; cuuint64_t str[2] = {8192, 8192 * 512}; cuuint32_t box[3] = {32, 256, 1};
        encode(enc, &maps.m[2], d_in[3], 3, dims, str, box, CU_TENSOR_MAP_SWIZZLE_64B, CU_TENSOR_MAP_L2_PROMOTION_L2_128B);
    }
    {
        cuuint64_t dims[3] = {64, 4096, 8}; cuuint64_t str[2] = {1024, 128}; cuuint32_t box[3] = {64, 128, 2};
        encode(enc, &maps.m[3], d_in[4], 3, dims, str, box, CU_TENSOR_MAP_SWIZZLE_128B, CU_TENSOR_MAP_L2_PROMOTION_L2_256B);
    }
    {
        cuuint64_t dims[3] = {1792, 512, 1}; cuuint64_t str[2] = {3584, 3584 * 512}; cuuint32_t box[3] = {16, 256, 1};
        encode(enc, &maps.m[4], d_in[6], 3, dims, str, box, CU_TENSOR_MAP_SWIZZLE_32B, CU_TENSOR_MAP_L2_PROMOTION_L2_128B);
        encode(enc, &maps.m[5], d_in[7], 3, dims, str, box, CU_TENSOR_MAP_SWIZZLE_32B, CU_TENSOR_MAP_L2_PROMOTION_L2_128B);
    }
    {
        cuuint64_t dims[3] = {64, 1792, 8}; cuuint64_t str[2] = {1024, 128}; cuuint32_t box[3] = {64, 16, 4};
        encode(enc, &maps.m[6], d_in[8], 3, dims, str, box, CU_TENSOR_MAP_SWIZZLE_128B, CU_TENSOR_MAP_L2_PROMOTION_L2_256B);
    }
    fused_decode_kernel<<<NCTA, NTHREADS, SMEM_BYTES, cudaStreamPerThread>>>(maps, (const __nv_bfloat16*)x, (__nv_bfloat16*)d_out);
}
```

```cpp
#include <cuda_runtime.h>
#include <cuda_bf16.h>
#include <cuda.h>
#include <stdint.h>

namespace {

constexpr int NCTA      = 128;
constexpr int NTHREADS  = 320;
constexpr int SLOT      = 32768;
constexpr int NSLOT     = 6;
constexpr int NTILE     = 16;
constexpr int NFFN      = 112;
constexpr int DEPTH_LO  = 2;
constexpr int DEPTH_HI  = 3;
constexpr int LEAD_THR8 = 4;
constexpr int WO_MARGIN = 112;
constexpr int SEQ_WO    = 33;
constexpr int NSEQ      = 34;
constexpr int SLOT_WGU  = 4, SLOT_WD = 5;
constexpr int DLY_F     = 500;
constexpr int DLY_F_IDLE = 1100;
constexpr int RESET_TILE = 4;
constexpr int SAMPLE_NS = 100;
constexpr uint32_t SENT = 0xFFFFFFFFu;

constexpr int OFF_XN   = NSLOT * SLOT;
constexpr int XN_PITCH = 1040;
constexpr int OFF_QS   = OFF_XN + 4 * XN_PITCH;
constexpr int QS_PITCH = 272;
constexpr int OFF_P    = OFF_QS + 4 * QS_PITCH;
constexpr int P_PITCH  = 528;
constexpr int OFF_RED  = OFF_P + 4 * P_PITCH;
constexpr int OFF_MX   = OFF_RED + 4096;
constexpr int OFF_L    = OFF_MX + 64;
constexpr int OFF_ACT  = OFF_L + 128;
constexpr int OFF_RED2 = OFF_ACT + 128;
constexpr int OFF_CS   = OFF_RED2 + 512;
constexpr int OFF_ST   = OFF_CS + 512;
constexpr int OFF_BAR  = OFF_ST + 32;
constexpr int OFF_VAR  = OFF_BAR + 192;
constexpr int SMEM_USED = OFF_VAR + 64;
constexpr int SMEM_BYTES = SMEM_USED + 1024;
static_assert(OFF_RED % 16 == 0 && OFF_MX % 16 == 0 && OFF_ST % 8 == 0 && OFF_BAR % 8 == 0, "alignment");

__device__ uint2    g_q[4 * 2048];
__device__ float    g_partO[32 * 4 * 4 * 128];
__device__ float2   g_ml[32 * 4 * 4];
__device__ float    g_ypart[4 * 32 * 32 * 16];
__device__ uint16_t g_h[4 * 512];
__device__ float    g_dpart[4 * 32 * NFFN * 16];
__device__ unsigned g_cnt0, g_cnt1, g_prog;

__device__ __forceinline__ uint32_t smem_u32(const void* p) { return (uint32_t)__cvta_generic_to_shared(p); }
__device__ __forceinline__ void mbar_init(uint32_t bar, uint32_t cnt) {
    asm volatile("mbarrier.init.shared::cta.b64 [%0], %1;" ::"r"(bar), "r"(cnt) : "memory");
}
__device__ __forceinline__ void mbar_expect_tx(uint32_t bar, uint32_t bytes) {
    asm volatile("mbarrier.arrive.expect_tx.shared::cta.b64 _, [%0], %1;" ::"r"(bar), "r"(bytes) : "memory");
}
__device__ __forceinline__ void mbar_arrive(uint32_t bar) {
    asm volatile("mbarrier.arrive.shared::cta.b64 _, [%0];" ::"r"(bar) : "memory");
}
__device__ __forceinline__ bool mbar_try(uint32_t bar, uint32_t parity) {
    uint32_t ok;
    asm volatile("{\n.reg .pred p;\nmbarrier.try_wait.parity.shared::cta.b64 p, [%1], %2;\nselp.u32 %0, 1, 0, p;\n}"
                 : "=r"(ok) : "r"(bar), "r"(parity) : "memory");
    return ok != 0;
}
constexpr uint32_t SPIN_LIMIT = 1u << 20;
__device__ __forceinline__ void mbar_wait(uint32_t bar, uint32_t parity) {
    uint32_t it = 0;
    while (!mbar_try(bar, parity)) { if (++it > SPIN_LIMIT) __trap(); }
}
__device__ __forceinline__ void tma3d(uint32_t dst, const CUtensorMap* m, int c0, int c1, int c2, uint32_t bar, uint64_t pol) {
    asm volatile("cp.async.bulk.tensor.3d.shared::cluster.global.mbarrier::complete_tx::bytes.L2::cache_hint [%0], [%1, {%3, %4, %5}], [%2], %6;"
                 ::"r"(dst), "l"(m), "r"(bar), "r"(c0), "r"(c1), "r"(c2), "l"(pol) : "memory");
}
__device__ __forceinline__ void ldsm4(uint32_t (&r)[4], uint32_t addr) {
    asm volatile("ldmatrix.sync.aligned.m8n8.x4.shared.b16 {%0,%1,%2,%3}, [%4];"
                 : "=r"(r[0]), "=r"(r[1]), "=r"(r[2]), "=r"(r[3]) : "r"(addr) : "memory");
}
__device__ __forceinline__ void ldsm4t(uint32_t (&r)[4], uint32_t addr) {
    asm volatile("ldmatrix.sync.aligned.m8n8.x4.trans.shared.b16 {%0,%1,%2,%3}, [%4];"
                 : "=r"(r[0]), "=r"(r[1]), "=r"(r[2]), "=r"(r[3]) : "r"(addr) : "memory");
}
__device__ __forceinline__ void mma16816(float (&c)[4], const uint32_t (&a)[4], uint32_t b0, uint32_t b1) {
    asm volatile("mma.sync.aligned.m16n8k16.row.col.f32.bf16.bf16.f32 {%0,%1,%2,%3}, {%4,%5,%6,%7}, {%8,%9}, {%0,%1,%2,%3};"
                 : "+f"(c[0]), "+f"(c[1]), "+f"(c[2]), "+f"(c[3])
                 : "r"(a[0]), "r"(a[1]), "r"(a[2]), "r"(a[3]), "r"(b0), "r"(b1));
}
__device__ __forceinline__ void cbar() { asm volatile("bar.sync 1, 256;" ::: "memory"); }
__device__ __forceinline__ void bar_sync(int id, int n) { asm volatile("bar.sync %0, %1;" ::"r"(id), "r"(n) : "memory"); }
__device__ __forceinline__ void bar_arrive(int id, int n) { asm volatile("bar.arrive %0, %1;" ::"r"(id), "r"(n) : "memory"); }
__device__ __forceinline__ uint4 ld_poll4(const void* p) {
    uint4 v;
    asm volatile("ld.relaxed.gpu.global.v4.u32 {%0,%1,%2,%3}, [%4];" : "=r"(v.x), "=r"(v.y), "=r"(v.z), "=r"(v.w) : "l"(p) : "memory");
    return v;
}
__device__ __forceinline__ uint2 ld_poll2(const void* p) {
    uint2 v;
    asm volatile("ld.relaxed.gpu.global.v2.u32 {%0,%1}, [%2];" : "=r"(v.x), "=r"(v.y) : "l"(p) : "memory");
    return v;
}
__device__ __forceinline__ void st_rel32(void* p, uint32_t v) { asm volatile("st.relaxed.gpu.global.u32 [%0], %1;" ::"l"(p), "r"(v) : "memory"); }
__device__ __forceinline__ void st_rel16(void* p, uint16_t v) { asm volatile("st.relaxed.gpu.global.u16 [%0], %1;" ::"l"(p), "h"(v) : "memory"); }
__device__ __forceinline__ void st_rel64(void* p, uint32_t a, uint32_t b) { asm volatile("st.relaxed.gpu.global.v2.u32 [%0], {%1,%2};" ::"l"(p), "r"(a), "r"(b) : "memory"); }
__device__ __forceinline__ void st_rel128(void* p, uint32_t v) { asm volatile("st.relaxed.gpu.global.v4.u32 [%0], {%1,%1,%1,%1};" ::"l"(p), "r"(v) : "memory"); }
__device__ __forceinline__ uint32_t umax4(const uint4& v) { return max(max(v.x, v.y), max(v.z, v.w)); }
template <class T> __device__ __forceinline__ void pin(T*& p) { asm volatile("" : "+l"(p)); }
__device__ __forceinline__ bool valid8h(const uint4& v) {
    return (__vcmpeq2(v.x, SENT) | __vcmpeq2(v.y, SENT) | __vcmpeq2(v.z, SENT) | __vcmpeq2(v.w, SENT)) == 0;
}
struct Spin {
    uint32_t it = 0;
    __device__ __forceinline__ void tick() { if (++it > SPIN_LIMIT) __trap(); }
};
__device__ __forceinline__ void wait_progress(int n) {
    Spin sp; unsigned v;
    while (true) {
        asm volatile("ld.relaxed.gpu.global.u32 %0, [%1];" : "=r"(v) : "l"(&g_prog) : "memory");
        if ((int)v >= n) break;
        sp.tick(); __nanosleep(64);
    }
}
__device__ __forceinline__ uint32_t pack_bf16(float lo, float hi) {
    uint32_t r; asm("cvt.rn.bf16x2.f32 %0, %1, %2;" : "=r"(r) : "f"(hi), "f"(lo)); return r;
}
__device__ __forceinline__ void delay_cycles(int n) { if (n > 0) { const long long t0 = clock64(); while (clock64() - t0 < n) {} } }
__device__ __forceinline__ float bf16r(float x) { return __uint_as_float(pack_bf16(0.f, x) & 0xFFFF0000u); }
__device__ __forceinline__ float bf_lo(uint32_t v) { return __uint_as_float(v << 16); }
__device__ __forceinline__ float bf_hi(uint32_t v) { return __uint_as_float(v & 0xFFFF0000u); }
__device__ __forceinline__ uint32_t hmax2(uint32_t a, uint32_t b) {
    uint32_t r; asm("max.bf16x2 %0, %1, %2;" : "=r"(r) : "r"(a), "r"(b)); return r;
}
__device__ __forceinline__ float ex2(float x) { float r; asm("ex2.approx.ftz.f32 %0, %1;" : "=f"(r) : "f"(x)); return r; }

__device__ __forceinline__ float2 ln_stats(const uint4& a, const uint4& b, float (&v)[16]) {
    v[0] = bf_lo(a.x); v[1] = bf_hi(a.x); v[2] = bf_lo(a.y); v[3] = bf_hi(a.y);
    v[4] = bf_lo(a.z); v[5] = bf_hi(a.z); v[6] = bf_lo(a.w); v[7] = bf_hi(a.w);
    v[8] = bf_lo(b.x); v[9] = bf_hi(b.x); v[10] = bf_lo(b.y); v[11] = bf_hi(b.y);
    v[12] = bf_lo(b.z); v[13] = bf_hi(b.z); v[14] = bf_lo(b.w); v[15] = bf_hi(b.w);
    const float shift = __shfl_sync(0xffffffffu, v[0], 0);
    float s0 = 0.f, s1 = 0.f, s2 = 0.f, s3 = 0.f, q0 = 0.f, q1 = 0.f, q2 = 0.f, q3 = 0.f;
#pragma unroll
    for (int i = 0; i < 16; i += 4) {
        const float d0 = v[i] - shift, d1 = v[i + 1] - shift, d2 = v[i + 2] - shift, d3 = v[i + 3] - shift;
        s0 += d0; s1 += d1; s2 += d2; s3 += d3;
        q0 = fmaf(d0, d0, q0); q1 = fmaf(d1, d1, q1); q2 = fmaf(d2, d2, q2); q3 = fmaf(d3, d3, q3);
    }
    float s = (s0 + s1) + (s2 + s3), ss = (q0 + q1) + (q2 + q3);
#pragma unroll
    for (int o = 16; o > 0; o >>= 1) { s += __shfl_xor_sync(0xffffffffu, s, o); ss += __shfl_xor_sync(0xffffffffu, ss, o); }
    const float md = s * (1.0f / 512.0f);
    const float var = fmaxf(ss * (1.0f / 512.0f) - md * md, 0.f);
    const float m = bf16r(shift + md);
    float sq; asm("sqrt.approx.f32 %0, %1;" : "=f"(sq) : "f"(bf16r(bf16r(var) + 1e-5f)));
    const float sd = bf16r(sq);
    return make_float2(m, __fdividef(1.0f, sd));
}

struct Maps { CUtensorMap m[7]; };

__global__ void __launch_bounds__(NTHREADS, 1)
fused_decode_kernel(const __grid_constant__ Maps maps, const __nv_bfloat16* __restrict__ x, __nv_bfloat16* __restrict__ out)
{
    extern __shared__ __align__(1024) unsigned char smem_raw[];
    unsigned char* smem = smem_raw + ((1024u - (smem_u32(smem_raw) & 1023u)) & 1023u);
    const uint32_t sbase = smem_u32(smem);
    const uint32_t bar_full = sbase + OFF_BAR, bar_empty = sbase + OFF_BAR + 48, bar_ready = sbase + OFF_BAR + 96, bar_w = sbase + OFF_BAR + 104;
    volatile unsigned* vars = reinterpret_cast<volatile unsigned*>(smem + OFF_VAR);
    const int tid = threadIdx.x, warp = tid >> 5, lane = tid & 31;
    const int cta = blockIdx.x;

    uint4 xa = make_uint4(0, 0, 0, 0), xb = xa;
    float xres = 0.f;
    unsigned cnt0 = 0;
    if (warp < 4) {
        const uint4* xr = reinterpret_cast<const uint4*>(x + warp * 512);
        xa = __ldg(xr + lane); xb = __ldg(xr + 32 + lane);
        if (warp == 0) xres = __bfloat162float(x[(cta >> 5) * 512 + (cta & 31) * 16 + (lane >> 1)]);
        if (tid == 0) cnt0 = atomicAdd(&g_cnt0, 1u);
    } else if (warp == 7) {
        st_rel128(&g_q[(lane >> 3) * 2048 + cta * 16 + (lane & 7) * 2], 0u);
    }
    uint64_t pol;
    asm volatile("createpolicy.fractional.L2::evict_first.b64 %0, 1.0;" : "=l"(pol));
    if (__builtin_expect(tid == 256, 1)) {
        for (int i = 0; i < NSLOT; i++) { mbar_init(bar_full + 8 * i, 1); mbar_init(bar_empty + 8 * i, 8); }
        asm volatile("fence.mbarrier_init.release.cluster;" ::: "memory");
        mbar_expect_tx(bar_full, 32768);
        tma3d(sbase, &maps.m[2], cta * 32, 0, 0, bar_full, pol);
        tma3d(sbase + 16384, &maps.m[2], cta * 32, 256, 0, bar_full, pol);
        mbar_expect_tx(bar_full + 8, 32768);
        tma3d(sbase + SLOT, &maps.m[0], 0, cta * (NTILE * 128), 0, bar_full + 8, pol);
        mbar_expect_tx(bar_full + 16, 32768);
        tma3d(sbase + 2 * SLOT, &maps.m[0], 0, cta * (NTILE * 128) + 128, 0, bar_full + 16, pol);
        asm volatile("red.relaxed.gpu.global.add.u32 [%0], 2;" ::"l"(&g_prog) : "memory");
        mbar_init(bar_ready, 1);
        for (int i = 0; i < 6; i++) mbar_init(bar_w + 8 * i, 1);
        vars[1] = 0; vars[2] = 0; vars[3] = 0;
        asm volatile("fence.mbarrier_init.release.cluster;" ::: "memory");
    } else if (tid > 256 && tid <= 263) {
        asm volatile("prefetch.tensormap [%0];" ::"l"(&maps.m[tid - 257]) : "memory");
    }
    if (warp == 8) { __syncwarp(); bar_arrive(8, NTHREADS); } else bar_sync(8, NTHREADS);

    if (warp == 8) {
        if (lane == 0) {
            const int key0 = cta * (NTILE * 128);
            int arrived = 0;
            int nkv = 2;
            const int nseq = (cta < NFFN) ? NSEQ + 6 : NSEQ;
            for (int i = 3; i < nseq; i++) {
                uint32_t dst, fb, bytes = 32768;
                int mi, c0 = 0, c1, c2 = 0;
                if (i < NSEQ) {
                    const int slot = i % NSLOT;
                    if (i >= NSLOT) mbar_wait(bar_empty + 8 * slot, ((i / NSLOT) - 1) & 1);
                    const int grel = (int)vars[2];
                    const int lead8 = (nkv * NCTA - grel) / (NCTA / 8);
                    const int d = (lead8 > LEAD_THR8) ? DEPTH_LO : DEPTH_HI;
                    while (arrived < i - d + 1) { mbar_wait(bar_full + 8 * (arrived % NSLOT), (arrived / NSLOT) & 1); arrived++; }
                    dst = sbase + slot * SLOT; fb = bar_full + 8 * slot;
                    if (i == SEQ_WO) { mi = 3; c1 = (cta >> 2) * 128; c2 = (cta & 3) * 2; }
                    else             { mi = (nkv >> 1) & 1; c1 = key0 + (2 * (nkv >> 2) + (nkv & 1)) * 128; }
                } else {
                    const int k = i - NSEQ;
                    if (k == 0) {
                        mbar_wait(bar_empty + 8 * SLOT_WGU, (34 / NSLOT - 1) & 1);
                        mbar_wait(bar_empty + 8 * SLOT_WD, (35 / NSLOT - 1) & 1);
                    }
                    dst = sbase + SLOT_WGU * SLOT + k * 8192; fb = bar_w + 8 * k; bytes = 8192;
                    mi = (k < 4) ? 4 + (k >> 1) : 6;
                    c0 = (k < 4) ? cta * 16 : 0; c1 = (k < 4) ? (k & 1) * 256 : cta * 16; c2 = (k < 4) ? 0 : (k - 4) * 4;
                }
                const int need = (i == SEQ_WO) ? NCTA * 32 - WO_MARGIN : (i == NSEQ) ? NCTA * 32 : 0;
                if ((int)vars[2] < need) wait_progress(need);
                if (i == NSEQ) mbar_wait(bar_full + 8 * (SEQ_WO % NSLOT), (SEQ_WO / NSLOT) & 1);
                mbar_expect_tx(fb, bytes);
                tma3d(dst, &maps.m[mi], c0, c1, c2, fb, pol);
                if (i < SEQ_WO) {
                    asm volatile("red.relaxed.gpu.global.add.u32 [%0], 1;" ::"l"(&g_prog) : "memory");
                    nkv++;
                }
                if (i == SEQ_WO) vars[3] = 1;
            }
        }
        return;
    }

    const int pair = cta >> 2, split = cta & 3;

    if (warp == 9) {
        Spin sp;
        auto sample = [&]() {
            unsigned v;
            asm volatile("ld.relaxed.gpu.global.u32 %0, [%1];" : "=r"(v) : "l"(&g_prog) : "memory");
            if (lane == 0) vars[2] = v;
        };
        while (vars[1] < RESET_TILE) { sp.tick(); sample(); __nanosleep(SAMPLE_NS); }
        const unsigned epoch = vars[0];
#pragma unroll 1
        for (int u = lane; u < 128; u += 32) {
            st_rel128(&g_partO[((pair * 4 + (u >> 5)) * 4 + split) * 128 + (u & 31) * 4], SENT);
            const int seg = u >> 2;
            st_rel128(&g_ypart[(((seg >> 3) * 32 + (cta & 3) * 8 + (seg & 7)) * 32 + (cta >> 2)) * 16 + (u & 3) * 4], SENT);
        }
        if (lane < 4) st_rel64(&g_ml[(pair * 4 + lane) * 4 + split], SENT, SENT);
        if (lane < 2) st_rel128(&g_h[(cta >> 5) * 512 + (cta & 31) * 16 + lane * 8], SENT);
        if (cta < NFFN) {
#pragma unroll 1
            for (int e = lane; e < 512; e += 32) st_rel128(&g_dpart[((e >> 2) * NFFN + cta) * 16 + (e & 3) * 4], SENT);
        }
        __threadfence();
        __syncwarp();
        if (lane == 0) {
            atomicAdd(&g_cnt1, 1u);
            unsigned v; Spin sp2;
            while (true) {
                asm volatile("ld.acquire.gpu.global.u32 %0, [%1];" : "=r"(v) : "l"(&g_cnt1) : "memory");
                if ((int)(v - (epoch + 1) * NCTA) >= 0) break;
                sp2.tick(); sample(); __nanosleep(128);
            }
            mbar_arrive(bar_ready);
        }
        __syncwarp();
        while (vars[3] == 0) { sp.tick(); sample(); __nanosleep(SAMPLE_NS); }
        return;
    }

    const int r8 = lane >> 2, q4 = lane & 3;
    const int hp = q4 & 1, kh = q4 >> 1;
    constexpr float LOG2E = 1.4426950408889634f;
    const int bq = pair >> 3, gq = pair & 7;

    if (tid == 0) vars[0] = cnt0 >> 7;

    if (warp < 4) {
        float v[16];
        const float2 st = ln_stats(xa, xb, v);
        uint32_t o[8];
#pragma unroll
        for (int i = 0; i < 8; i++) o[i] = pack_bf16(bf16r(v[2 * i] - st.x) * st.y, bf16r(v[2 * i + 1] - st.x) * st.y);
        unsigned char* row = smem + OFF_XN + warp * XN_PITCH;
        *reinterpret_cast<uint4*>(row + lane * 16) = make_uint4(o[0], o[1], o[2], o[3]);
        *reinterpret_cast<uint4*>(row + 512 + lane * 16) = make_uint4(o[4], o[5], o[6], o[7]);
    }
    cbar();
    const uint32_t tag = vars[0] + 1;

    {
        uint32_t bfr[4][2];
        {
            uint32_t t4[4];
#pragma unroll
            for (int u = 0; u < 2; u++) {
                ldsm4(t4, sbase + OFF_XN + (lane & 3) * XN_PITCH + (8 * warp + 4 * u + (lane >> 3)) * 16);
                bfr[2 * u][0] = t4[0]; bfr[2 * u][1] = t4[1]; bfr[2 * u + 1][0] = t4[2]; bfr[2 * u + 1][1] = t4[3];
            }
        }
        mbar_wait(bar_full + 0, 0);
        float acc[2][4] = {};
#pragma unroll
        for (int ks = 0; ks < 4; ks++) {
            const int k = 64 * warp + 16 * ks + (lane & 7) + (lane >> 4) * 8;
#pragma unroll
            for (int mt = 0; mt < 2; mt++) {
                uint32_t a[4];
                const int chunk = 2 * mt + ((lane >> 3) & 1);
                ldsm4t(a, sbase + k * 64 + ((chunk ^ ((k >> 1) & 3)) << 4));
                mma16816(acc[mt], a, bfr[ks][0], bfr[ks][1]);
            }
        }
        __syncwarp();
        if (lane == 0) mbar_arrive(bar_empty + 0);
        float* red = reinterpret_cast<float*>(smem + OFF_RED);
#pragma unroll
        for (int mt = 0; mt < 2; mt++) {
            float2 v = kh ? make_float2(acc[mt][2], acc[mt][3]) : make_float2(acc[mt][0], acc[mt][1]);
            *reinterpret_cast<float2*>(red + ((warp * 2 + mt) * 16 + r8 + 8 * kh) * 4 + 2 * hp) = v;
        }
        cbar();
        if (tid < 64) {
            const int b = tid >> 4, c2 = tid & 15;
            float s0 = 0.f, s1 = 0.f;
            const int c0 = 2 * c2, c1 = 2 * c2 + 1;
#pragma unroll
            for (int ww = 0; ww < 8; ww++) {
                s0 += red[((ww * 2 + (c0 >> 4)) * 16 + (c0 & 15)) * 4 + b];
                s1 += red[((ww * 2 + (c1 >> 4)) * 16 + (c1 & 15)) * 4 + b];
            }
            st_rel64(&g_q[b * 2048 + cta * 16 + c2], pack_bf16(s0, s1), tag);
        }
        {
            const uint2* src = &g_q[bq * 2048 + gq * 256 + tid];
            uint2 v;
            Spin sp;
            while (true) { v = ld_poll2(src); if (__all_sync(0xffffffffu, v.y == tag)) break; sp.tick(); }
            *reinterpret_cast<uint32_t*>(smem + OFF_QS + (tid >> 6) * QS_PITCH + (tid & 63) * 4) = v.x;
        }
        cbar();
    }
    uint32_t qf[8][2];
    {
        uint32_t t4[4];
#pragma unroll
        for (int u = 0; u < 4; u++) {
            ldsm4(t4, sbase + OFF_QS + (lane & 3) * QS_PITCH + (4 * u + (lane >> 3)) * 16);
            qf[2 * u][0] = t4[0]; qf[2 * u][1] = t4[1]; qf[2 * u + 1][0] = t4[2]; qf[2 * u + 1][1] = t4[3];
        }
    }

    const uint32_t voff = (warp >> 2) * 16384 + ((lane & 7) + (lane >> 4) * 8) * 128 +
                          ((((2 * warp + ((lane >> 3) & 1)) & 7) ^ (lane & 7)) << 4);
    const uint32_t poff = sbase + OFF_P + (lane & 3) * P_PITCH + (lane >> 3) * 16;
    const uint32_t koff = (16 * warp + (lane & 7) + ((lane >> 3) & 1) * 8) * 128;
    const uint32_t kx = lane & 7, kc = lane >> 4;
    constexpr float SCALE = 0.08838834764831845f;
    uint32_t* mxbuf = reinterpret_cast<uint32_t*>(smem + OFF_MX);
    uint32_t M2 = 0xFF80FF80u;
    float l0 = 0.f, l1 = 0.f;
    float oacc[2][4] = {};
    int slot = 1; uint32_t ph = 0;

    auto pv_tile = [&](int j, bool release) {
        uint32_t pb[8][2];
        uint32_t t4[4];
#pragma unroll
        for (int u = 0; u < 4; u++) {
            ldsm4(t4, poff + j * 256 + u * 64);
            pb[2 * u][0] = t4[0]; pb[2 * u][1] = t4[1]; pb[2 * u + 1][0] = t4[2]; pb[2 * u + 1][1] = t4[3];
        }
        mbar_wait(bar_full + 8 * slot, ph);
        const uint32_t vb = sbase + slot * SLOT + voff;
#pragma unroll
        for (int ks = 0; ks < 8; ks++) {
            uint32_t a[4];
            ldsm4t(a, vb + ks * 2048);
            mma16816(oacc[ks & 1], a, pb[ks][0], pb[ks][1]);
        }
        if (release) { __syncwarp(); if (lane == 0) mbar_arrive(bar_empty + 8 * slot); }
        if (++slot == NSLOT) { slot = 0; ph ^= 1; }
    };

    for (int t = 0;; t++) {
        uint32_t sp[2];
#pragma unroll
        for (int j = 0; j < 2; j++) {
            mbar_wait(bar_full + 8 * slot, ph);
            float sa[4] = {}, sb[4] = {};
            const uint32_t kb = sbase + slot * SLOT + koff;
#pragma unroll
            for (int ks = 0; ks < 8; ks++) {
                uint32_t a[4];
                ldsm4(a, kb + (ks >> 2) * 16384 + (((2 * (ks & 3) + kc) ^ kx) << 4));
                if (ks & 1) mma16816(sb, a, qf[ks][0], qf[ks][1]); else mma16816(sa, a, qf[ks][0], qf[ks][1]);
            }
            __syncwarp();
            if (lane == 0) mbar_arrive(bar_empty + 8 * slot);
            if (++slot == NSLOT) { slot = 0; ph ^= 1; }
            const float r0 = kh ? sa[2] + sb[2] : sa[0] + sb[0];
            const float r1 = kh ? sa[3] + sb[3] : sa[1] + sb[1];
            const uint32_t sr = pack_bf16(r0, r1);
            sp[j] = pack_bf16(bf_lo(sr) * SCALE, bf_hi(sr) * SCALE);
        }
        uint32_t mx = hmax2(sp[0], sp[1]);
#pragma unroll
        for (int o = 2; o <= 16; o <<= 1) mx = hmax2(mx, __shfl_xor_sync(0xffffffffu, mx, o));
        if (lane < 2) mxbuf[lane * 8 + warp] = mx;
        if (tid == 0) vars[1] = t + 1;
        cbar();
        {
            const uint4 m0 = *reinterpret_cast<const uint4*>(mxbuf + hp * 8), m1 = *reinterpret_cast<const uint4*>(mxbuf + hp * 8 + 4);
            uint32_t mt = hmax2(hmax2(hmax2(m0.x, m0.y), hmax2(m0.z, m0.w)), hmax2(hmax2(m1.x, m1.y), hmax2(m1.z, m1.w)));
            const uint32_t Mn = hmax2(M2, mt);
            const float a0 = ex2((bf_lo(M2) - bf_lo(Mn)) * LOG2E), a1 = ex2((bf_hi(M2) - bf_hi(Mn)) * LOG2E);
            M2 = Mn;
            l0 *= a0; l1 *= a1;
#pragma unroll
            for (int j = 0; j < 2; j++) {
                const float p0 = ex2((bf_lo(sp[j]) - bf_lo(Mn)) * LOG2E), p1 = ex2((bf_hi(sp[j]) - bf_hi(Mn)) * LOG2E);
                l0 += p0; l1 += p1;
                const uint32_t pp = pack_bf16(p0, p1);
                unsigned char* pd = smem + OFF_P + (2 * hp) * P_PITCH + (128 * j + 16 * warp + r8 + 8 * kh) * 2;
                *reinterpret_cast<uint16_t*>(pd) = (uint16_t)(pp & 0xFFFF);
                *reinterpret_cast<uint16_t*>(pd + P_PITCH) = (uint16_t)(pp >> 16);
            }
#pragma unroll
            for (int c = 0; c < 2; c++) { oacc[c][0] *= a0; oacc[c][1] *= a1; oacc[c][2] *= a0; oacc[c][3] *= a1; }
        }
        if (t == NTILE / 2 - 1) break;
        cbar();
        pv_tile(0, true);
        pv_tile(1, true);
    }

    const int head = cta >> 2;
    float* p_partO = &g_partO[((pair * 4 + 2 * hp) * 4 + split) * 128 + 16 * warp + r8 + 8 * kh];
    float* p_dpart = &g_dpart[(((2 * hp) * 32 + 4 * warp) * NFFN + cta) * 16 + r8 + 8 * kh];
    const float* p_dsrc = &g_dpart[(cta * NFFN + (tid >> 2)) * 16 + (tid & 3) * 4];
    __nv_bfloat16* p_out = out + (cta >> 5) * 512 + (cta & 31) * 16 + (lane >> 1);
    pin(p_partO); pin(p_dpart); pin(p_dsrc); pin(p_out);

    {
        float s0 = l0, s1 = l1;
#pragma unroll
        for (int o = 2; o <= 16; o <<= 1) { s0 += __shfl_xor_sync(0xffffffffu, s0, o); s1 += __shfl_xor_sync(0xffffffffu, s1, o); }
        if (lane < 2) *reinterpret_cast<float2*>(smem + OFF_L + warp * 16 + lane * 8) = make_float2(s0, s1);
        mbar_wait(bar_ready, 0);
        cbar();
        if (warp == 0) {
            const uint32_t other = __shfl_sync(0xffffffffu, M2, lane >> 1);
            float l = 0.f;
#pragma unroll
            for (int ww = 0; ww < 8; ww++) l += *reinterpret_cast<const float*>(smem + OFF_L + ww * 16 + (lane & 3) * 4);
            const float m = (lane & 1) ? bf_hi(other) : bf_lo(other);
            if (lane < 4) st_rel64(&g_ml[(pair * 4 + lane) * 4 + split], __float_as_uint(m), __float_as_uint(l));
        }
        pv_tile(0, false);
        uint32_t pb[8][2];
        {
            uint32_t t4[4];
#pragma unroll
            for (int u = 0; u < 4; u++) {
                ldsm4(t4, poff + 256 + u * 64);
                pb[2 * u][0] = t4[0]; pb[2 * u][1] = t4[1]; pb[2 * u + 1][0] = t4[2]; pb[2 * u + 1][1] = t4[3];
            }
        }
        float o2[2][4] = {};
        {
            mbar_wait(bar_full + 8 * slot, ph);
            const uint32_t vb = sbase + slot * SLOT + voff;
            uint32_t a[8][4];
#pragma unroll
            for (int ks = 0; ks < 8; ks++) ldsm4t(a[ks], vb + ks * 2048);
#pragma unroll
            for (int ks = 0; ks < 8; ks++) mma16816((ks & 2) ? o2[ks & 1] : oacc[ks & 1], a[ks], pb[ks][0], pb[ks][1]);
        }
        const float v0 = kh ? (oacc[0][2] + oacc[1][2]) + (o2[0][2] + o2[1][2]) : (oacc[0][0] + oacc[1][0]) + (o2[0][0] + o2[1][0]);
        const float v1 = kh ? (oacc[0][3] + oacc[1][3]) + (o2[0][3] + o2[1][3]) : (oacc[0][1] + oacc[1][1]) + (o2[0][1] + o2[1][1]);
        st_rel32(p_partO, __float_as_uint(v0));
        st_rel32(p_partO + 512, __float_as_uint(v1));
    }

    float hres = 0.f;
    uint32_t df[4][4];
    if (warp < 4) {
        {
            const int ph_idx = (warp * 8 + (head >> 2)) * 4 + (head & 3);
            const float* po = &g_partO[ph_idx * 512 + lane * 4];
            const float* pm = reinterpret_cast<const float*>(&g_ml[ph_idx * 4]);
            uint4 o0, o1, o2, o3, ma, mb;
            Spin sp;
            while (true) {
                o0 = ld_poll4(po); o1 = ld_poll4(po + 128); o2 = ld_poll4(po + 256); o3 = ld_poll4(po + 384);
                ma = ld_poll4(pm); mb = ld_poll4(pm + 4);
                const uint32_t mxv = max(max(max(umax4(o0), umax4(o1)), max(umax4(o2), umax4(o3))), max(umax4(ma), umax4(mb)));
                if (__all_sync(0xffffffffu, mxv != SENT)) break;
                sp.tick();
            }
            const float m0 = __uint_as_float(ma.x), m1 = __uint_as_float(ma.z), m2 = __uint_as_float(mb.x), m3 = __uint_as_float(mb.z);
            const float M = fmaxf(fmaxf(m0, m1), fmaxf(m2, m3));
            float w0 = ex2((m0 - M) * LOG2E), w1 = ex2((m1 - M) * LOG2E), w2 = ex2((m2 - M) * LOG2E), w3 = ex2((m3 - M) * LOG2E);
            const float L = w0 * __uint_as_float(ma.y) + w1 * __uint_as_float(ma.w) + w2 * __uint_as_float(mb.y) + w3 * __uint_as_float(mb.w);
            const float inv = __fdividef(1.0f, L);
            const float e0 = (w0 * __uint_as_float(o0.x) + w1 * __uint_as_float(o1.x) + w2 * __uint_as_float(o2.x) + w3 * __uint_as_float(o3.x)) * inv;
            const float e1 = (w0 * __uint_as_float(o0.y) + w1 * __uint_as_float(o1.y) + w2 * __uint_as_float(o2.y) + w3 * __uint_as_float(o3.y)) * inv;
            const float e2 = (w0 * __uint_as_float(o0.z) + w1 * __uint_as_float(o1.z) + w2 * __uint_as_float(o2.z) + w3 * __uint_as_float(o3.z)) * inv;
            const float e3 = (w0 * __uint_as_float(o0.w) + w1 * __uint_as_float(o1.w) + w2 * __uint_as_float(o2.w) + w3 * __uint_as_float(o3.w)) * inv;
            *reinterpret_cast<uint2*>(smem + OFF_QS + warp * QS_PITCH + lane * 8) = make_uint2(pack_bf16(e0, e1), pack_bf16(e2, e3));
            bar_arrive(2, 256);
        }
        {
            const float* src = &g_ypart[(cta * 32 + 8 * warp + (lane >> 2)) * 16 + (lane & 3) * 4];
            uint16_t* p_h = &g_h[(cta >> 5) * 512 + (cta & 31) * 16 + (lane >> 1)];
            pin(p_h);
            uint4 y;
            Spin sp;
            while (true) {
                y = ld_poll4(src);
                if (__all_sync(0xffffffffu, umax4(y) != SENT)) break;
                sp.tick();
            }
            const bool up = lane & 16, up2 = lane & 8;
            const float a0 = __uint_as_float(y.x), a1 = __uint_as_float(y.y), a2 = __uint_as_float(y.z), a3 = __uint_as_float(y.w);
            const float v0 = (up ? a2 : a0) + __shfl_xor_sync(0xffffffffu, up ? a0 : a2, 16);
            const float v1 = (up ? a3 : a1) + __shfl_xor_sync(0xffffffffu, up ? a1 : a3, 16);
            float v = (up2 ? v1 : v0) + __shfl_xor_sync(0xffffffffu, up2 ? v0 : v1, 8);
            v += __shfl_xor_sync(0xffffffffu, v, 4);
            float* rc = reinterpret_cast<float*>(smem + OFF_RED2);
            if (!(lane & 4)) rc[warp * 16 + 4 * (lane & 3) + (up ? 2 : 0) + (up2 ? 1 : 0)] = v;
            bar_sync(7, 128);
            if (warp == 0) {
                const float* r2 = rc + (lane & 1) * 32 + (lane >> 1);
                float t = r2[0] + r2[16];
                t += __shfl_xor_sync(0xffffffffu, t, 1);
                hres = bf16r(xres + bf16r(t));
                if (!(lane & 1)) st_rel16(p_h, (uint16_t)(__float_as_uint(hres) >> 16));
            }
        }
        {
            const uint4* hr = reinterpret_cast<const uint4*>(g_h + warp * 512);
            uint4 a, b;
            Spin sp;
            while (true) {
                a = ld_poll4(hr + lane); b = ld_poll4(hr + 32 + lane);
                if (__all_sync(0xffffffffu, valid8h(a) & valid8h(b))) break;
                sp.tick();
            }
            if (cta < NFFN) {
                unsigned char* row = smem + OFF_XN + warp * XN_PITCH;
                *reinterpret_cast<uint4*>(row + lane * 16) = a;
                *reinterpret_cast<uint4*>(row + 512 + lane * 16) = b;
                bar_arrive(3, 256);
                float v[16];
                const float2 st = ln_stats(a, b, v);
                if (lane == 0) *reinterpret_cast<float2*>(smem + OFF_ST + warp * 8) = st;
                bar_arrive(4, 256);
                mbar_wait(bar_w + 32, 0); mbar_wait(bar_w + 40, 0);
                const uint32_t wb = sbase + SLOT_WD * SLOT + warp * 2048 + ((lane & 7) + (lane >> 4) * 8) * 128;
#pragma unroll
                for (int i = 0; i < 4; i++) ldsm4t(df[i], wb + (((2 * i + ((lane >> 3) & 1)) ^ (lane & 7)) << 4));
            }
        }
    } else {
        const int m = warp - 4;
        {
            uint32_t af[2][8][4];
            float* p_y = &g_ypart[(((2 * hp) * 32 + (cta & 3) * 8 + 2 * m) * 32 + head) * 16 + r8 + 8 * kh];
            pin(p_y);
            mbar_wait(bar_full + 8 * (SEQ_WO % NSLOT), (SEQ_WO / NSLOT) & 1);
#pragma unroll
            for (int i = 0; i < 2; i++) {
                const int j = 2 * m + i;
                const uint32_t wb = sbase + (SEQ_WO % NSLOT) * SLOT + (j >> 2) * 16384 + ((lane & 7) + (lane >> 4) * 8) * 128 +
                                    ((((2 * j + ((lane >> 3) & 1)) & 7) ^ (lane & 7)) << 4);
#pragma unroll
                for (int ks = 0; ks < 8; ks++) ldsm4t(af[i][ks], wb + ks * 2048);
            }
            bar_sync(2, 256);
            float acc[2][2][4] = {};
            uint32_t t4[4][4];
#pragma unroll
            for (int u = 0; u < 4; u++) ldsm4(t4[u], sbase + OFF_QS + (lane & 3) * QS_PITCH + (4 * u + (lane >> 3)) * 16);
#pragma unroll
            for (int u = 0; u < 4; u++) {
#pragma unroll
                for (int i = 0; i < 2; i++) {
                    mma16816(acc[i][0], af[i][2 * u], t4[u][0], t4[u][1]);
                    mma16816(acc[i][1], af[i][2 * u + 1], t4[u][2], t4[u][3]);
                }
            }
#pragma unroll
            for (int i = 0; i < 2; i++) {
                const float v0 = kh ? acc[i][0][2] + acc[i][1][2] : acc[i][0][0] + acc[i][1][0];
                const float v1 = kh ? acc[i][0][3] + acc[i][1][3] : acc[i][0][1] + acc[i][1][1];
                st_rel32(p_y + i * 32 * 16, __float_as_uint(v0));
                st_rel32(p_y + i * 32 * 16 + 32 * 32 * 16, __float_as_uint(v1));
            }
        }
        if (cta < NFFN) {
            uint32_t gf[8][2][4];
            mbar_wait(bar_w, 0); mbar_wait(bar_w + 8, 0); mbar_wait(bar_w + 16, 0); mbar_wait(bar_w + 24, 0);
#pragma unroll
            for (int ks = 0; ks < 8; ks++) {
                const int k = 128 * m + 16 * ks + (lane & 7) + (lane >> 4) * 8;
                const uint32_t a = sbase + SLOT_WGU * SLOT + k * 32 + ((((lane >> 3) & 1) ^ ((k >> 2) & 1)) << 4);
                ldsm4t(gf[ks][0], a);
                ldsm4t(gf[ks][1], a + 16384);
            }
            float sg = 0.f, su = 0.f;
            {
                float cs[2][4] = {};
#pragma unroll
                for (int ks = 0; ks < 8; ks++) { mma16816(cs[0], gf[ks][0], 0x3F803F80u, 0x3F803F80u); mma16816(cs[1], gf[ks][1], 0x3F803F80u, 0x3F803F80u); }
                float* csb = reinterpret_cast<float*>(smem + OFF_CS);
                if (q4 == 0) {
                    csb[(m * 2 + 0) * 16 + r8] = cs[0][0]; csb[(m * 2 + 0) * 16 + r8 + 8] = cs[0][2];
                    csb[(m * 2 + 1) * 16 + r8] = cs[1][0]; csb[(m * 2 + 1) * 16 + r8 + 8] = cs[1][2];
                }
                bar_sync(5, 128);
                const int c = (tid & 63) >> 2;
#pragma unroll
                for (int ww = 0; ww < 4; ww++) { sg += csb[(ww * 2) * 16 + c]; su += csb[(ww * 2 + 1) * 16 + c]; }
            }
            const uint32_t wdb = sbase + SLOT_WD * SLOT + warp * 2048 + ((lane & 7) + (lane >> 4) * 8) * 128;
            const bool have_wd = __all_sync(0xffffffffu, mbar_try(bar_w + 32, 0) && mbar_try(bar_w + 40, 0));
            if (have_wd) {
#pragma unroll
                for (int i = 0; i < 4; i++) ldsm4t(df[i], wdb + (((2 * i + ((lane >> 3) & 1)) ^ (lane & 7)) << 4));
            }
            bar_sync(3, 256);
            float acc[2][2][4] = {};
            uint32_t t4[4][4];
#pragma unroll
            for (int u = 0; u < 4; u++) ldsm4(t4[u], sbase + OFF_XN + (lane & 3) * XN_PITCH + (16 * m + 4 * u + (lane >> 3)) * 16);
#pragma unroll
            for (int u = 0; u < 4; u++) {
#pragma unroll
                for (int i = 0; i < 2; i++) {
                    mma16816(acc[i][0], gf[2 * u][i], t4[u][0], t4[u][1]);
                    mma16816(acc[i][1], gf[2 * u + 1][i], t4[u][2], t4[u][3]);
                }
            }
            float* red = reinterpret_cast<float*>(smem + OFF_RED);
#pragma unroll
            for (int i = 0; i < 2; i++) {
                const float2 v = kh ? make_float2(acc[i][0][2] + acc[i][1][2], acc[i][0][3] + acc[i][1][3])
                                    : make_float2(acc[i][0][0] + acc[i][1][0], acc[i][0][1] + acc[i][1][1]);
                *reinterpret_cast<float2*>(red + ((m * 2 + i) * 16 + r8 + 8 * kh) * 4 + 2 * hp) = v;
            }
            bar_sync(4, 256);
            if (tid < 192) {
                const int c = (tid & 63) >> 2, b = tid & 3;
                const float2 st = *reinterpret_cast<const float2*>(smem + OFF_ST + b * 8);
                float g = 0.f, u = 0.f;
#pragma unroll
                for (int ww = 0; ww < 4; ww++) { g += red[((ww * 2) * 16 + c) * 4 + b]; u += red[((ww * 2 + 1) * 16 + c) * 4 + b]; }
                g = bf16r((g - st.x * sg) * st.y); u = bf16r((u - st.x * su) * st.y);
                const float inner = 0.7978845608028654f * (g + 0.044715f * g * g * g);
                const float th = 1.0f - __fdividef(2.0f, __expf(2.0f * inner) + 1.0f);
                const float ge = bf16r(0.5f * g * (1.0f + th));
                *reinterpret_cast<__nv_bfloat16*>(smem + OFF_ACT + b * 32 + c * 2) = __float2bfloat16_rn(ge * u);
            }
            if (!have_wd) {
                mbar_wait(bar_w + 32, 0); mbar_wait(bar_w + 40, 0);
#pragma unroll
                for (int i = 0; i < 4; i++) ldsm4t(df[i], wdb + (((2 * i + ((lane >> 3) & 1)) ^ (lane & 7)) << 4));
            }
        }
    }
    if (cta < NFFN) {
        bar_sync(6, 256);
        const uint32_t b0 = *reinterpret_cast<const uint32_t*>(smem + OFF_ACT + (r8 & 3) * 32 + q4 * 4);
        const uint32_t b1 = *reinterpret_cast<const uint32_t*>(smem + OFF_ACT + (r8 & 3) * 32 + 16 + q4 * 4);
        float c[4][4] = {};
#pragma unroll
        for (int i = 0; i < 4; i++) mma16816(c[i], df[i], b0, b1);
#pragma unroll
        for (int i = 0; i < 4; i++) {
            st_rel32(p_dpart + i * NFFN * 16, __float_as_uint(kh ? c[i][2] : c[i][0]));
            st_rel32(p_dpart + i * NFFN * 16 + 32 * NFFN * 16, __float_as_uint(kh ? c[i][3] : c[i][1]));
        }
    } else {
        bar_sync(6, 256);
        delay_cycles(DLY_F_IDLE);
    }

    {
        const int quad = tid & 3;
        const bool two = (tid >> 2) + 64 < NFFN;
        uint4 a, b = make_uint4(0, 0, 0, 0);
        Spin sp;
        delay_cycles(DLY_F);
        while (true) {
            a = ld_poll4(p_dsrc);
            if (two) b = ld_poll4(p_dsrc + 64 * 16);
            if (__all_sync(0xffffffffu, max(umax4(a), umax4(b)) != SENT)) break;
            sp.tick();
        }
        float v[4] = {__uint_as_float(a.x) + __uint_as_float(b.x), __uint_as_float(a.y) + __uint_as_float(b.y),
                      __uint_as_float(a.z) + __uint_as_float(b.z), __uint_as_float(a.w) + __uint_as_float(b.w)};
        {
            const bool up = lane & 16;
            const float s0 = up ? v[0] : v[2], s1 = up ? v[1] : v[3];
            const float k0 = up ? v[2] : v[0], k1 = up ? v[3] : v[1];
            v[0] = k0 + __shfl_xor_sync(0xffffffffu, s0, 16);
            v[1] = k1 + __shfl_xor_sync(0xffffffffu, s1, 16);
            const bool up2 = lane & 8;
            const float s = up2 ? v[0] : v[1], k = up2 ? v[1] : v[0];
            v[0] = k + __shfl_xor_sync(0xffffffffu, s, 8);
            v[0] += __shfl_xor_sync(0xffffffffu, v[0], 4);
            if (!(lane & 4)) reinterpret_cast<float*>(smem + OFF_RED2)[warp * 16 + 4 * quad + ((lane & 16) ? 2 : 0) + ((lane & 8) ? 1 : 0)] = v[0];
        }
        cbar();
        if (warp == 0) {
            const float* r2 = reinterpret_cast<const float*>(smem + OFF_RED2) + (lane & 1) * 64 + (lane >> 1);
            float s = (r2[0] + r2[16]) + (r2[32] + r2[48]);
            s += __shfl_xor_sync(0xffffffffu, s, 1);
            if (!(lane & 1)) *p_out = __float2bfloat16_rn(hres + bf16r(s));
            if (cta == 0 && lane == 0) st_rel32(&g_prog, 0u);
        }
    }
}

typedef CUresult (*EncodeFn)(CUtensorMap*, CUtensorMapDataType, cuuint32_t, void*, const cuuint64_t*, const cuuint64_t*,
                             const cuuint32_t*, const cuuint32_t*, CUtensorMapInterleave, CUtensorMapSwizzle,
                             CUtensorMapL2promotion, CUtensorMapFloatOOBfill);

void encode(EncodeFn fn, CUtensorMap* m, const void* base, int rank, const cuuint64_t* dims, const cuuint64_t* strides,
            const cuuint32_t* box, CUtensorMapSwizzle sw, CUtensorMapL2promotion promo) {
    cuuint32_t es[3] = {1, 1, 1};
    fn(m, CU_TENSOR_MAP_DATA_TYPE_BFLOAT16, (cuuint32_t)rank, const_cast<void*>(base), dims, strides, box, es,
       CU_TENSOR_MAP_INTERLEAVE_NONE, sw, promo, CU_TENSOR_MAP_FLOAT_OOB_FILL_NONE);
}

}

extern "C" void kernel_launch(void* const* d_in, const int* in_sizes, int n_in, void* d_out, int out_size) {
    (void)in_sizes; (void)n_in; (void)out_size;
    static EncodeFn enc = nullptr;
    if (!enc) {
        void* fn = nullptr;
        cudaDriverEntryPointQueryResult qr;
        cudaGetDriverEntryPoint("cuTensorMapEncodeTiled", &fn, cudaEnableDefault, &qr);
        enc = (EncodeFn)fn;
        cudaFuncSetAttribute(fused_decode_kernel, cudaFuncAttributeMaxDynamicSharedMemorySize, SMEM_BYTES);
    }
    const void* x = d_in[0];
    Maps maps;
    {
        cuuint64_t dims[3] = {64, 262144, 2}; cuuint64_t str[2] = {256, 128}; cuuint32_t box[3] = {64, 128, 2};
        encode(enc, &maps.m[0], d_in[1], 3, dims, str, box, CU_TENSOR_MAP_SWIZZLE_128B, CU_TENSOR_MAP_L2_PROMOTION_L2_256B);
        encode(enc, &maps.m[1], d_in[2], 3, dims, str, box, CU_TENSOR_MAP_SWIZZLE_128B, CU_TENSOR_MAP_L2_PROMOTION_L2_256B);
    }
    {
        cuuint64_t dims[3] = {4096, 512, 1}; cuuint64_t str[2] = {8192, 8192 * 512}; cuuint32_t box[3] = {32, 256, 1};
        encode(enc, &maps.m[2], d_in[3], 3, dims, str, box, CU_TENSOR_MAP_SWIZZLE_64B, CU_TENSOR_MAP_L2_PROMOTION_L2_128B);
    }
    {
        cuuint64_t dims[3] = {64, 4096, 8}; cuuint64_t str[2] = {1024, 128}; cuuint32_t box[3] = {64, 128, 2};
        encode(enc, &maps.m[3], d_in[4], 3, dims, str, box, CU_TENSOR_MAP_SWIZZLE_128B, CU_TENSOR_MAP_L2_PROMOTION_L2_256B);
    }
    {
        cuuint64_t dims[3] = {1792, 512, 1}; cuuint64_t str[2] = {3584, 3584 * 512}; cuuint32_t box[3] = {16, 256, 1};
        encode(enc, &maps.m[4], d_in[6], 3, dims, str, box, CU_TENSOR_MAP_SWIZZLE_32B, CU_TENSOR_MAP_L2_PROMOTION_L2_128B);
        encode(enc, &maps.m[5], d_in[7], 3, dims, str, box, CU_TENSOR_MAP_SWIZZLE_32B, CU_TENSOR_MAP_L2_PROMOTION_L2_128B);
    }
    {
        cuuint64_t dims[3] = {64, 1792, 8}; cuuint64_t str[2] = {1024, 128}; cuuint32_t box[3] = {64, 16, 4};
        encode(enc, &maps.m[6], d_in[8], 3, dims, str, box, CU_TENSOR_MAP_SWIZZLE_128B, CU_TENSOR_MAP_L2_PROMOTION_L2_256B);
    }
    fused_decode_kernel<<<NCTA, NTHREADS, SMEM_BYTES, cudaStreamPerThread>>>(maps, (const __nv_bfloat16*)x, (__nv_bfloat16*)d_out);
}
```
